```python
import torch

def _softmax(x, axis=-1):
    return torch.softmax(x, dim=axis)
def _gelu(x):
    return torch.nn.functional.gelu(x, approximate="tanh")
def _silu(x):
    return torch.nn.functional.silu(x)
def _sigmoid(x):
    return torch.sigmoid(x)
def _layernorm(x, axis=-1, eps=1e-5):
    m = x.mean(dim=axis, keepdim=True)
    v = x.var(dim=axis, keepdim=True, unbiased=False)
    return (x - m) / torch.sqrt(v + eps)
def _scatter_add(tgt, idx, src, axis=0):
    return tgt.clone().index_add_(axis, idx, src)
def _segment_sum(src, seg, n):
    out = torch.zeros((n,) + src.shape[1:], dtype=src.dtype)
    return out.index_add_(0, seg, src)
def _pad(x, pw):
    flat = tuple(v for pair in reversed(pw) for v in pair)
    return torch.nn.functional.pad(x, flat)

kernel_name = 'gated_mix__ssm_conv_s5__ssm_conv_h3__prompt'

def setup_inputs():

    _w = (lambda a: (lambda t: t.to(torch.bfloat16) if t.is_floating_point() else t)(torch.as_tensor(a)))
    def _A_setup():
        B, S, D = 1, 2048, 1024
        P = D
        Lambda_re = -0.5 * (lambda _x: torch.exp(torch.as_tensor(_x)))((lambda *s: torch.randn(*s, dtype=torch.bfloat16) * 0.2)(P))
        Lambda_im = (lambda *s: torch.randn(*s, dtype=torch.bfloat16) * 0.4)(P) * 1.0
        B_re = (lambda *s: torch.randn(*s, dtype=torch.bfloat16) * 0.2)(P, D) * (D ** -0.5)
        B_im = (lambda *s: torch.randn(*s, dtype=torch.bfloat16) * 0.2)(P, D) * (D ** -0.5)
        C_re = (lambda *s: torch.randn(*s, dtype=torch.bfloat16) * 0.2)(D, P) * (P ** -0.5)
        C_im = (lambda *s: torch.randn(*s, dtype=torch.bfloat16) * 0.2)(D, P) * (P ** -0.5)
        log_dt = (lambda *s: torch.randn(*s, dtype=torch.bfloat16) * 0.2)(P) * 0.3 - 2.0
        Dskip = (lambda *s: torch.randn(*s, dtype=torch.bfloat16) * 0.05)(D)
        return {
            "x": _w((lambda *s: torch.randn(*s, dtype=torch.bfloat16) * 0.05)(B, S, D)),
            "Lambda_re": _w(Lambda_re),
            "Lambda_im": _w(Lambda_im),
            "B_re": _w(B_re),
            "B_im": _w(B_im),
            "C_re": _w(C_re),
            "C_im": _w(C_im),
            "log_dt": _w(log_dt),
            "Dskip": _w(Dskip),
        }
    _A_in = _A_setup()

    def _B_setup():
        B, S, D = 1, 2048, 1024
        ks = 4
        return {
            "q": _w((lambda *s: torch.randn(*s, dtype=torch.bfloat16) * 0.05)(B, S, D)),
            "k": _w((lambda *s: torch.randn(*s, dtype=torch.bfloat16) * 0.4)(B, S, D)),
            "v": _w((lambda *s: torch.randn(*s, dtype=torch.bfloat16) * 0.2)(B, S, D)),
            "shift_k": _w((lambda *s: torch.randn(*s, dtype=torch.bfloat16) * 0.4)(D, ks) * 0.5),
            "ssm_k": _w((lambda *s: torch.randn(*s, dtype=torch.bfloat16) * 0.4)(D, S) * (1.0 / S ** 0.5)),
            "ssm_D": _w((lambda *s: torch.randn(*s, dtype=torch.bfloat16) * 0.2)(D)),
        }
    _B_in = _B_setup()

    return {
        "A_x": _A_in["x"],
        "A_Lambda_re": _A_in["Lambda_re"],
        "A_Lambda_im": _A_in["Lambda_im"],
        "A_B_re": _A_in["B_re"],
        "A_B_im": _A_in["B_im"],
        "A_C_re": _A_in["C_re"],
        "A_C_im": _A_in["C_im"],
        "A_log_dt": _A_in["log_dt"],
        "A_Dskip": _A_in["Dskip"],
        "B_q": _B_in["q"],
        "B_k": _B_in["k"],
        "B_v": _B_in["v"],
        "B_shift_k": _B_in["shift_k"],
        "B_ssm_k": _B_in["ssm_k"],
        "B_ssm_D": _B_in["ssm_D"],
        "gate_w": _w((lambda *s: torch.randn(*s, dtype=torch.bfloat16) * 0.05)(1024) * 16.0),
    }

def reference(A_x, A_Lambda_re, A_Lambda_im, A_B_re, A_B_im, A_C_re, A_C_im, A_log_dt, A_Dskip, B_q, B_k, B_v, B_shift_k, B_ssm_k, B_ssm_D, gate_w):
    def _A_ref(x, Lambda_re, Lambda_im, B_re, B_im, C_re, C_im, log_dt, Dskip):
        Bsz, L, H = x.shape
        Lam = Lambda_re + 1j * Lambda_im
        Bmat = B_re + 1j * B_im
        Cmat = C_re + 1j * C_im
        dt = torch.exp(log_dt)
        Lam_bar = torch.exp(dt * Lam)
        B_bar = ((Lam_bar - 1.0) / Lam)[:, None] * Bmat
        Bu = torch.einsum("bld,pd->blp", x + 0j, B_bar)
        h = torch.zeros_like(Bu[:, 0, :])
        hs = []
        for t in range(L):
            h = Lam_bar[None, :] * h + Bu[:, t, :]
            hs.append(h)
        hseq = torch.stack(hs, 1)
        y = 2.0 * torch.einsum("blp,dp->bld", hseq, Cmat).real + x * Dskip[None, None, :]
        return y

    def _B_ref(q, k, v, shift_k, ssm_k, ssm_D):
        B, S, D = q.shape
        ks = shift_k.shape[-1]
        k_pad = _pad(k, ((0, 0), (ks - 1, 0), (0, 0)))
        k_shift = torch.zeros_like(k)
        for t in range(ks):
            k_shift = k_shift + k_pad[:, t:t + S, :] * shift_k[:, ks - 1 - t][None, None, :]
        kv = k_shift * v
        L = 2 * S
        kv_pad = _pad(kv, ((0, 0), (0, S), (0, 0)))
        kf_pad = _pad(ssm_k, ((0, 0), (0, S)))
        kv_f = (lambda x, axes=(-2,-1): torch.fft.rfft2(x.float(), dim=axes))(kv_pad[:, None, :, :], axes=(1, 2))
        kf_f = (lambda x, axes=(-2,-1): torch.fft.rfft2(x.float(), dim=axes))(kf_pad[:, None, :], axes=(1, 2))
        kf_f = (lambda x, *d: x.permute(*d))(kf_f, 1, 2, 0)
        y_f = kv_f * kf_f[None, :, :, :]
        y = (lambda x, s, axes=(-2,-1): torch.fft.irfft2(x, s=s, dim=axes).to(torch.bfloat16))(y_f, (1, L), axes=(1, 2))[:, 0, :S, :]
        y = y + kv * ssm_D[None, None, :]
        return q * y

    x = A_x
    g = _sigmoid((x * gate_w).sum(-1, keepdims=True))
    a = _A_ref(x, A_Lambda_re, A_Lambda_im, A_B_re, A_B_im, A_C_re, A_C_im, A_log_dt, A_Dskip)
    b = _B_ref(x, B_k, B_v, B_shift_k, B_ssm_k, B_ssm_D)
    return g * a + (1 - g) * b
```

```cpp
#include <cuda_runtime.h>
#include <cuda_bf16.h>
#include <cuda.h>
#include <stdint.h>

namespace {

constexpr int SEQ = 2048, DM = 1024;
constexpr int NS = 5;
constexpr int STAGE = 32768;
#define NCH 8
constexpr int OFF_CONV = NS * STAGE;
constexpr int OFF_M1 = OFF_CONV + 32768;
constexpr int OFF_M2 = OFF_M1 + 4096;
constexpr int OFF_M2I = OFF_M2 + 2048;
constexpr int OFF_PAR = OFF_M2I + 2048;
constexpr int OFF_G = OFF_PAR + 2048;
constexpr int OFF_BAR = OFF_G + 512;
constexpr int SMEM_BYTES = OFF_BAR + 256;
constexpr uint32_t sb = 1024;
constexpr int SPIN_LIMIT = 1 << 21;

struct alignas(64) Maps { CUtensorMap x, bre, bim, cre, cim, f, z; };
struct Ptrs {
  const __nv_bfloat16 *x, *lre, *lim, *ldt, *dskip, *k, *v, *shift, *f, *ssmd, *gw, *bre, *bim, *cre, *cim;
  float* out;
};

__device__ uint4 g_h[16 * 32 * 1024];
__device__ uint4 g_u[1024 * 256];
__device__ uint4 g_z[1024 * 256];
__device__ float4 g_agg[2 * 16 * 512];
__device__ float g_gate[SEQ];
__device__ unsigned g_flag[64 * 32];
__device__ unsigned g_epoch[128];
#define TIM(i)

#define WG_FENCE() asm volatile("wgmma.fence.sync.aligned;" ::: "memory")
#define WG_COMMIT() asm volatile("wgmma.commit_group.sync.aligned;" ::: "memory")
#define WG_WAIT(n) asm volatile("wgmma.wait_group.sync.aligned %0;" ::"n"(n) : "memory")
#define R8(d, o) "+f"(d[o + 0]), "+f"(d[o + 1]), "+f"(d[o + 2]), "+f"(d[o + 3]), "+f"(d[o + 4]), "+f"(d[o + 5]), "+f"(d[o + 6]), "+f"(d[o + 7])
#define L16 "%0,%1,%2,%3,%4,%5,%6,%7,%8,%9,%10,%11,%12,%13,%14,%15"
#define L64 L16 ",%16,%17,%18,%19,%20,%21,%22,%23,%24,%25,%26,%27,%28,%29,%30,%31," \
  "%32,%33,%34,%35,%36,%37,%38,%39,%40,%41,%42,%43,%44,%45,%46,%47,%48,%49,%50,%51,%52,%53,%54,%55,%56,%57,%58,%59,%60,%61,%62,%63"

template <int TA>
__device__ __forceinline__ void wgmma_ss128(float (&d)[64], uint64_t da, uint64_t db) {
  asm volatile("wgmma.mma_async.sync.aligned.m64n128k16.f32.bf16.bf16 {" L64 "}, %64, %65, 1, 1, 1, %66, 0;"
               : R8(d, 0), R8(d, 8), R8(d, 16), R8(d, 24), R8(d, 32), R8(d, 40), R8(d, 48), R8(d, 56)
               : "l"(da), "l"(db), "n"(TA));
}
template <int ACC>
__device__ __forceinline__ void wgmma_rs128_tb(float (&d)[64], uint32_t a0, uint32_t a1, uint32_t a2, uint32_t a3, uint64_t db) {
  asm volatile("wgmma.mma_async.sync.aligned.m64n128k16.f32.bf16.bf16 {" L64 "}, {%64,%65,%66,%67}, %68, %69, 1, 1, 1;"
               : R8(d, 0), R8(d, 8), R8(d, 16), R8(d, 24), R8(d, 32), R8(d, 40), R8(d, 48), R8(d, 56)
               : "r"(a0), "r"(a1), "r"(a2), "r"(a3), "l"(db), "n"(ACC));
}
template <int ACC>
__device__ __forceinline__ void wgmma_rs32(float (&d)[16], uint32_t a0, uint32_t a1, uint32_t a2, uint32_t a3, uint64_t db) {
  asm volatile("wgmma.mma_async.sync.aligned.m64n32k16.f32.bf16.bf16 {" L16 "}, {%16,%17,%18,%19}, %20, %21, 1, 1, 0;"
               : R8(d, 0), R8(d, 8)
               : "r"(a0), "r"(a1), "r"(a2), "r"(a3), "l"(db), "n"(ACC));
}
template <int N>
__device__ __forceinline__ void reg_fence(float (&d)[N]) {
#pragma unroll
  for (int i = 0; i < N; i++) asm volatile("" : "+f"(d[i])::"memory");
}
__device__ __forceinline__ uint64_t mkdesc(uint32_t addr, uint32_t lbo, uint32_t sbo, uint32_t mode) {
  uint64_t d;
  asm("mov.b64 %0, {%1, %2};" : "=l"(d) : "r"((addr >> 4) + ((lbo >> 4) << 16)), "r"((sbo >> 4) | (mode << 30)));
  return d;
}
template <int N>
__device__ __forceinline__ void zero(float (&d)[N]) {
#pragma unroll
  for (int i = 0; i < N; i++) d[i] = 0.f;
}
__device__ __forceinline__ void trap_if(int c) {
  asm volatile("{.reg .pred p; .reg .b64 z; setp.ne.s32 p, %0, 0; mov.b64 z, 0; @p st.global.u32 [z], %0;}" ::"r"(c) : "memory");
}
__device__ __forceinline__ void mbar_init(uint32_t bar, uint32_t cnt) {
  asm volatile("mbarrier.init.shared::cta.b64 [%0], %1;" ::"r"(bar), "r"(cnt) : "memory");
}
__device__ __forceinline__ void mbar_wait(uint32_t bar, uint32_t par) {
  uint32_t ok;
  int n = 0;
  do {
    asm volatile("{.reg .pred p; mbarrier.try_wait.parity.shared::cta.b64 p, [%1], %2; selp.u32 %0, 1, 0, p;}"
                 : "=r"(ok) : "r"(bar), "r"(par) : "memory");
  } while (!ok && ++n < SPIN_LIMIT);
  trap_if(n >= SPIN_LIMIT);
}
__device__ __forceinline__ void mbar_arrive(uint32_t bar) {
  asm volatile("mbarrier.arrive.shared::cta.b64 _, [%0];" ::"r"(bar) : "memory");
}
__device__ __forceinline__ void mbar_expect(uint32_t bar, uint32_t bytes) {
  asm volatile("mbarrier.arrive.expect_tx.shared::cta.b64 _, [%0], %1;" ::"r"(bar), "r"(bytes) : "memory");
}
__device__ __forceinline__ void tma2d(uint32_t dst, const CUtensorMap* m, uint32_t bar, int c0, int c1) {
  asm volatile("cp.async.bulk.tensor.2d.shared::cluster.global.mbarrier::complete_tx::bytes [%0], [%1, {%3, %4}], [%2];"
               ::"r"(dst), "l"(m), "r"(bar), "r"(c0), "r"(c1) : "memory");
}
__device__ __forceinline__ void tma4d(uint32_t dst, const CUtensorMap* m, uint32_t bar, int c0, int c1, int c2, int c3) {
  asm volatile("cp.async.bulk.tensor.4d.shared::cluster.global.mbarrier::complete_tx::bytes [%0], [%1, {%3, %4, %5, %6}], [%2];"
               ::"r"(dst), "l"(m), "r"(bar), "r"(c0), "r"(c1), "r"(c2), "r"(c3) : "memory");
}
__device__ __forceinline__ void tma5d(uint32_t dst, const CUtensorMap* m, uint32_t bar, int c0, int c1, int c2, int c3, int c4) {
  asm volatile("cp.async.bulk.tensor.5d.shared::cluster.global.mbarrier::complete_tx::bytes [%0], [%1, {%3, %4, %5, %6, %7}], [%2];"
               ::"r"(dst), "l"(m), "r"(bar), "r"(c0), "r"(c1), "r"(c2), "r"(c3), "r"(c4) : "memory");
}
__device__ __forceinline__ void bulk_load(uint32_t dst, const void* src, uint32_t bytes, uint32_t bar) {
  asm volatile("cp.async.bulk.shared::cluster.global.mbarrier::complete_tx::bytes [%0], [%1], %2, [%3];"
               ::"r"(dst), "l"(src), "r"(bytes), "r"(bar) : "memory");
}
__device__ __forceinline__ void l2_prefetch(const void* src, uint32_t bytes) {
  asm volatile("cp.async.bulk.prefetch.L2.global [%0], %1;" ::"l"(src), "r"(bytes) : "memory");
}
__device__ __forceinline__ void bar_sync(int id, int n) { asm volatile("bar.sync %0, %1;" ::"r"(id), "r"(n) : "memory"); }
__device__ __forceinline__ void bar_arrive(int id, int n) { asm volatile("bar.arrive %0, %1;" ::"r"(id), "r"(n) : "memory"); }
__device__ __forceinline__ void flag_signal(unsigned* f) {
  asm volatile("fence.acq_rel.gpu;" ::: "memory");
  asm volatile("red.relaxed.gpu.global.add.u32 [%0], 1;" ::"l"(f) : "memory");
}
__device__ __forceinline__ void flag_wait(const unsigned* f, unsigned target) {
  unsigned v;
  int n = 0;
  do {
    asm volatile("ld.acquire.gpu.global.u32 %0, [%1];" : "=r"(v) : "l"(f) : "memory");
  } while ((int)(v - target) < 0 && ++n < SPIN_LIMIT);
  trap_if(n >= SPIN_LIMIT);
}
__device__ __forceinline__ uint32_t pack2(float lo, float hi) {
  uint32_t r;
  asm("cvt.rn.bf16x2.f32 %0, %1, %2;" : "=r"(r) : "f"(hi), "f"(lo));
  return r;
}
__device__ __forceinline__ float bf_lo(uint32_t v) { return __uint_as_float(v << 16); }
__device__ __forceinline__ float bf_hi(uint32_t v) { return __uint_as_float(v & 0xffff0000u); }
__device__ __forceinline__ float bf_round(float v) { return __bfloat162float(__float2bfloat16_rn(v)); }
__device__ __forceinline__ uint32_t hmul2(uint32_t a, uint32_t b) {
  uint32_t r;
  asm("mul.rn.bf16x2 %0, %1, %2;" : "=r"(r) : "r"(a), "r"(b));
  return r;
}
__device__ __forceinline__ uint32_t hadd2(uint32_t a, uint32_t b) {
  uint32_t r;
  asm("add.rn.bf16x2 %0, %1, %2;" : "=r"(r) : "r"(a), "r"(b));
  return r;
}
__device__ __forceinline__ uint4 ldg128(const void* p) {
  uint4 v;
  asm volatile("ld.global.nc.v4.u32 {%0,%1,%2,%3}, [%4];" : "=r"(v.x), "=r"(v.y), "=r"(v.z), "=r"(v.w) : "l"(p));
  return v;
}
__device__ __forceinline__ uint2 ldg64(const void* p) {
  uint2 v;
  asm volatile("ld.global.nc.v2.u32 {%0,%1}, [%2];" : "=r"(v.x), "=r"(v.y) : "l"(p));
  return v;
}
__device__ __forceinline__ void stg128(void* p, uint32_t a, uint32_t b, uint32_t c, uint32_t d) {
  asm volatile("st.global.v4.u32 [%0], {%1,%2,%3,%4};" ::"l"(p), "r"(a), "r"(b), "r"(c), "r"(d) : "memory");
}
__device__ __forceinline__ void sts128(uint32_t a, uint32_t x, uint32_t y, uint32_t z, uint32_t w) {
  asm volatile("st.shared.v4.u32 [%0], {%1,%2,%3,%4};" ::"r"(a), "r"(x), "r"(y), "r"(z), "r"(w) : "memory");
}
__device__ __forceinline__ uint4 lds128(uint32_t a) {
  uint4 v;
  asm volatile("ld.shared.v4.u32 {%0,%1,%2,%3}, [%4];" : "=r"(v.x), "=r"(v.y), "=r"(v.z), "=r"(v.w) : "r"(a) : "memory");
  return v;
}
__device__ __forceinline__ void stsm4(uint32_t a, uint32_t x, uint32_t y, uint32_t z, uint32_t w) {
  asm volatile("stmatrix.sync.aligned.m8n8.x4.shared.b16 [%0], {%1,%2,%3,%4};" ::"r"(a), "r"(x), "r"(y), "r"(z), "r"(w) : "memory");
}
__device__ __forceinline__ void stsm4t(uint32_t a, uint32_t x, uint32_t y, uint32_t z, uint32_t w) {
  asm volatile("stmatrix.sync.aligned.m8n8.x4.trans.shared.b16 [%0], {%1,%2,%3,%4};" ::"r"(a), "r"(x), "r"(y), "r"(z), "r"(w) : "memory");
}
__device__ __forceinline__ uint4 ldsm4t(uint32_t a) {
  uint4 v;
  asm volatile("ldmatrix.sync.aligned.m8n8.x4.trans.shared.b16 {%0,%1,%2,%3}, [%4];" : "=r"(v.x), "=r"(v.y), "=r"(v.z), "=r"(v.w) : "r"(a) : "memory");
  return v;
}
struct cx { float r, i; };
__device__ __forceinline__ cx cmul(cx a, cx b) { return {a.r * b.r - a.i * b.i, a.r * b.i + a.i * b.r}; }
__device__ __forceinline__ cx cfma(cx a, cx b, cx c) { return {fmaf(a.r, b.r, fmaf(-a.i, b.i, c.r)), fmaf(a.r, b.i, fmaf(a.i, b.r, c.i))}; }
__device__ __forceinline__ cx csq(cx a) { return {a.r * a.r - a.i * a.i, 2.f * a.r * a.i}; }
__device__ __forceinline__ cx unit(int num, int den) {
  int m = num & (den - 1);
  if (m >= den / 2) m -= den;
  float s, c;
  __sincosf((float)m * (-6.283185307179586f / (float)den), &s, &c);
  return {c, s};
}

__device__ __forceinline__ void prep(const Ptrs& p, int ti, int pj, int pw, int lane) {
  {
    const int t = ti * 128 + pj * 16 + pw * 2;
    uint4 xa[4], xb[4], gw[4];
#pragma unroll
    for (int i = 0; i < 4; i++) {
      xa[i] = ldg128(p.x + (size_t)t * DM + i * 256 + lane * 8);
      xb[i] = ldg128(p.x + (size_t)(t + 1) * DM + i * 256 + lane * 8);
      gw[i] = ldg128(p.gw + i * 256 + lane * 8);
    }
    float sa = 0.f, sb = 0.f;
#pragma unroll
    for (int i = 0; i < 4; i++) {
      const uint32_t* a = &xa[i].x; const uint32_t* b = &xb[i].x; const uint32_t* w = &gw[i].x;
#pragma unroll
      for (int j = 0; j < 4; j++) {
        uint32_t pa = hmul2(a[j], w[j]), pb = hmul2(b[j], w[j]);
        sa += bf_lo(pa) + bf_hi(pa);
        sb += bf_lo(pb) + bf_hi(pb);
      }
    }
#pragma unroll
    for (int o = 16; o > 0; o >>= 1) { sa += __shfl_xor_sync(~0u, sa, o); sb += __shfl_xor_sync(~0u, sb, o); }
    if (lane < 2) {
      float l = bf_round(lane ? sb : sa);
      g_gate[t + lane] = bf_round(1.f / (1.f + expf(-l)));
    }
  }
  const int t0 = ti * 128 + (pw >> 2) * 64 + (lane >> 2) * 8;
  const int d0 = pj * 128 + (pw & 3) * 32 + (lane & 3) * 8;
  uint4 kk[11], vv[8], sh[4];
#pragma unroll
  for (int i = 0; i < 4; i++) sh[i] = ldg128(p.shift + d0 * 4 + i * 8);
#pragma unroll
  for (int i = 0; i < 11; i++) {
    int t = t0 - 3 + i;
    kk[i] = make_uint4(0, 0, 0, 0);
    if (t >= 0) kk[i] = ldg128(p.k + (size_t)t * DM + d0);
  }
#pragma unroll
  for (int i = 0; i < 8; i++) vv[i] = ldg128(p.v + (size_t)(t0 + i) * DM + d0);
  const int q = t0 >> 3;
  uint4* dst = g_u + (size_t)d0 * 256 + (q ^ ((q >> 3) & 1));
#pragma unroll
  for (int e = 0; e < 4; e++) {
    uint32_t s0 = __byte_perm(sh[e].x, sh[e].z, 0x5410), s1 = __byte_perm(sh[e].x, sh[e].z, 0x7632);
    uint32_t s2 = __byte_perm(sh[e].y, sh[e].w, 0x5410), s3 = __byte_perm(sh[e].y, sh[e].w, 0x7632);
    uint32_t u[8];
#pragma unroll
    for (int i = 0; i < 8; i++) {
      uint32_t a = hmul2((&kk[i].x)[e], s3);
      a = hadd2(a, hmul2((&kk[i + 1].x)[e], s2));
      a = hadd2(a, hmul2((&kk[i + 2].x)[e], s1));
      a = hadd2(a, hmul2((&kk[i + 3].x)[e], s0));
      u[i] = hmul2(a, (&vv[i].x)[e]);
    }
    stg128(dst + (2 * e) * 256, __byte_perm(u[0], u[1], 0x5410), __byte_perm(u[2], u[3], 0x5410),
           __byte_perm(u[4], u[5], 0x5410), __byte_perm(u[6], u[7], 0x5410));
    stg128(dst + (2 * e + 1) * 256, __byte_perm(u[0], u[1], 0x7632), __byte_perm(u[2], u[3], 0x7632),
           __byte_perm(u[4], u[5], 0x7632), __byte_perm(u[6], u[7], 0x7632));
  }
}

__device__ __forceinline__ void conv_tables(int tid) {
  {
    const int s = tid >> 5, n1 = tid & 31;
    uint32_t re[4], im[4];
#pragma unroll
    for (int e = 0; e < 4; e++) {
      cx a = unit(n1 * (4 * (8 * s + 2 * e) + 1), 128), b = unit(n1 * (4 * (8 * s + 2 * e + 1) + 1), 128);
      re[e] = pack2(a.r, b.r); im[e] = pack2(a.i, b.i);
    }
    sts128(sb + OFF_M1 + (2 * s) * 512 + n1 * 16, re[0], re[1], re[2], re[3]);
    sts128(sb + OFF_M1 + (2 * s + 1) * 512 + n1 * 16, im[0], im[1], im[2], im[3]);
  }
  {
    const int kg = tid >> 5, n = tid & 31;
    const int pi = kg >> 1, po = n >> 4, f2 = n & 15;
    uint32_t fw[4], iv[4];
#pragma unroll
    for (int e = 0; e < 4; e++) {
      int n2 = (kg & 1) * 8 + 2 * e;
      cx a = unit(n2 * f2, 16), b = unit((n2 + 1) * f2, 16);
      float sg = pi ? -1.f : 1.f;
      float x0 = (pi == po) ? a.r : sg * a.i, x1 = (pi == po) ? b.r : sg * b.i;
      float y0 = (pi == po) ? a.r : -sg * a.i, y1 = (pi == po) ? b.r : -sg * b.i;
      fw[e] = pack2(x0, x1); iv[e] = pack2(y0, y1);
    }
    sts128(sb + OFF_M2 + kg * 512 + n * 16, fw[0], fw[1], fw[2], fw[3]);
    sts128(sb + OFF_M2I + kg * 512 + n * 16, iv[0], iv[1], iv[2], iv[3]);
  }
  asm volatile("fence.proxy.async.shared::cta;" ::: "memory");
}

__device__ __forceinline__ void conv_issue(const Maps& m, int d, int buf) {
  const uint32_t bar = sb + OFF_BAR + 8 * (2 * NS + buf);
  const uint32_t dst = sb + OFF_CONV + buf * 8192;
  mbar_expect(bar, 8192);
  bulk_load(dst, g_u + (size_t)d * 256, 4096, bar);
  tma2d(dst + 4096, &m.f, bar, 0, d * 128);
}

__device__ __forceinline__ void conv_main(const Maps& m, const Ptrs& p, int ti, int pj, int tid, unsigned ep) {
  const int w = tid >> 5, lane = tid & 31, r = lane >> 2, c = lane & 3;
  const int f1 = 8 * w + r;
  const int dbase = pj * 128 + ti * 8;
  uint32_t wa[8];
#pragma unroll
  for (int s = 0; s < 2; s++)
#pragma unroll
    for (int h = 0; h < 2; h++) {
      int n1 = 16 * s + 8 * h + 2 * c;
      cx a = unit(n1 * (4 * f1 + 1), 128), b = unit((n1 + 1) * (4 * f1 + 1), 128);
      wa[4 * s + 2 * h] = pack2(a.r, b.r);
      wa[4 * s + 2 * h + 1] = pack2(a.i, b.i);
    }
  cx tw[4];
#pragma unroll
  for (int i = 0; i < 4; i++) tw[i] = unit((8 * (i >> 1) + 2 * c + (i & 1)) * (4 * f1 + 1), 2048);
  const uint4 dsk = ldg128(p.ssmd + dbase);

  if (tid == 0) {
    flag_wait(g_flag + pj * 32, (ep + 1) * 16);
    asm volatile("fence.proxy.async.global;" ::: "memory");
    conv_issue(m, dbase, 0);
    conv_issue(m, dbase + 1, 1);
  }
  TIM(20);
#define CDESC(off) mkdesc(sb + (off), 512, 128, 0)

#pragma unroll 1
  for (int ch = 0; ch < NCH; ch++) {
    const int buf = ch & 1;
    mbar_wait(sb + OFF_BAR + 8 * (2 * NS + buf), (ch >> 1) & 1);
    uint32_t R[8][2], I[8][2];
    {
      float d[64];
      const uint32_t in = sb + OFF_CONV + buf * 8192;
      WG_FENCE();
      wgmma_rs128_tb<0>(d, wa[0], wa[1], wa[2], wa[3], mkdesc(in, 1024, 256, 3));
      wgmma_rs128_tb<1>(d, wa[4], wa[5], wa[6], wa[7], mkdesc(in + 512, 1024, 256, 3));
      WG_COMMIT();
      WG_WAIT(0);
      reg_fence(d);
#pragma unroll
      for (int j = 0; j < 16; j++) {
        cx a = cmul({d[4 * j], d[4 * j + 2]}, tw[2 * (j & 1)]);
        cx b = cmul({d[4 * j + 1], d[4 * j + 3]}, tw[2 * (j & 1) + 1]);
        R[j >> 1][j & 1] = pack2(a.r, b.r);
        I[j >> 1][j & 1] = pack2(a.i, b.i);
      }
    }
    uint32_t QR[4][2], QI[4][2];
    {
      float X[4][16];
      WG_FENCE();
#pragma unroll
      for (int q = 0; q < 4; q++) {
        wgmma_rs32<0>(X[q], R[2 * q][0], R[2 * q + 1][0], R[2 * q][1], R[2 * q + 1][1], CDESC(OFF_M2));
        wgmma_rs32<1>(X[q], I[2 * q][0], I[2 * q + 1][0], I[2 * q][1], I[2 * q + 1][1], CDESC(OFF_M2 + 1024));
      }
      WG_COMMIT();
      uint32_t dw = ch < 4 ? (ch < 2 ? dsk.x : dsk.y) : (ch < 6 ? dsk.z : dsk.w);
      const float dval = (ch & 1) ? bf_hi(dw) : bf_lo(dw);
      WG_WAIT(0);
#pragma unroll
      for (int q = 0; q < 4; q++) reg_fence(X[q]);
#pragma unroll
      for (int hh = 0; hh < 2; hh++) {
        cx Q[2][4];
#pragma unroll
        for (int b = 0; b < 2; b++) {
          cx U[4], K[4];
#pragma unroll
          for (int k = 0; k < 4; k++) {
            U[k] = {X[k >> 1][4 * hh + 2 * (k & 1) + b], X[k >> 1][8 + 4 * hh + 2 * (k & 1) + b]};
            K[k] = {X[2 + (k >> 1)][4 * hh + 2 * (k & 1) + b], X[2 + (k >> 1)][8 + 4 * hh + 2 * (k & 1) + b]};
          }
          K[0].r += dval;
#pragma unroll
          for (int k = 3; k > 0; k--) U[k] = {U[k].r - U[k - 1].i, U[k].i + U[k - 1].r};
#pragma unroll
          for (int j = 0; j < 4; j++) {
            cx a = cmul(K[0], U[j]);
#pragma unroll
            for (int k = 1; k <= j; k++) a = cfma(K[k], U[j - k], a);
            Q[b][j] = a;
          }
        }
#pragma unroll
        for (int j = 0; j < 4; j++) { QR[j][hh] = pack2(Q[0][j].r, Q[1][j].r); QI[j][hh] = pack2(Q[0][j].i, Q[1][j].i); }
      }
    }
    const uint32_t T = sb + OFF_CONV + 16384 + buf * 8192;
    {
      float Z[2][16];
      WG_FENCE();
#pragma unroll
      for (int q = 0; q < 2; q++) {
        wgmma_rs32<0>(Z[q], QR[2 * q][0], QR[2 * q + 1][0], QR[2 * q][1], QR[2 * q + 1][1], CDESC(OFF_M2I));
        wgmma_rs32<1>(Z[q], QI[2 * q][0], QI[2 * q + 1][0], QI[2 * q][1], QI[2 * q + 1][1], CDESC(OFF_M2I + 1024));
      }
      WG_COMMIT();
      WG_WAIT(0);
      reg_fence(Z[0]); reg_fence(Z[1]);
#pragma unroll
      for (int k = 0; k < 4; k++) {
        uint32_t zr[2], zi[2];
#pragma unroll
        for (int hh = 0; hh < 2; hh++) {
          cx a = cmul({Z[k >> 1][4 * hh + 2 * (k & 1)], Z[k >> 1][8 + 4 * hh + 2 * (k & 1)]}, {tw[2 * hh].r, -tw[2 * hh].i});
          cx b = cmul({Z[k >> 1][4 * hh + 2 * (k & 1) + 1], Z[k >> 1][8 + 4 * hh + 2 * (k & 1) + 1]}, {tw[2 * hh + 1].r, -tw[2 * hh + 1].i});
          zr[hh] = pack2(a.r, b.r); zi[hh] = pack2(a.i, b.i);
        }
        stsm4(T + (4 * k + w) * 512 + lane * 16, zr[0], zr[1], zi[0], zi[1]);
      }
    }
    bar_sync(3, 128);
    if (tid == 0 && ch + 2 < NCH) conv_issue(m, dbase + ch + 2, buf);
    {
      uint4 a[4];
#pragma unroll
      for (int s = 0; s < 4; s++) a[s] = ldsm4t(T + (4 * w + s) * 512 + lane * 16);
      float Y[16];
      WG_FENCE();
      wgmma_rs32<0>(Y, a[0].x, a[0].y, a[0].z, a[0].w, CDESC(OFF_M1));
      wgmma_rs32<1>(Y, a[1].x, a[1].y, a[1].z, a[1].w, CDESC(OFF_M1 + 1024));
      wgmma_rs32<1>(Y, a[2].x, a[2].y, a[2].z, a[2].w, CDESC(OFF_M1 + 2048));
      wgmma_rs32<1>(Y, a[3].x, a[3].y, a[3].z, a[3].w, CDESC(OFF_M1 + 3072));
      WG_COMMIT();
      WG_WAIT(0);
      reg_fence(Y);
      const float sc = 1.f / 512.f;
      const uint32_t Zs = T + w * 2048;
      const uint32_t za = Zs + (lane >> 4) * 256 + (lane & 7) * 32 + ((lane >> 3) & 1) * 16;
#pragma unroll
      for (int jj = 0; jj < 2; jj++)
        stsm4t(za + jj * 512, pack2(Y[8 * jj] * sc, Y[8 * jj + 1] * sc), pack2(Y[8 * jj + 2] * sc, Y[8 * jj + 3] * sc),
               pack2(Y[8 * jj + 4] * sc, Y[8 * jj + 5] * sc), pack2(Y[8 * jj + 6] * sc, Y[8 * jj + 7] * sc));
      __syncwarp();
      uint4 v0 = lds128(Zs + lane * 16), v1 = lds128(Zs + 512 + lane * 16);
      uint4* zp = g_z + (size_t)(dbase + ch) * 256 + w * 64 + lane;
      stg128(zp, v0.x, v0.y, v0.z, v0.w);
      stg128(zp + 32, v1.x, v1.y, v1.z, v1.w);
    }
    if (ch == 0) TIM(21);
  }
  bar_sync(3, 128);
  if (tid == 0) flag_signal(g_flag + (8 + pj) * 32);
  TIM(22);
}

__device__ __forceinline__ cx shfl_up_cx(cx a, int o) { return {__shfl_up_sync(~0u, a.r, o, 4), __shfl_up_sync(~0u, a.i, o, 4)}; }

__device__ __forceinline__ void scan_epilogue(float (&aR)[64], float (&aI)[64], int ph, int ti, int pj, int tid, unsigned ep) {
  const int w = tid >> 5, lane = tid & 31, r = lane >> 2, c = lane & 3;
  const float tag = __uint_as_float(ep + 1);
  cx lam[2], h[2];
  {
    cx cf[2];
#pragma unroll
    for (int q = 0; q < 2; q++) {
      uint4 v = lds128(sb + OFF_PAR + (ph * 64 + 16 * w + 8 * q + r) * 16);
      lam[q] = {__uint_as_float(v.x), __uint_as_float(v.y)};
      cf[q] = {__uint_as_float(v.z), __uint_as_float(v.w)};
      h[q] = {0.f, 0.f};
    }
#pragma unroll
    for (int s = 0; s < 32; s++)
#pragma unroll
      for (int q = 0; q < 2; q++) {
        const int i = 4 * (s >> 1) + 2 * q + (s & 1);
        cx u = cmul(cf[q], {aR[i], -aI[i]});
        aR[i] = u.r; aI[i] = u.i;
        h[q] = cfma(lam[q], h[q], u);
      }
  }
  float4* agg = g_agg + (size_t)ph * 16 * 512 + pj * 64 + 16 * w + r;
#pragma unroll
  for (int q = 0; q < 2; q++) {
    cx l32 = csq(csq(csq(csq(csq(lam[q]))))), l64 = csq(l32);
    cx a = h[q], t = shfl_up_cx(a, 1);
    if (c >= 1) a = cfma(l32, t, a);
    t = shfl_up_cx(a, 2);
    if (c >= 2) a = cfma(l64, t, a);
    if (c == 3) asm volatile("st.relaxed.gpu.global.v4.f32 [%0], {%1,%2,%3,%3};" ::"l"(agg + ti * 512 + 8 * q), "f"(a.r), "f"(a.i), "f"(tag) : "memory");
    t = shfl_up_cx(a, 1);
    h[q] = c ? t : cx{0.f, 0.f};
  }
  TIM(8 + ph * 4);
  if (ti > 0) {
#pragma unroll
    for (int q = 0; q < 2; q++) {
      cx l32 = csq(csq(csq(csq(csq(lam[q]))))), l64 = csq(l32), l128 = csq(l64), l256 = csq(l128), l512 = csq(l256);
      float4 v[4];
      int n = 0;
      bool ok;
      do {
        ok = true;
#pragma unroll
        for (int j = 0; j < 4; j++) {
          const int tj = ti - 1 - c - 4 * j;
          v[j] = make_float4(0.f, 0.f, tag, tag);
          if (tj >= 0)
            asm volatile("ld.relaxed.gpu.global.v4.f32 {%0,%1,%2,%3}, [%4];" : "=f"(v[j].x), "=f"(v[j].y), "=f"(v[j].z), "=f"(v[j].w) : "l"(agg + tj * 512 + 8 * q) : "memory");
        }
#pragma unroll
        for (int j = 0; j < 4; j++) ok = ok && (__float_as_uint(v[j].z) == ep + 1);
      } while (!ok && ++n < SPIN_LIMIT);
      trap_if(n >= SPIN_LIMIT);
      __syncwarp();
      cx a = {v[3].x, v[3].y};
      a = cfma(l512, a, {v[2].x, v[2].y});
      a = cfma(l512, a, {v[1].x, v[1].y});
      a = cfma(l512, a, {v[0].x, v[0].y});
      if (c & 1) a = cmul(a, l128);
      if (c & 2) a = cmul(a, l256);
      a.r += __shfl_xor_sync(~0u, a.r, 1); a.i += __shfl_xor_sync(~0u, a.i, 1);
      a.r += __shfl_xor_sync(~0u, a.r, 2); a.i += __shfl_xor_sync(~0u, a.i, 2);
      if (c & 1) a = cmul(a, l32);
      if (c & 2) a = cmul(a, l64);
      h[q].r += a.r; h[q].i += a.i;
    }
  }
  TIM(9 + ph * 4);
  uint4* hp = g_h + (size_t)(ti * 32 + ph * 16 + pj * 2) * 1024 + (2 * w) * 128 + (4 * c) * 8 + r;
#pragma unroll
  for (int i = 0; i < 4; i++) {
    uint32_t pr[2][4], pi[2][4];
#pragma unroll
    for (int s2 = 0; s2 < 4; s2++)
#pragma unroll
      for (int q = 0; q < 2; q++) {
        const int k = 4 * (4 * i + s2) + 2 * q;
        cx h0 = cfma(lam[q], h[q], {aR[k], aI[k]});
        h[q] = cfma(lam[q], h0, {aR[k + 1], aI[k + 1]});
        pr[q][s2] = pack2(h0.r, h[q].r);
        pi[q][s2] = pack2(h0.i, h[q].i);
      }
#pragma unroll
    for (int q = 0; q < 2; q++) {
      stg128(hp + q * 128 + i * 8, pr[q][0], pr[q][1], pr[q][2], pr[q][3]);
      stg128(hp + 1024 + q * 128 + i * 8, pi[q][0], pi[q][1], pi[q][2], pi[q][3]);
    }
  }
  bar_sync(1 + ph, 128);
  TIM(10 + ph * 4);
  if (tid == 0) flag_signal(g_flag + (16 + ph * 16 + ti) * 32);
  TIM(11 + ph * 4);
}

__device__ __forceinline__ void eterm(const Maps& m, const Ptrs& p, int ti, int pj, int tid, unsigned ep) {
  const int w = tid >> 5, lane = tid & 31, r = lane >> 2, c = lane & 3;
  const uint32_t zbar = sb + OFF_BAR + 8 * (2 * NS + 2);
  const uint32_t zt = sb + OFF_CONV;
  uint2 xv[2][8][2], ds[8];
  const __nv_bfloat16* xp = p.x + (size_t)(ti * 128 + 16 * w + r) * DM + pj * 128 + 4 * c;
#pragma unroll
  for (int jj = 0; jj < 8; jj++) {
    ds[jj] = ldg64(p.dskip + pj * 128 + 16 * jj + 4 * c);
#pragma unroll
    for (int mh = 0; mh < 2; mh++)
#pragma unroll
      for (int hf = 0; hf < 2; hf++) xv[mh][jj][hf] = ldg64(xp + (64 * mh + 8 * hf) * DM + 16 * jj);
  }
  if (tid == 0) {
    flag_wait(g_flag + (32 + ti) * 32, (ep + 1) * 8);
    flag_wait(g_flag + (8 + pj) * 32, (ep + 1) * 16);
    asm volatile("fence.proxy.async;" ::: "memory");
    mbar_expect(zbar, 32768);
    tma2d(zt, &m.z, zbar, ti * 128, pj * 128);
    tma2d(zt + 16384, &m.z, zbar, ti * 128 + 64, pj * 128);
  }
  bar_sync(2, 128);
  TIM(16);
  float g[2][2];
#pragma unroll
  for (int mh = 0; mh < 2; mh++)
#pragma unroll
    for (int hf = 0; hf < 2; hf++) g[mh][hf] = __ldcg(g_gate + ti * 128 + 64 * mh + 16 * w + 8 * hf + r);
  {
    float gs = __ldcg(g_gate + ti * 128 + tid);
    asm volatile("st.shared.f32 [%0], %1;" ::"r"(sb + OFF_G + tid * 4), "f"(gs) : "memory");
  }
  mbar_wait(zbar, 0);
  const int dl = 4 * ((lane & 7) >> 1) + (lane & 1) + 2 * ((lane >> 3) & 1);
  const uint32_t za = zt + dl * 128 + (((2 * w + (lane >> 4)) ^ (dl & 7)) << 4);
#pragma unroll
  for (int mh = 0; mh < 2; mh++)
#pragma unroll
    for (int jj = 0; jj < 8; jj++) {
      uint4 z = ldsm4t(za + mh * 16384 + jj * 2048);
#pragma unroll
      for (int hf = 0; hf < 2; hf++) {
        const float gg = g[mh][hf], og = bf_round(1.f - gg);
        const uint32_t z0 = hf ? z.z : z.x, z1 = hf ? z.w : z.y;
        uint2& x = xv[mh][jj][hf];
        float e0 = bf_lo(x.x) * fmaf(og, bf_lo(z0), gg * bf_lo(ds[jj].x));
        float e1 = bf_hi(x.x) * fmaf(og, bf_hi(z0), gg * bf_hi(ds[jj].x));
        float e2 = bf_lo(x.y) * fmaf(og, bf_lo(z1), gg * bf_lo(ds[jj].y));
        float e3 = bf_hi(x.y) * fmaf(og, bf_hi(z1), gg * bf_hi(ds[jj].y));
        x.x = pack2(e0, e1); x.y = pack2(e2, e3);
      }
    }
  bar_sync(2, 128);
#pragma unroll
  for (int mh = 0; mh < 2; mh++)
#pragma unroll
    for (int jj = 0; jj < 8; jj++)
      sts128(zt + (mh * 8 + jj) * 2048 + tid * 16, xv[mh][jj][0].x, xv[mh][jj][0].y, xv[mh][jj][1].x, xv[mh][jj][1].y);
  bar_arrive(5, 256);
  TIM(17);
}

__device__ __forceinline__ void store_half(float (&a)[64], float* op, uint32_t ea, float g0, float g1) {
#pragma unroll
  for (int jj = 0; jj < 8; jj++) {
    uint4 e = lds128(ea + jj * 2048);
    stg128(op + 16 * jj, __float_as_uint(fmaf(g0, a[8 * jj], bf_lo(e.x))), __float_as_uint(fmaf(g0, a[8 * jj + 1], bf_hi(e.x))),
           __float_as_uint(fmaf(g0, a[8 * jj + 4], bf_lo(e.y))), __float_as_uint(fmaf(g0, a[8 * jj + 5], bf_hi(e.y))));
    stg128(op + 8 * DM + 16 * jj, __float_as_uint(fmaf(g1, a[8 * jj + 2], bf_lo(e.z))), __float_as_uint(fmaf(g1, a[8 * jj + 3], bf_hi(e.z))),
           __float_as_uint(fmaf(g1, a[8 * jj + 6], bf_lo(e.w))), __float_as_uint(fmaf(g1, a[8 * jj + 7], bf_hi(e.w))));
  }
}

__global__ void __launch_bounds__(512, 1) fused_kernel(const __grid_constant__ Maps m, const __grid_constant__ Ptrs p) {
  extern __shared__ __align__(1024) uint8_t smem_raw[];
  const int b = blockIdx.x;
  const int ti = ((b >> 5) << 2) | (b & 3), pj = (((b >> 4) & 1) << 2) | ((b >> 2) & 3);
  const int wg = __shfl_sync(~0u, threadIdx.x >> 7, 0), tid = threadIdx.x & 127;
  const uint32_t fullb = sb + OFF_BAR, emptyb = fullb + 8 * NS;
  if (wg == 0) TIM(0);
  if (threadIdx.x == 384) {
    trap_if((uint32_t)__cvta_generic_to_shared(smem_raw) != sb);
    asm volatile("prefetch.tensormap [%0];" ::"l"(&m.x) : "memory");
    asm volatile("prefetch.tensormap [%0];" ::"l"(&m.bre) : "memory");
    asm volatile("prefetch.tensormap [%0];" ::"l"(&m.bim) : "memory");
#pragma unroll
    for (int i = 0; i < NS; i++) { mbar_init(fullb + 8 * i, 1); mbar_init(emptyb + 8 * i, 4); }
#pragma unroll
    for (int i = 0; i < 3; i++) mbar_init(fullb + 8 * (2 * NS + i), 1);
    asm volatile("fence.proxy.async.shared::cta;" ::: "memory");
  }
  const unsigned ep = __ldcg(g_epoch + b);
  __syncthreads();

  if (wg == 3) {
    asm volatile("setmaxnreg.dec.sync.aligned.u32 32;");
    if (tid == 0) {
      int sl = 0, par = 1;
#pragma unroll 1
      for (int s = 0; s < 64; s++) {
        if (s == 32 || s == 48) {
          flag_wait(g_flag + (s - 16 + ti) * 32, (ep + 1) * 8);
          asm volatile("fence.proxy.async.global;" ::: "memory");
          TIM(24 + (s >> 4) - 2);
        }
        mbar_wait(emptyb + 8 * sl, par);
        const uint32_t bar = fullb + 8 * sl, dst = sb + sl * STAGE;
        mbar_expect(bar, STAGE);
        if (s < 32) {
          const int k0 = (s & 15) * 64, ch = (s >> 4) * 512 + pj * 64;
          tma4d(dst + 16384, &m.x, bar, k0, 0, 4 * ti, 0);
          tma2d(dst, &m.bre, bar, k0, ch);
          tma2d(dst + 8192, &m.bim, bar, k0, ch);
        } else {
          bulk_load(dst, g_h + (size_t)(ti * 32 + s - 32) * 1024, 16384, bar);
          tma5d(dst + 16384, (s & 1) ? &m.cim : &m.cre, bar, ((s - 32) >> 1) * 64, 0, 0, 0, pj * 8);
        }
        if (s == 8) {
          l2_prefetch(p.f + (size_t)(pj * 128 + ti * 8) * SEQ, 32768);
          l2_prefetch(p.bre + (size_t)(512 + b * 4) * DM, 8192);
          l2_prefetch(p.bim + (size_t)(512 + b * 4) * DM, 8192);
        }
        if (s == 18) {
          l2_prefetch(p.cre + (size_t)b * 8 * DM, 16384);
          l2_prefetch(p.cim + (size_t)b * 8 * DM, 16384);
        }
        if (++sl == NS) { sl = 0; par ^= 1; }
      }
    }
  } else if (wg == 2) {
    asm volatile("setmaxnreg.inc.sync.aligned.u32 144;");
    conv_tables(tid);
    prep(p, ti, pj, 4 + (tid >> 5), tid & 31);
    bar_sync(4, 256);
    if (tid == 0) flag_signal(g_flag + pj * 32);
    conv_main(m, p, ti, pj, tid, ep);
  } else {
    asm volatile("setmaxnreg.inc.sync.aligned.u32 168;");
    const int lane = tid & 31;
    if (wg == 1) {
      const int ch = (tid >> 6) * 512 + pj * 64 + (tid & 63);
      const float lr = __bfloat162float(p.lre[ch]), li = __bfloat162float(p.lim[ch]);
      const float dt = bf_round(expf(__bfloat162float(p.ldt[ch])));
      float sn, cs;
      sincosf(dt * li, &sn, &cs);
      const float ex = expf(dt * lr);
      const float ar = ex * cs, ai = ex * sn;
      const float inv = 2.f / (lr * lr + li * li);
      const float cr = ((ar - 1.f) * lr + ai * li) * inv, ci = (ai * lr - (ar - 1.f) * li) * inv;
      sts128(sb + OFF_PAR + tid * 16, __float_as_uint(ar), __float_as_uint(-ai), __float_as_uint(cr), __float_as_uint(-ci));
      bar_arrive(6, 256);
      prep(p, ti, pj, tid >> 5, lane);
      bar_sync(4, 256);
      TIM(1);
    }
    {
      float a0[64], a1[64];
      int sl = wg ? 16 % NS : 0, par = wg ? (16 / NS) & 1 : 0, psl = 0;
      zero(a0); zero(a1);
      reg_fence(a0); reg_fence(a1);
      if (wg == 1) bar_sync(7, 256);
#pragma unroll 1
      for (int s = 0; s < 16; s++) {
        mbar_wait(fullb + 8 * sl, par);
        if (s == 0) TIM(2 + wg * 2);
        if (s == 15) bar_arrive(7 + wg, 256);
        const uint32_t st = sb + sl * STAGE;
        WG_FENCE();
#pragma unroll
        for (int k = 0; k < 4; k++) {
          const uint64_t db = mkdesc(st + 16384 + 32 * k, 16, 1024, 1);
          wgmma_ss128<0>(a0, mkdesc(st + 32 * k, 16, 1024, 1), db);
          wgmma_ss128<0>(a1, mkdesc(st + 8192 + 32 * k, 16, 1024, 1), db);
        }
        WG_COMMIT();
        WG_WAIT(1);
        if (s > 0 && lane == 0) mbar_arrive(emptyb + 8 * psl);
        psl = sl;
        if (++sl == NS) { sl = 0; par ^= 1; }
      }
      WG_WAIT(0);
      if (lane == 0) mbar_arrive(emptyb + 8 * psl);
      reg_fence(a0); reg_fence(a1);
      TIM(3 + wg * 2);
      if (wg == 0) bar_sync(6, 256);
      scan_epilogue(a0, a1, wg, ti, pj, tid, ep);
      if (wg == 1) {
        eterm(m, p, ti, pj, tid, ep);
      } else {
        sl = 32 % NS; par = (32 / NS) & 1;
        zero(a0); zero(a1);
        reg_fence(a0); reg_fence(a1);
        bar_sync(8, 256);
#pragma unroll 1
        for (int s = 0; s < 32; s++) {
          mbar_wait(fullb + 8 * sl, par);
          if (s == 0) TIM(6);
          if (s == 16) TIM(18);
          const uint32_t st = sb + sl * STAGE;
          WG_FENCE();
#pragma unroll
          for (int k = 0; k < 4; k++) {
            const uint64_t db = mkdesc(st + 16384 + 32 * k, 16, 1024, 1);
            wgmma_ss128<1>(a0, mkdesc(st + 4096 * k, 2048, 128, 0), db);
            wgmma_ss128<1>(a1, mkdesc(st + 4096 * k + 1024, 2048, 128, 0), db);
          }
          WG_COMMIT();
          WG_WAIT(1);
          if (s > 0 && lane == 0) mbar_arrive(emptyb + 8 * psl);
          psl = sl;
          if (++sl == NS) { sl = 0; par ^= 1; }
        }
        bar_sync(5, 256);
        const int w = tid >> 5, r = lane >> 2, c = lane & 3;
        float g[4];
#pragma unroll
        for (int i = 0; i < 4; i++)
          asm volatile("ld.shared.f32 %0, [%1];" : "=f"(g[i]) : "r"(sb + OFF_G + (64 * (i >> 1) + 16 * w + 8 * (i & 1) + r) * 4) : "memory");
        WG_WAIT(0);
        reg_fence(a0); reg_fence(a1);
        TIM(7);
        float* op = p.out + (size_t)(ti * 128 + 16 * w + r) * DM + pj * 128 + 4 * c;
        store_half(a0, op, sb + OFF_CONV + tid * 16, g[0], g[1]);
        store_half(a1, op + 64 * DM, sb + OFF_CONV + 16384 + tid * 16, g[2], g[3]);
        if (tid == 0) g_epoch[b] = ep + 1;
        TIM(19);
      }
    }
  }
}

typedef CUresult (*EncFn)(CUtensorMap*, CUtensorMapDataType, cuuint32_t, void*, const cuuint64_t*, const cuuint64_t*,
                          const cuuint32_t*, const cuuint32_t*, CUtensorMapInterleave, CUtensorMapSwizzle,
                          CUtensorMapL2promotion, CUtensorMapFloatOOBfill);

void encode(EncFn enc, CUtensorMap* m, const void* ptr, int rank, const cuuint64_t* dims, const cuuint64_t* strides,
            const cuuint32_t* box, CUtensorMapSwizzle sw) {
  cuuint32_t es[5] = {1, 1, 1, 1, 1};
  enc(m, CU_TENSOR_MAP_DATA_TYPE_BFLOAT16, rank, const_cast<void*>(ptr), dims, strides, box, es, CU_TENSOR_MAP_INTERLEAVE_NONE,
      sw, CU_TENSOR_MAP_L2_PROMOTION_L2_128B, CU_TENSOR_MAP_FLOAT_OOB_FILL_NONE);
}

}

extern "C" void kernel_launch(void* const* d_in, const int* in_sizes, int n_in, void* d_out, int out_size) {
  typedef const __nv_bfloat16* bp;
  Ptrs p;
  p.x = (bp)d_in[0]; p.lre = (bp)d_in[1]; p.lim = (bp)d_in[2]; p.bre = (bp)d_in[3]; p.bim = (bp)d_in[4];
  p.cre = (bp)d_in[5]; p.cim = (bp)d_in[6]; p.ldt = (bp)d_in[7]; p.dskip = (bp)d_in[8];
  p.k = (bp)d_in[10]; p.v = (bp)d_in[11]; p.shift = (bp)d_in[12]; p.f = (bp)d_in[13]; p.ssmd = (bp)d_in[14];
  p.gw = (bp)d_in[15]; p.out = (float*)d_out;

  EncFn enc = nullptr;
  cudaDriverEntryPointQueryResult qr;
  cudaGetDriverEntryPoint("cuTensorMapEncodeTiled", (void**)&enc, cudaEnableDefault, &qr);
  void* zptr = nullptr;
  cudaGetSymbolAddress(&zptr, g_z);

  Maps m;
  {
    cuuint64_t d[4] = {1024, 2, 64, 16}, s[3] = {2048, 65536, 4096};
    cuuint32_t bx[4] = {64, 2, 4, 16};
    encode(enc, &m.x, p.x, 4, d, s, bx, CU_TENSOR_MAP_SWIZZLE_128B);
  }
  {
    cuuint64_t d[2] = {1024, 1024}, s[1] = {2048};
    cuuint32_t bx[2] = {64, 64};
    encode(enc, &m.bre, p.bre, 2, d, s, bx, CU_TENSOR_MAP_SWIZZLE_128B);
    encode(enc, &m.bim, p.bim, 2, d, s, bx, CU_TENSOR_MAP_SWIZZLE_128B);
  }
  {
    cuuint64_t d[5] = {1024, 2, 4, 2, 64}, s[4] = {2048, 8192, 4096, 32768};
    cuuint32_t bx[5] = {64, 2, 4, 2, 8};
    encode(enc, &m.cre, p.cre, 5, d, s, bx, CU_TENSOR_MAP_SWIZZLE_128B);
    encode(enc, &m.cim, p.cim, 5, d, s, bx, CU_TENSOR_MAP_SWIZZLE_128B);
  }
  {
    cuuint64_t d[2] = {16, 1024 * 128}, s[1] = {32};
    cuuint32_t bx[2] = {16, 128};
    encode(enc, &m.f, p.f, 2, d, s, bx, CU_TENSOR_MAP_SWIZZLE_32B);
  }
  {
    cuuint64_t d[2] = {2048, 1024}, s[1] = {4096};
    cuuint32_t bx[2] = {64, 128};
    encode(enc, &m.z, zptr, 2, d, s, bx, CU_TENSOR_MAP_SWIZZLE_128B);
  }
  cudaFuncSetAttribute(fused_kernel, cudaFuncAttributeMaxDynamicSharedMemorySize, SMEM_BYTES);
  fused_kernel<<<128, 512, SMEM_BYTES, cudaStreamPerThread>>>(m, p);
}
```

```cpp
#include <cuda_runtime.h>
#include <cuda_bf16.h>
#include <cuda.h>
#include <stdint.h>

namespace {

constexpr int SEQ = 2048, DM = 1024;
constexpr int NS = 5;
constexpr int STAGE = 32768;
#define NCH 8
#define LEAD 3
#define GRP 16
#define PACE 350
#define KV0_AT 600
#define KV_GAP 600
#define KV_GAP1 600
#define EARLY 1
#define GV 10
#define SFM 0
#define LD_GAP 400
#define LDQ ""
#define PROMO CU_TENSOR_MAP_L2_PROMOTION_L2_128B
constexpr uint32_t sb = 1024;
constexpr uint32_t S_STG = sb + NS * STAGE;
constexpr uint32_t S_CIN = S_STG + 32768;
constexpr uint32_t S_T = S_CIN + 16384;
constexpr uint32_t S_M1 = S_T + 8192;
constexpr uint32_t S_M2 = S_M1 + 4096;
constexpr uint32_t S_PAR = S_M2 + 2048;
constexpr uint32_t S_G = S_PAR + 4096;
constexpr uint32_t S_BAR = S_G + 512;
constexpr int SMEM_BYTES = S_BAR + 512 - sb;
constexpr uint32_t B_FULL = S_BAR, B_EMPTY = B_FULL + 8 * NS, B_CINF = B_EMPTY + 8 * NS,
                   B_FLG = B_CINF + 16, B_SFREE = B_FLG + 56, B_ZT = B_SFREE + 16,
                   B_XT = B_ZT + 8, B_PIN = B_XT + 8, S_MIR = B_PIN + 32, S_EP = S_MIR + 32;
constexpr int SPIN_LIMIT = 1 << 21;
constexpr int F_GRP = 0, F_H = 8, F_U = 72, F_Z = 88;

struct alignas(64) Maps { CUtensorMap x, bre, bim, cre, cim, f, u, z, x2, k, kh, v; };
struct Ptrs {
  const __nv_bfloat16 *x, *lre, *lim, *ldt, *dskip, *k, *v, *shift, *f, *ssmd, *gw, *bre, *bim, *cre, *cim;
  float* out;
};

__device__ uint4 g_h[16 * 32 * 1024];
__device__ uint4 g_u[1024 * 256];
__device__ uint4 g_z[1024 * 256];
__device__ uint4 g_agg[2 * 16 * 256];
__device__ unsigned g_gate[8 * SEQ];
__device__ unsigned g_flag[96 * 32];
__device__ unsigned g_epoch[128];
#define TIM(i)
#define TIMC(i)

#define WG_FENCE() asm volatile("wgmma.fence.sync.aligned;" ::: "memory")
#define WG_COMMIT() asm volatile("wgmma.commit_group.sync.aligned;" ::: "memory")
#define WG_WAIT(n) asm volatile("wgmma.wait_group.sync.aligned %0;" ::"n"(n) : "memory")
#define R8(d, o) "+f"(d[o + 0]), "+f"(d[o + 1]), "+f"(d[o + 2]), "+f"(d[o + 3]), "+f"(d[o + 4]), "+f"(d[o + 5]), "+f"(d[o + 6]), "+f"(d[o + 7])
#define W8(d, o) "=f"(d[o + 0]), "=f"(d[o + 1]), "=f"(d[o + 2]), "=f"(d[o + 3]), "=f"(d[o + 4]), "=f"(d[o + 5]), "=f"(d[o + 6]), "=f"(d[o + 7])
#define L16 "%0,%1,%2,%3,%4,%5,%6,%7,%8,%9,%10,%11,%12,%13,%14,%15"
#define L64 L16 ",%16,%17,%18,%19,%20,%21,%22,%23,%24,%25,%26,%27,%28,%29,%30,%31," \
  "%32,%33,%34,%35,%36,%37,%38,%39,%40,%41,%42,%43,%44,%45,%46,%47,%48,%49,%50,%51,%52,%53,%54,%55,%56,%57,%58,%59,%60,%61,%62,%63"

template <int TA, int TB, int ACC>
__device__ __forceinline__ void wgmma_ss128(float (&d)[64], uint64_t da, uint64_t db) {
  if (ACC)
    asm volatile("wgmma.mma_async.sync.aligned.m64n128k16.f32.bf16.bf16 {" L64 "}, %64, %65, 1, 1, 1, %66, %67;"
                 : R8(d, 0), R8(d, 8), R8(d, 16), R8(d, 24), R8(d, 32), R8(d, 40), R8(d, 48), R8(d, 56)
                 : "l"(da), "l"(db), "n"(TA), "n"(TB));
  else
    asm volatile("wgmma.mma_async.sync.aligned.m64n128k16.f32.bf16.bf16 {" L64 "}, %64, %65, 0, 1, 1, %66, %67;"
                 : W8(d, 0), W8(d, 8), W8(d, 16), W8(d, 24), W8(d, 32), W8(d, 40), W8(d, 48), W8(d, 56)
                 : "l"(da), "l"(db), "n"(TA), "n"(TB));
}
template <int ACC, int TB = 0>
__device__ __forceinline__ void wgmma_rs32(float (&d)[16], uint32_t a0, uint32_t a1, uint32_t a2, uint32_t a3, uint64_t db) {
  if (ACC)
    asm volatile("wgmma.mma_async.sync.aligned.m64n32k16.f32.bf16.bf16 {" L16 "}, {%16,%17,%18,%19}, %20, 1, 1, 1, %21;"
                 : R8(d, 0), R8(d, 8) : "r"(a0), "r"(a1), "r"(a2), "r"(a3), "l"(db), "n"(TB));
  else
    asm volatile("wgmma.mma_async.sync.aligned.m64n32k16.f32.bf16.bf16 {" L16 "}, {%16,%17,%18,%19}, %20, 0, 1, 1, %21;"
                 : W8(d, 0), W8(d, 8) : "r"(a0), "r"(a1), "r"(a2), "r"(a3), "l"(db), "n"(TB));
}
template <int N>
__device__ __forceinline__ void reg_fence(float (&d)[N]) {
#pragma unroll
  for (int i = 0; i < N; i++) asm volatile("" : "+f"(d[i])::"memory");
}
__device__ __forceinline__ constexpr uint32_t dlo(uint32_t addr, uint32_t lbo) { return (addr >> 4) + ((lbo >> 4) << 16); }
__device__ __forceinline__ uint64_t mkdesc(uint32_t lo, uint32_t sbo, uint32_t mode) {
  uint64_t d;
  asm("mov.b64 %0, {%1, %2};" : "=l"(d) : "r"(lo), "r"((sbo >> 4) | (mode << 30)));
  return d;
}
template <int N>
__device__ __forceinline__ void zero(float (&d)[N]) {
#pragma unroll
  for (int i = 0; i < N; i++) d[i] = 0.f;
}
__device__ __forceinline__ void trap_if(int c) {
  asm volatile("{.reg .pred p; .reg .b64 z; setp.ne.s32 p, %0, 0; mov.b64 z, 0; @p st.global.u32 [z], %0;}" ::"r"(c) : "memory");
}
template <int K>
__device__ __forceinline__ void sched_fence() {
  asm volatile("{.reg .pred p; setp.eq.u32 p, %0, %1; @p exit;}" ::"r"(gridDim.x), "n"(256 + K) : "memory");
}
__device__ __forceinline__ bool elect_one() {
  uint32_t pred;
  asm volatile("{.reg .pred p; elect.sync _|p, 0xffffffff; selp.u32 %0, 1, 0, p;}" : "=r"(pred));
  return pred;
}
__device__ __forceinline__ void mbar_init(uint32_t bar, uint32_t cnt) {
  asm volatile("mbarrier.init.shared::cta.b64 [%0], %1;" ::"r"(bar), "r"(cnt) : "memory");
}
__device__ __forceinline__ bool mbar_try(uint32_t bar, uint32_t par) {
  uint32_t ok;
  asm volatile("{.reg .pred p; mbarrier.try_wait.parity.shared::cta.b64 p, [%1], %2; selp.u32 %0, 1, 0, p;}"
               : "=r"(ok) : "r"(bar), "r"(par) : "memory");
  return ok;
}
__device__ __forceinline__ void mbar_wait(uint32_t bar, uint32_t par) {
  if (__builtin_expect(!mbar_try(bar, par), 0)) {
    int n = SPIN_LIMIT;
    while (!mbar_try(bar, par) && --n) {}
    trap_if(n == 0);
  }
}
__device__ __forceinline__ void mbar_wait_long(uint32_t bar, uint32_t par) {
  int n = SPIN_LIMIT;
  while (!mbar_try(bar, par) && --n) __nanosleep(100);
  trap_if(n == 0);
}
__device__ __forceinline__ void mbar_arrive(uint32_t bar) {
  asm volatile("mbarrier.arrive.shared::cta.b64 _, [%0];" ::"r"(bar) : "memory");
}
__device__ __forceinline__ void mbar_expect(uint32_t bar, uint32_t bytes) {
  asm volatile("mbarrier.arrive.expect_tx.shared::cta.b64 _, [%0], %1;" ::"r"(bar), "r"(bytes) : "memory");
}
__device__ __forceinline__ void tma2d(uint32_t dst, const CUtensorMap* m, uint32_t bar, int c0, int c1) {
  asm volatile("cp.async.bulk.tensor.2d.shared::cluster.global.mbarrier::complete_tx::bytes [%0], [%1, {%3, %4}], [%2];"
               ::"r"(dst), "l"(m), "r"(bar), "r"(c0), "r"(c1) : "memory");
}
__device__ __forceinline__ void tma3d(uint32_t dst, const CUtensorMap* m, uint32_t bar, int c0, int c1, int c2) {
  asm volatile("cp.async.bulk.tensor.3d.shared::cluster.global.mbarrier::complete_tx::bytes [%0], [%1, {%3, %4, %5}], [%2];"
               ::"r"(dst), "l"(m), "r"(bar), "r"(c0), "r"(c1), "r"(c2) : "memory");
}
__device__ __forceinline__ void tma4d(uint32_t dst, const CUtensorMap* m, uint32_t bar, int c0, int c1, int c2, int c3) {
  asm volatile("cp.async.bulk.tensor.4d.shared::cluster.global.mbarrier::complete_tx::bytes [%0], [%1, {%3, %4, %5, %6}], [%2];"
               ::"r"(dst), "l"(m), "r"(bar), "r"(c0), "r"(c1), "r"(c2), "r"(c3) : "memory");
}
__device__ __forceinline__ void tma5d(uint32_t dst, const CUtensorMap* m, uint32_t bar, int c0, int c1, int c2, int c3, int c4) {
  asm volatile("cp.async.bulk.tensor.5d.shared::cluster.global.mbarrier::complete_tx::bytes [%0], [%1, {%3, %4, %5, %6, %7}], [%2];"
               ::"r"(dst), "l"(m), "r"(bar), "r"(c0), "r"(c1), "r"(c2), "r"(c3), "r"(c4) : "memory");
}
__device__ __forceinline__ void bulk_load(uint32_t dst, const void* src, uint32_t bytes, uint32_t bar) {
  asm volatile("cp.async.bulk.shared::cluster.global.mbarrier::complete_tx::bytes [%0], [%1], %2, [%3];"
               ::"r"(dst), "l"(src), "r"(bytes), "r"(bar) : "memory");
}
__device__ __forceinline__ void l2_prefetch(const void* src, uint32_t bytes) {
  asm volatile("cp.async.bulk.prefetch.L2.global [%0], %1;" ::"l"(src), "r"(bytes) : "memory");
}
__device__ __forceinline__ void bar_sync(int id, int n) { asm volatile("bar.sync %0, %1;" ::"r"(id), "r"(n) : "memory"); }
__device__ __forceinline__ void bar_arrive(int id, int n) { asm volatile("bar.arrive %0, %1;" ::"r"(id), "r"(n) : "memory"); }
__device__ __forceinline__ void bulk_store(void* dst, uint32_t src, uint32_t bytes) {
  asm volatile("cp.async.bulk.global.shared::cta.bulk_group [%0], [%1], %2;" ::"l"(dst), "r"(src), "r"(bytes) : "memory");
}
__device__ __forceinline__ void bulk_commit() { asm volatile("cp.async.bulk.commit_group;" ::: "memory"); }
__device__ __forceinline__ void bulk_wait_read() { asm volatile("cp.async.bulk.wait_group.read 0;" ::: "memory"); }
__device__ __forceinline__ void fence_async_smem() { asm volatile("fence.proxy.async.shared::cta;" ::: "memory"); }
__device__ __forceinline__ void fence_async_global() { asm volatile("fence.proxy.async.global;" ::: "memory"); }
__device__ __forceinline__ void flag_add(int f) {
  asm volatile("red.relaxed.gpu.global.add.u32 [%0], 1;" ::"l"(g_flag + f * 32) : "memory");
}
__device__ __forceinline__ void bulk_done_signal(int f) {
  asm volatile("cp.async.bulk.wait_group 0;" ::: "memory");
  fence_async_global();
  flag_add(f);
}
__device__ __forceinline__ unsigned ld_relaxed(const unsigned* p) {
  unsigned v;
  asm volatile("ld.relaxed.gpu.global.u32 %0, [%1];" : "=r"(v) : "l"(p) : "memory");
  return v;
}
__device__ __forceinline__ void wait_clock(unsigned t) {
  int d;
  while ((d = (int)(t - (unsigned)clock())) > 0) __nanosleep(d > 600 ? 200 : 40);
}
__device__ __forceinline__ uint32_t pack2(float lo, float hi) {
  uint32_t r;
  asm("cvt.rn.bf16x2.f32 %0, %1, %2;" : "=r"(r) : "f"(hi), "f"(lo));
  return r;
}
__device__ __forceinline__ float bf_lo(uint32_t v) { return __uint_as_float(v << 16); }
__device__ __forceinline__ float bf_hi(uint32_t v) { return __uint_as_float(v & 0xffff0000u); }
__device__ __forceinline__ float bf_round(float v) { return __bfloat162float(__float2bfloat16_rn(v)); }
__device__ __forceinline__ uint32_t hmul2(uint32_t a, uint32_t b) {
  uint32_t r;
  asm("mul.rn.bf16x2 %0, %1, %2;" : "=r"(r) : "r"(a), "r"(b));
  return r;
}
__device__ __forceinline__ uint32_t hadd2(uint32_t a, uint32_t b) {
  uint32_t r;
  asm("add.rn.bf16x2 %0, %1, %2;" : "=r"(r) : "r"(a), "r"(b));
  return r;
}
__device__ __forceinline__ uint32_t hsub2(uint32_t a, uint32_t b) {
  uint32_t r;
  asm("sub.rn.bf16x2 %0, %1, %2;" : "=r"(r) : "r"(a), "r"(b));
  return r;
}
__device__ __forceinline__ uint32_t hfma2(uint32_t a, uint32_t b, uint32_t c) {
  uint32_t r;
  asm("fma.rn.bf16x2 %0, %1, %2, %3;" : "=r"(r) : "r"(a), "r"(b), "r"(c));
  return r;
}
__device__ __forceinline__ uint32_t hneg2(uint32_t a) {
  uint32_t r;
  asm("neg.bf16x2 %0, %1;" : "=r"(r) : "r"(a));
  return r;
}
__device__ __forceinline__ uint4 ldg128(const void* p) {
  uint4 v;
  asm volatile("ld.global.nc" LDQ ".v4.u32 {%0,%1,%2,%3}, [%4];" : "=r"(v.x), "=r"(v.y), "=r"(v.z), "=r"(v.w) : "l"(p));
  return v;
}
__device__ __forceinline__ uint2 ldg64(const void* p) {
  uint2 v;
  asm volatile("ld.global.nc.v2.u32 {%0,%1}, [%2];" : "=r"(v.x), "=r"(v.y) : "l"(p));
  return v;
}
__device__ __forceinline__ void stg128(void* p, uint32_t a, uint32_t b, uint32_t c, uint32_t d) {
  asm volatile("st.global.v4.u32 [%0], {%1,%2,%3,%4};" ::"l"(p), "r"(a), "r"(b), "r"(c), "r"(d) : "memory");
}
__device__ __forceinline__ void sts128(uint32_t a, uint32_t x, uint32_t y, uint32_t z, uint32_t w) {
  asm volatile("st.shared.v4.u32 [%0], {%1,%2,%3,%4};" ::"r"(a), "r"(x), "r"(y), "r"(z), "r"(w) : "memory");
}
__device__ __forceinline__ uint32_t lds32(uint32_t a) {
  uint32_t v;
  asm volatile("ld.shared.u32 %0, [%1];" : "=r"(v) : "r"(a) : "memory");
  return v;
}
__device__ __forceinline__ uint4 lds128(uint32_t a) {
  uint4 v;
  asm volatile("ld.shared.v4.u32 {%0,%1,%2,%3}, [%4];" : "=r"(v.x), "=r"(v.y), "=r"(v.z), "=r"(v.w) : "r"(a) : "memory");
  return v;
}
__device__ __forceinline__ void stsm4(uint32_t a, uint32_t x, uint32_t y, uint32_t z, uint32_t w) {
  asm volatile("stmatrix.sync.aligned.m8n8.x4.shared.b16 [%0], {%1,%2,%3,%4};" ::"r"(a), "r"(x), "r"(y), "r"(z), "r"(w) : "memory");
}
__device__ __forceinline__ void stsm4t(uint32_t a, uint32_t x, uint32_t y, uint32_t z, uint32_t w) {
  asm volatile("stmatrix.sync.aligned.m8n8.x4.trans.shared.b16 [%0], {%1,%2,%3,%4};" ::"r"(a), "r"(x), "r"(y), "r"(z), "r"(w) : "memory");
}
__device__ __forceinline__ uint4 ldsm4t(uint32_t a) {
  uint4 v;
  asm volatile("ldmatrix.sync.aligned.m8n8.x4.trans.shared.b16 {%0,%1,%2,%3}, [%4];" : "=r"(v.x), "=r"(v.y), "=r"(v.z), "=r"(v.w) : "r"(a) : "memory");
  return v;
}
struct cx { float r, i; };
__device__ __forceinline__ cx cmul(cx a, cx b) { return {a.r * b.r - a.i * b.i, a.r * b.i + a.i * b.r}; }
__device__ __forceinline__ cx cfma(cx a, cx b, cx c) { return {fmaf(a.r, b.r, fmaf(-a.i, b.i, c.r)), fmaf(a.r, b.i, fmaf(a.i, b.r, c.i))}; }
__device__ __forceinline__ cx csq(cx a) { return {a.r * a.r - a.i * a.i, 2.f * a.r * a.i}; }
__device__ __forceinline__ cx unit(int num, int den) {
  int m = num & (den - 1);
  if (m >= den / 2) m -= den;
  float s, c;
  __sincosf((float)m * (-6.283185307179586f / (float)den), &s, &c);
  return {c, s};
}

__device__ __forceinline__ uint2 lds64(uint32_t a) {
  uint2 v;
  asm volatile("ld.shared.v2.u32 {%0,%1}, [%2];" : "=r"(v.x), "=r"(v.y) : "r"(a) : "memory");
  return v;
}
template <int PG>
__device__ __forceinline__ void prep(const Ptrs& p, int ti, int pj, int w, int lane) {
  const int tb = lane & 7, chunk = 2 * w + (lane >> 4), ch = chunk * 8 + ((lane >> 3) & 1) * 4;
  uint32_t s[2][4];
#pragma unroll
  for (int e = 0; e < 2; e++) {
    const uint4 sh = ldg128(p.shift + (pj * 128 + PG * 64 + ch) * 4 + e * 8);
    s[e][0] = __byte_perm(sh.x, sh.z, 0x5410); s[e][1] = __byte_perm(sh.x, sh.z, 0x7632);
    s[e][2] = __byte_perm(sh.y, sh.w, 0x5410); s[e][3] = __byte_perm(sh.y, sh.w, 0x7632);
  }
#pragma unroll 1
  for (int th = 0; th < 2; th++) {
    const uint32_t in = S_STG + th * 16384 + (lane & 8);
    const uint32_t a0 = in + tb * 128 + ((chunk ^ tb) << 4);
    const uint32_t hb = tb ? in + (39 + tb) * 128 + ((chunk ^ (tb - 1)) << 4) : S_T + (PG * 2 + th) * 512 + ch * 2;
    const uint32_t hs = tb ? 1024 : 128;
    uint2 kk[11], vv[8];
    mbar_wait_long(B_PIN + 16 * PG + 8 * th, 0);
    if (th) TIM(29 + PG);
#pragma unroll
    for (int i = 0; i < 3; i++) kk[i] = lds64(hb + i * hs);
#pragma unroll
    for (int i = 0; i < 8; i++) { kk[3 + i] = lds64(a0 + i * 1024); vv[i] = lds64(a0 + 8192 + i * 1024); }
#pragma unroll
    for (int i = 0; i < 8; i++)
#pragma unroll
      for (int e = 0; e < 2; e++) {
        uint32_t a = hmul2((&kk[i].x)[e], s[e][3]);
        a = hfma2((&kk[i + 1].x)[e], s[e][2], a);
        a = hfma2((&kk[i + 2].x)[e], s[e][1], a);
        a = hfma2((&kk[i + 3].x)[e], s[e][0], a);
        (&vv[i].x)[e] = hmul2(a, (&vv[i].x)[e]);
      }
    if (PG) bar_sync(3, 128); else bar_arrive(th ? 12 : 14, 160);
    const uint32_t dst = (PG ? S_STG + 8192 + th * 16384 : S_CIN + th * 8192) + ch * 128 + tb * 16;
#pragma unroll
    for (int e = 0; e < 2; e++) {
#define U(i) (&vv[i].x)[e]
      sts128(dst + (2 * e) * 128, __byte_perm(U(0), U(1), 0x5410), __byte_perm(U(2), U(3), 0x5410),
             __byte_perm(U(4), U(5), 0x5410), __byte_perm(U(6), U(7), 0x5410));
      sts128(dst + (2 * e + 1) * 128, __byte_perm(U(0), U(1), 0x7632), __byte_perm(U(2), U(3), 0x7632),
             __byte_perm(U(4), U(5), 0x7632), __byte_perm(U(6), U(7), 0x7632));
#undef U
    }
    bar_arrive(PG ? 9 + th : 15 - 4 * th, 160);
  }
}

__device__ __forceinline__ void conv_tables(int tid) {
  {
    const int s = tid >> 5, n1 = tid & 31;
    uint32_t re[4], im[4];
#pragma unroll
    for (int e = 0; e < 4; e++) {
      cx a = unit(n1 * (4 * (8 * s + 2 * e) + 1), 128), b = unit(n1 * (4 * (8 * s + 2 * e + 1) + 1), 128);
      re[e] = pack2(a.r * 0.125f, b.r * 0.125f); im[e] = pack2(a.i * 0.125f, b.i * 0.125f);
    }
    sts128(S_M1 + (2 * s) * 512 + n1 * 16, re[0], re[1], re[2], re[3]);
    sts128(S_M1 + (2 * s + 1) * 512 + n1 * 16, im[0], im[1], im[2], im[3]);
  }
  {
    const int kg = tid >> 5, n = tid & 31;
    const int pi = kg >> 1, po = n >> 4, f2 = n & 15;
    uint32_t fw[4];
#pragma unroll
    for (int e = 0; e < 4; e++) {
      int n2 = (kg & 1) * 8 + 2 * e;
      cx a = unit(n2 * f2, 16), b = unit((n2 + 1) * f2, 16);
      float sg = pi ? -1.f : 1.f;
      float x0 = (pi == po) ? a.r : sg * a.i, x1 = (pi == po) ? b.r : sg * b.i;
      fw[e] = pack2(x0, x1);
    }
    sts128(S_M2 + kg * 512 + n * 16, fw[0], fw[1], fw[2], fw[3]);
  }
  fence_async_smem();
}
__device__ __forceinline__ int conv_chan(int ti, int pj, int ch) { return pj * 128 + (ch >> 2) * 64 + ti * 4 + (ch & 3); }

#define CDESC(a) mkdesc(dlo(a, 512), 128, 0)
struct ConvTw { uint32_t r[2], i[2], n[2]; };

__device__ __forceinline__ void cv_tw1(float (&d)[64], uint32_t (&R)[16], uint32_t (&I)[16], const ConvTw& t, int i) {
#pragma unroll
  for (int j = 8 * (i & 1); j < 8 * (i & 1) + 8; j++) {
    if (i < 2) {
      R[j] = pack2(d[4 * j], d[4 * j + 1]); I[j] = pack2(d[4 * j + 2], d[4 * j + 3]);
    } else {
      const uint32_t xr = R[j], xi = I[j];
      R[j] = hfma2(xr, t.r[j & 1], hmul2(xi, t.n[j & 1]));
      I[j] = hfma2(xr, t.i[j & 1], hmul2(xi, t.r[j & 1]));
    }
  }
}
template <int N>
__device__ __forceinline__ void cv_pack(float (&X)[16], uint32_t (&P)[N][2][2], int q) {
#pragma unroll
  for (int k = 0; k < 2; k++)
#pragma unroll
    for (int j = 0; j < 4; j++) P[2 * q + k][j >> 1][j & 1] = pack2(X[4 * j + 2 * k], X[4 * j + 2 * k + 1]);
}
__device__ __forceinline__ void cv_pw(uint32_t (&P)[8][2][2], uint32_t (&Q)[4][2][2], int q) {
#pragma unroll
  for (int k = 3; k > 0; k--)
#pragma unroll
    for (int hh = 0; hh < 2; hh++)
      if (q == 0) {
        P[k][0][hh] = hsub2(P[k][0][hh], P[k - 1][1][hh]);
        P[k][1][hh] = hadd2(P[k][1][hh], P[k - 1][0][hh]);
      }
#pragma unroll
  for (int jh = 4 * q; jh < 4 * q + 4; jh++) {
    const int j = jh >> 1, hh = jh & 1;
    uint32_t qr = hmul2(P[4 + j][0][hh], P[0][0][hh]), qi = hmul2(P[4 + j][0][hh], P[0][1][hh]);
    qr = hfma2(hneg2(P[4 + j][1][hh]), P[0][1][hh], qr);
    qi = hfma2(P[4 + j][1][hh], P[0][0][hh], qi);
#pragma unroll
    for (int k = j - 1; k >= 0; k--) {
      qr = hfma2(P[4 + k][0][hh], P[j - k][0][hh], qr);
      qi = hfma2(P[4 + k][0][hh], P[j - k][1][hh], qi);
      qr = hfma2(hneg2(P[4 + k][1][hh]), P[j - k][1][hh], qr);
      qi = hfma2(P[4 + k][1][hh], P[j - k][0][hh], qi);
    }
    Q[j][0][hh] = qr; Q[j][1][hh] = qi;
  }
}
__device__ __forceinline__ void cv_tw2(uint32_t (&Q)[4][2][2], const ConvTw& t, int k, uint32_t ta) {
  uint32_t zr[2], zi[2];
#pragma unroll
  for (int hh = 0; hh < 2; hh++) {
    zr[hh] = hfma2(Q[k][0][hh], t.r[hh], hmul2(Q[k][1][hh], t.i[hh]));
    zi[hh] = hfma2(Q[k][0][hh], t.n[hh], hmul2(Q[k][1][hh], t.r[hh]));
  }
  stsm4(ta + k * 2048, zr[0], zr[1], zi[0], zi[1]);
}
__device__ __forceinline__ void cv_out0(float (&Y)[16], int w, int lane) {
  reg_fence(Y);
  const uint32_t za = S_T + w * 2048 + (lane >> 4) * 256 + (lane & 7) * 32 + ((lane >> 3) & 1) * 16;
#pragma unroll
  for (int jj = 0; jj < 2; jj++)
    stsm4t(za + jj * 512, pack2(Y[8 * jj], Y[8 * jj + 1]), pack2(Y[8 * jj + 2], Y[8 * jj + 3]),
           pack2(Y[8 * jj + 4], Y[8 * jj + 5]), pack2(Y[8 * jj + 6], Y[8 * jj + 7]));
}

template <bool FW, bool BW, int K>
__device__ __forceinline__ void conv_step(uint32_t (&Q)[4][2][2], const ConvTw& t, float dl, int ch, int w, int lane) {
#define SF(n) if ((SFM >> (n)) & 1) sched_fence<K + (n)>()
  float d[64], X[4][16], Z[2][16], Y[16];
  uint32_t R[16], I[16];
  uint4 a[4];
  const int nx = ch + 1;
  float dv;
  TIMC(1);
  if (FW) {
    dv = __shfl_sync(~0u, dl, nx);
    mbar_wait(B_CINF + 8 * (nx & 1), (nx >> 1) & 1);
  }
  TIMC(2);
  WG_FENCE();
  if (BW) {
#pragma unroll
    for (int q = 0; q < 2; q++) {
      wgmma_rs32<0, 1>(Z[q], Q[2 * q][0][0], Q[2 * q + 1][0][0], Q[2 * q][0][1], Q[2 * q + 1][0][1], mkdesc(dlo(S_M2, 128), 512, 0));
      wgmma_rs32<1, 1>(Z[q], Q[2 * q][1][0], Q[2 * q + 1][1][0], Q[2 * q][1][1], Q[2 * q + 1][1][1], mkdesc(dlo(S_M2 + 256, 128), 512, 0));
    }
    WG_COMMIT();
  }
  if (FW) {
    const uint32_t lo = dlo(S_CIN, 1024) + (nx & 1) * 512;
    wgmma_ss128<1, 1, 0>(d, mkdesc(dlo(S_M1, 128), 512, 0), mkdesc(lo, 256, 3));
    wgmma_ss128<1, 1, 1>(d, mkdesc(dlo(S_M1 + 256, 128), 512, 0), mkdesc(lo + 32, 256, 3));
    WG_COMMIT();
  }
  TIMC(3);
  if (BW) {
    bar_sync(13, 160);
    TIMC(4);
    WG_WAIT(FW ? 1 : 0);
    TIMC(5);
    reg_fence(Z[0]); reg_fence(Z[1]);
    uint32_t V[4][2][2];
    cv_pack(Z[0], V, 0); cv_pack(Z[1], V, 1);
    SF(0);
#pragma unroll
    for (int k = 0; k < 4; k++) cv_tw2(V, t, k, S_T + w * 512 + lane * 16);
    SF(1);
    TIMC(6);
  }
  if (FW) {
    WG_WAIT(0);
    reg_fence(d);
    if (nx + 2 < NCH) bar_arrive(12, 160);
    cv_tw1(d, R, I, t, 0); cv_tw1(d, R, I, t, 1);
    SF(2);
    TIMC(7);
  }
  if (BW) {
    bar_sync(3, 128);
#pragma unroll
    for (int s = 0; s < 4; s++) a[s] = ldsm4t(S_T + (4 * w + s) * 512 + lane * 16);
  }
  if (FW) { cv_tw1(d, R, I, t, 2); cv_tw1(d, R, I, t, 3); }
  sched_fence<K + 3>();
  TIMC(8);
  WG_FENCE();
  if (BW) {
    wgmma_rs32<0>(Y, a[0].x, a[0].y, a[0].z, a[0].w, CDESC(S_M1));
#pragma unroll
    for (int i = 1; i < 4; i++) wgmma_rs32<1>(Y, a[i].x, a[i].y, a[i].z, a[i].w, CDESC(S_M1 + 1024 * i));
  }
  if (FW) {
#pragma unroll
    for (int q = 0; q < 4; q++) {
      wgmma_rs32<0>(X[q], R[4 * q], R[4 * q + 2], R[4 * q + 1], R[4 * q + 3], CDESC(S_M2));
      wgmma_rs32<1>(X[q], I[4 * q], I[4 * q + 2], I[4 * q + 1], I[4 * q + 3], CDESC(S_M2 + 1024));
    }
  }
  WG_COMMIT();
  TIMC(9);
  WG_WAIT(0);
  TIMC(10);
  if (BW) { cv_out0(Y, w, lane); bar_arrive(4, 160); }
  uint32_t P[8][2][2];
  if (FW) {
#pragma unroll
    for (int q = 0; q < 4; q++) reg_fence(X[q]);
    X[2][0] += dv; X[2][1] += dv; X[2][4] += dv; X[2][5] += dv;
#pragma unroll
    for (int q = 0; q < 4; q++) cv_pack(X[q], P, q);
    SF(4);
    TIMC(11);
  }
  TIMC(12);
  if (FW) { cv_pw(P, Q, 0); cv_pw(P, Q, 1); }
  sched_fence<K + 5>();
  TIMC(13);
#undef SF
}

__device__ __forceinline__ void conv_main(const Ptrs& p, int ti, int pj, int tid) {
  const int w = tid >> 5, lane = tid & 31;
  ConvTw t;
#pragma unroll
  for (int hh = 0; hh < 2; hh++) {
    const int n2 = 8 * hh + 2 * (lane & 3), m = 4 * (8 * w + (lane >> 2)) + 1;
    cx a = unit(n2 * m, 2048), b = unit((n2 + 1) * m, 2048);
    t.r[hh] = pack2(a.r, b.r); t.i[hh] = pack2(a.i, b.i); t.n[hh] = pack2(-a.i, -b.i);
  }
  const float dl = 0.125f * __bfloat162float(p.ssmd[conv_chan(ti, pj, lane & 7)]);
  prep<1>(p, ti, pj, w, lane);
  if (NCH > 0) {
    uint32_t P[4][2][2];
    mbar_wait_long(B_CINF, 0);
    TIM(20);
    conv_step<true, false, 10>(P, t, dl, -1, w, lane);
#pragma unroll 1
    for (int ch = 0; ch < NCH - 1; ch++) {
      conv_step<true, true, 20>(P, t, dl, ch, w, lane);
      if (ch == 0) TIM(21);
    }
    conv_step<false, true, 30>(P, t, dl, NCH - 1, w, lane);
  }
  TIM(22);
}

__device__ __forceinline__ cx csel(bool k, cx a, cx b) { return {k ? a.r : b.r, k ? a.i : b.i}; }
__device__ __forceinline__ void ld2cx(uint32_t a, cx& x, cx& y) {
  const uint4 v = lds128(a);
  x = {__uint_as_float(v.x), __uint_as_float(v.y)};
  y = {__uint_as_float(v.z), __uint_as_float(v.w)};
}
__device__ __forceinline__ cx ldcx(uint32_t a) {
  cx x;
  asm volatile("ld.shared.v2.f32 {%0,%1}, [%2];" : "=f"(x.r), "=f"(x.i) : "r"(a) : "memory");
  return x;
}

__device__ __forceinline__ void scan_epilogue(float (&aR)[64], float (&aI)[64], uint32_t last_empty, int ph, int ti, int pj, int tid) {
  const int w = tid >> 5, lane = tid & 31, r = lane >> 2, c = lane & 3;
  const uint32_t par = S_PAR + (ph * 64 + 16 * w + r) * 16;
  uint4* agg = g_agg + ph * 16 * 256 + pj * 32 + 8 * w + r;
  const uint32_t tag = (lds32(S_EP) + 1) & 3;
  {
    cx lam[2], cf[2], l32[2], h[2];
#pragma unroll
    for (int q = 0; q < 2; q++) { ld2cx(par + q * 128, lam[q], cf[q]); l32[q] = ldcx(par + 2048 + q * 128); }
    WG_WAIT(0);
    if (elect_one()) mbar_arrive(last_empty);
    asm volatile("setmaxnreg.inc.sync.aligned.u32 168;");
    reg_fence(aR); reg_fence(aI);
    TIM(3 + ph * 2);
#pragma unroll
    for (int q = 0; q < 2; q++) h[q] = {aR[2 * q], -aI[2 * q]};
#pragma unroll
    for (int s = 1; s < 32; s++)
#pragma unroll
      for (int q = 0; q < 2; q++) {
        const int i = 4 * (s >> 1) + 2 * q + (s & 1);
        h[q] = cfma(lam[q], h[q], {aR[i], -aI[i]});
      }
    sched_fence<1>();
    cx t[2][3];
#pragma unroll
    for (int q = 0; q < 2; q++)
#pragma unroll
      for (int k = 0; k < 3; k++) t[q][k] = {__shfl_up_sync(~0u, h[q].r, k + 1, 4), __shfl_up_sync(~0u, h[q].i, k + 1, 4)};
#pragma unroll
    for (int q = 0; q < 2; q++) {
      const cx z = {0.f, 0.f};
      cx ex = cfma(l32[q], csel(c >= 3, t[q][2], z), csel(c >= 2, t[q][1], z));
      ex = cfma(l32[q], ex, csel(c >= 1, t[q][0], z));
      h[q] = cmul(cf[q], cfma(l32[q], ex, h[q]));
      const cx u = cfma(lam[q], ex, {aR[2 * q], -aI[2 * q]});
      aR[2 * q] = u.r; aI[2 * q] = -u.i;
    }
    if (c == 3)
      asm volatile("st.relaxed.gpu.global.v4.u32 [%0], {%1,%2,%3,%4};" ::"l"(agg + ti * 256),
                   "r"((__float_as_uint(h[0].r) & ~3u) | tag), "r"((__float_as_uint(h[0].i) & ~3u) | tag),
                   "r"((__float_as_uint(h[1].r) & ~3u) | tag), "r"((__float_as_uint(h[1].i) & ~3u) | tag) : "memory");
    TIM(8 + ph * 4);
    sched_fence<2>();
#pragma unroll
    for (int i = 0; i < 64; i++) {
      const cx u = cmul(cf[(i >> 1) & 1], {aR[i], -aI[i]});
      aR[i] = u.r; aI[i] = u.i;
    }
    reg_fence(aR); reg_fence(aI);
    sched_fence<3>();
  }
  TIM(27 + ph);
  cx h[2] = {{0.f, 0.f}, {0.f, 0.f}};
  if (ti > 0) {
    const uint2* ap = (const uint2*)(agg + (ti - 1 - (c >> 1)) * 256) + (c & 1);
    const int cnt = ti - (c >> 1);
    const cx l128 = ldcx(par + 2048 + 8 + (c & 1) * 128);
    uint2 v[8];
    int n = 0;
    while (true) {
      uint32_t bad = 0;
#pragma unroll
      for (int j = 0; j < 8; j++) {
        v[j] = make_uint2(tag, tag);
        if (2 * j < cnt)
          asm volatile("ld.relaxed.gpu.global.v2.u32 {%0,%1}, [%2];" : "=r"(v[j].x), "=r"(v[j].y) : "l"(ap - j * 1024) : "memory");
      }
#pragma unroll
      for (int j = 0; j < 8; j++) bad |= (v[j].x ^ tag) | (v[j].y ^ tag);
      if (!__any_sync(~0u, bad & 3)) break;
      trap_if(++n >= SPIN_LIMIT);
    }
    const cx l256 = csq(l128);
    cx a = {__uint_as_float(v[7].x), __uint_as_float(v[7].y)};
#pragma unroll
    for (int j = 6; j >= 0; j--) a = cfma(l256, a, {__uint_as_float(v[j].x), __uint_as_float(v[j].y)});
    if (c & 2) a = cmul(a, l128);
    const cx l32a = ldcx(par + 2048), l32b = ldcx(par + 2048 + 128);
    const cx t1 = {__shfl_xor_sync(~0u, a.r, 1), __shfl_xor_sync(~0u, a.i, 1)};
    const cx t2 = {__shfl_xor_sync(~0u, a.r, 2), __shfl_xor_sync(~0u, a.i, 2)};
    const cx t3 = {__shfl_xor_sync(~0u, a.r, 3), __shfl_xor_sync(~0u, a.i, 3)};
    const cx own = {a.r + t2.r, a.i + t2.i}, oth = {t1.r + t3.r, t1.i + t3.i};
#pragma unroll
    for (int q = 0; q < 2; q++) {
      const cx l32 = q ? l32b : l32a;
      cx x = csel((c & 1) == q, own, oth);
      if (c & 1) x = cmul(x, l32);
      if (c & 2) x = cmul(x, csq(l32));
      h[q] = x;
    }
  }
  TIM(9 + ph * 4);
  const cx lam[2] = {ldcx(par), ldcx(par + 128)};
  mbar_wait(B_SFREE + 8 * ph, 0);
  const uint32_t hs = S_STG + w * 1024 + r * 64 + ((c ^ (r >> 1)) << 4);
  uint32_t pi[4][2][4];
#pragma unroll
  for (int i = 0; i < 4; i++) {
    uint32_t pr[2][4];
#pragma unroll
    for (int s2 = 0; s2 < 4; s2++)
#pragma unroll
      for (int q = 0; q < 2; q++) {
        const int k = 4 * (4 * i + s2) + 2 * q;
        cx h0 = cfma(lam[q], h[q], {aR[k], aI[k]});
        h[q] = cfma(lam[q], h0, {aR[k + 1], aI[k + 1]});
        pr[q][s2] = pack2(h0.r, h[q].r);
        pi[i][q][s2] = pack2(h0.i, h[q].i);
      }
#pragma unroll
    for (int q = 0; q < 2; q++) sts128(hs + i * 4096 + q * 512, pr[q][0], pr[q][1], pr[q][2], pr[q][3]);
    if (i & 1) {
      bar_arrive(9 + (i >> 1), 160);
      if (i == 1) sched_fence<8>(); else sched_fence<9>();
    }
  }
  TIM(10 + ph * 4);
#pragma unroll
  for (int i = 0; i < 4; i++)
#pragma unroll
    for (int q = 0; q < 2; q++) sts128(hs + 16384 + i * 4096 + q * 512, pi[i][q][0], pi[i][q][1], pi[i][q][2], pi[i][q][3]);
  bar_arrive(11, 160);
  bar_sync(1 + ph, 128);
  asm volatile("setmaxnreg.dec.sync.aligned.u32 160;");
}

__device__ __forceinline__ void eterm(const Ptrs& p, int ti, int pj, int tid, uint32_t tag) {
  const int w = tid >> 5, lane = tid & 31, r = lane >> 2, c = lane & 3;
  const int trow = 64 * (w & 1) + 8 * (w >> 1) + r;
  const int rs = 2 * (r & 3) + (r >> 2);
  uint2 xv[2][8][2], ds[8];
  {
    uint2 gw[8];
#pragma unroll
    for (int jj = 0; jj < 8; jj++) {
      gw[jj] = ldg64(p.gw + pj * 128 + 16 * jj + 4 * c);
      ds[jj] = ldg64(p.dskip + pj * 128 + 16 * jj + 4 * c);
    }
    mbar_wait_long(B_XT, 0);
    float s[4];
#pragma unroll
    for (int i = 0; i < 4; i++) {
      s[i] = 0.f;
#pragma unroll
      for (int jj = 0; jj < 8; jj++) {
        uint2& x = xv[i >> 1][jj][i & 1];
        const uint32_t a = S_STG + (jj >> 2) * 16384 + (trow - r + rs + 16 * (i >> 1) + 32 * (i & 1)) * 128 + (((2 * (jj & 3) + (c >> 1)) ^ rs) << 4) + (c & 1) * 8;
        asm volatile("ld.shared.v2.u32 {%0,%1}, [%2];" : "=r"(x.x), "=r"(x.y) : "r"(a) : "memory");
        const uint32_t q = hfma2(x.x, gw[jj].x, hmul2(x.y, gw[jj].y));
        s[i] += bf_lo(q) + bf_hi(q);
      }
    }
    float u0 = (c & 1) ? s[1] : s[0], v0 = (c & 1) ? s[0] : s[1];
    float u1 = (c & 1) ? s[3] : s[2], v1 = (c & 1) ? s[2] : s[3];
    u0 += __shfl_xor_sync(~0u, v0, 1);
    u1 += __shfl_xor_sync(~0u, v1, 1);
    float u = (c & 2) ? u1 : u0;
    u += __shfl_xor_sync(~0u, (c & 2) ? u0 : u1, 2);
    asm volatile("st.relaxed.gpu.global.u32 [%0], %1;" ::"l"(g_gate + pj * SEQ + ti * 128 + trow + 16 * (c >> 1) + 32 * (c & 1)),
                 "r"((__float_as_uint(u) & ~3u) | tag) : "memory");
  }
  {
    float l;
    int n = 0;
    while (true) {
      __nanosleep(200);
      uint32_t v[8], bad = 0;
#pragma unroll
      for (int j = 0; j < 8; j++) v[j] = ld_relaxed(g_gate + j * SEQ + ti * 128 + tid) ^ tag;
      l = 0.f;
#pragma unroll
      for (int j = 0; j < 8; j++) { bad |= v[j]; l += __uint_as_float(v[j]); }
      if (!__any_sync(~0u, bad & 3)) break;
      trap_if(++n >= SPIN_LIMIT);
    }
    const float g = bf_round(1.f / (1.f + __expf(-bf_round(l))));
    asm volatile("st.shared.f32 [%0], %1;" ::"r"(S_G + tid * 4), "f"(g) : "memory");
  }
  bar_sync(2, 128);
  TIM(31);
  uint32_t g2[2][2], og2[2][2];
#pragma unroll
  for (int mh = 0; mh < 2; mh++)
#pragma unroll
    for (int hf = 0; hf < 2; hf++) {
      uint32_t g;
      asm volatile("ld.shared.u32 %0, [%1];" : "=r"(g) : "r"(S_G + (trow + 16 * mh + 32 * hf) * 4) : "memory");
      g2[mh][hf] = __byte_perm(g, g, 0x3232);
      og2[mh][hf] = hsub2(0x3f803f80u, g2[mh][hf]);
    }
  mbar_wait_long(B_ZT, 0);
  TIM(16);
  const int dl = lane & 15;
  const uint32_t za = S_CIN + (w & 1) * 16384 + dl * 128;
#pragma unroll
  for (int mh = 0; mh < 2; mh++) {
    const uint32_t zb = za + (((4 * (lane >> 4) + 2 * mh + (w >> 1)) ^ (dl & 7)) << 4);
#pragma unroll
    for (int jj = 0; jj < 8; jj++) {
      uint4 z = ldsm4t(zb + jj * 2048);
#pragma unroll
      for (int hf = 0; hf < 2; hf++) {
        uint2& x = xv[mh][jj][hf];
        x.x = hmul2(x.x, hfma2(og2[mh][hf], hf ? z.z : z.x, hmul2(g2[mh][hf], ds[jj].x)));
        x.y = hmul2(x.y, hfma2(og2[mh][hf], hf ? z.w : z.y, hmul2(g2[mh][hf], ds[jj].y)));
      }
      sts128(S_STG + (mh * 8 + jj) * 2048 + tid * 16, xv[mh][jj][0].x, xv[mh][jj][0].y, xv[mh][jj][1].x, xv[mh][jj][1].y);
    }
  }
  bar_arrive(5, 256);
  TIM(17);
}

__device__ __forceinline__ void store_half(float (&a)[64], float* op, uint32_t ea, float g0, float g1) {
#pragma unroll
  for (int jj = 0; jj < 8; jj++) {
    uint4 e = lds128(ea + jj * 2048);
    stg128(op + 16 * jj, __float_as_uint(fmaf(g0, a[8 * jj], bf_lo(e.x))), __float_as_uint(fmaf(g0, a[8 * jj + 1], bf_hi(e.x))),
           __float_as_uint(fmaf(g0, a[8 * jj + 4], bf_lo(e.y))), __float_as_uint(fmaf(g0, a[8 * jj + 5], bf_hi(e.y))));
    stg128(op + 32 * DM + 16 * jj, __float_as_uint(fmaf(g1, a[8 * jj + 2], bf_lo(e.z))), __float_as_uint(fmaf(g1, a[8 * jj + 3], bf_hi(e.z))),
           __float_as_uint(fmaf(g1, a[8 * jj + 6], bf_lo(e.w))), __float_as_uint(fmaf(g1, a[8 * jj + 7], bf_hi(e.w))));
  }
}

__device__ __forceinline__ void ring_acquire(int s, int sl, int par, int grp) {
  mbar_wait(B_EMPTY + 8 * sl, par);
  flag_add(F_GRP + grp);
  const int need = (s - NS - LEAD + 1) * GRP;
  int v, n = 0;
  while (true) {
    asm volatile("ld.volatile.shared.u32 %0, [%1];" : "=r"(v) : "r"(S_MIR) : "memory");
    if (v >= need) break;
    __nanosleep(40);
    trap_if(++n >= SPIN_LIMIT);
  }
}

__device__ __forceinline__ void issue_g1(const Maps& m, int s, int sl, int ti, int pj) {
  const uint32_t bar = B_FULL + 8 * sl, dst = sb + sl * STAGE;
  const int k0 = (s & 15) * 64, ch = (s >> 4) * 512 + pj * 64;
  mbar_expect(bar, STAGE);
  tma4d(dst + 16384, &m.x, bar, k0, 0, 4 * ti, 0);
  tma2d(dst, &m.bre, bar, k0, ch);
  tma2d(dst + 8192, &m.bim, bar, k0, ch);
}
__device__ __forceinline__ void producer(const Maps& m, int b, int ti, int pj) {
#pragma unroll
  for (int s = EARLY; s < NS; s++) issue_g1(m, s, s, ti, pj);
  int sl = 0, par = 0;
#pragma unroll 1
  for (int s = NS; s < 32; s++) {
    ring_acquire(s, sl, par, b / GRP);
    issue_g1(m, s, sl, ti, pj);
    if (++sl == NS) { sl = 0; par ^= 1; }
  }
#pragma unroll 1
  for (int q = 0; q < 32; q++) {
    ring_acquire(q + 32, sl, par, b / GRP);
    const uint32_t bar = B_FULL + 8 * sl, dst = sb + sl * STAGE;
    mbar_expect(bar, STAGE);
    tma5d(dst + 16384, (q & 8) ? &m.cim : &m.cre, bar, (q >> 4) * 512 + (q & 7) * 64, 0, 0, 0, pj * 8);
    if ((q & 7) == 0) {
      mbar_wait(B_FLG + q, 0);
      fence_async_global();
      if ((q & 15) == 0) TIM(24 + (q >> 4));
    }
    bulk_load(dst, g_h + (size_t)(ti * 32 + q) * 1024, 16384, bar);
    if (++sl == NS) { sl = 0; par ^= 1; }
  }
}

__device__ __forceinline__ void poller(int b, int ti, int pj, int lane, unsigned ep) {
  if (lane < 8) {
    const int f = lane == 0 ? F_GRP + b / GRP : (lane < 5 ? F_H + (lane - 1) * 16 + ti : (lane < 7 ? F_U + pj * 2 + lane - 5 : F_Z + pj));
    const unsigned per = lane == 0 ? GRP * (64 - NS) : (lane < 5 ? 8 : 16);
    const unsigned base = ep * per;
    int need = lane ? per : GRP * (64 - NS - LEAD);
    int n = SPIN_LIMIT, left = 8;
    do {
      const int v = ld_relaxed(g_flag + f * 32) - base;
      asm volatile("st.volatile.shared.u32 [%0], %1;" ::"r"(S_MIR + 4 * lane), "r"(v) : "memory");
      const unsigned hit = __ballot_sync(0xffu, v >= need);
      if (hit) {
        if (v >= need) {
          need = 0x7fffffff;
          if (lane) {
            asm volatile("fence.acquire.gpu;" ::: "memory");
            mbar_arrive(B_FLG - 8 + 8 * lane);
          }
        }
        left -= __popc(hit);
      }
    } while (left && --n);
    trap_if(n == 0);
  }
}

__device__ __forceinline__ void storer(const Maps& m, int ti, int pj) {
  unsigned t = clock();
#pragma unroll 1
  for (int job = -2; job < 4; job++) {
#pragma unroll 1
    for (int i = 0; i < 4; i++) {
      if (job > 0 && (job & 1)) { if (i == 0) bar_sync(11, 160); }
      else if (!(i & 1)) bar_sync(job == -2 ? 15 - 2 * i : 9 + (i >> 1), 160);
      if (!(i & 1)) fence_async_smem();
      const uint32_t src = job >= 0 ? S_STG + (job & 1) * 16384 + i * 4096
                                    : (job == -2 ? S_CIN + i * 4096 : S_STG + 8192 + (i >> 1) * 16384 + (i & 1) * 4096);
      uint4* dst = job < 0 ? g_u + (size_t)((pj * 4 + (job + 2) * 2 + (i & 1)) * 32 + ti * 2 + (i >> 1)) * 256
                           : g_h + (size_t)(ti * 32 + job * 8 + pj) * 1024 + i * 256;
      wait_clock(t);
      t = clock() + PACE;
      if (elect_one()) bulk_store(dst, src, 4096);
    }
    if (elect_one()) {
      bulk_commit();
      bulk_done_signal(job < 0 ? F_U + pj * 2 + job + 2 : F_H + job * 16 + ti);
      if (job == -1 || job == 1) mbar_arrive(B_SFREE + 4 + 4 * job);
    }
    __syncwarp();
    if (job == 0 || job == 2) TIM(11 + job * 2);
    if (job == -2) TIM(1);
    if (job == -1) TIM(23);
  }
  if (elect_one()) {
    mbar_expect(B_XT, 32768);
    tma4d(S_STG, &m.x2, B_XT, pj * 128, 0, 0, ti * 16);
    wait_clock(clock() + LD_GAP);
    tma4d(S_STG + 16384, &m.x2, B_XT, pj * 128 + 64, 0, 0, ti * 16);
    mbar_wait_long(B_FLG + 48, 0);
    fence_async_global();
    mbar_expect(B_ZT, 32768);
    tma5d(S_CIN, &m.z, B_ZT, ti * 128, 0, 0, 0, pj * 8);
    wait_clock(clock() + LD_GAP);
    tma5d(S_CIN + 16384, &m.z, B_ZT, ti * 128 + 64, 0, 0, 0, pj * 8);
  }
}

__device__ __forceinline__ void conv_loader(const Maps& m, const Ptrs& p, int b, int ti, int pj, unsigned t_start) {
  if (NCH > 0) bar_arrive(13, 160);
  unsigned tt = t_start + KV0_AT;
#pragma unroll 1
  for (int st = 0; st < 4; st++) {
    const int d = pj * 128 + (st >> 1) * 64, tb = ti * 16 + (st & 1) * 8;
    const uint32_t bar = B_PIN + 8 * st;
    if (st >= 2) bar_sync(st == 2 ? 14 : 12, 160);
    if (elect_one()) {
      mbar_expect(bar, 16384 + 384);
      if ((int)(clock() - tt) > 0) tt = clock();
#pragma unroll 1
      for (int i = 0; i < 4; i++) {
        wait_clock(tt);
        tt += st == 3 ? KV_GAP1 : KV_GAP;
        tma3d(S_STG + (st & 1) * 16384 + i * 4096, (i & 2) ? &m.v : &m.k, bar, d, tb, (i & 1) * 4);
        if (i == 0) tma3d(S_T + st * 512, &m.kh, bar, d, tb - 1, 5);
      }
      if (st == 3) l2_prefetch(p.f + (size_t)conv_chan(ti, pj, 0) * SEQ, 2 * 4096);
    }
    tt = __shfl_sync(~0u, tt, 0);
  }
#pragma unroll 1
  for (int ch = 0; ch < NCH + 3; ch++) {
    if (ch < NCH) {
      const int d = conv_chan(ti, pj, ch);
      const uint32_t bar = B_CINF + 8 * (ch & 1), dst = S_CIN + (ch & 1) * 8192;
      if (ch >= 2) bar_sync(12, 160);
      if (elect_one()) {
        mbar_expect(bar, 8192);
        if ((ch & 3) == 0) {
          mbar_wait_long(B_FLG + 32 + 2 * ch, 0);
          fence_async_global();
        }
        tma2d(dst + 4096, &m.f, bar, 0, d * 128);
        tma3d(dst, &m.u, bar, 0, 4 * (d & 31), d & ~31);
      }
      __syncwarp();
    }
    if (ch >= 3) {
      bar_sync(4, 160);
      fence_async_smem();
      if (elect_one()) {
        uint4* dst = g_z + (size_t)conv_chan(ti, pj, ch - 3) * 256;
#pragma unroll
        for (int i = 0; i < 4; i++) bulk_store(dst + i * 64, S_T + i * 2048, 1024);
        bulk_commit();
        bulk_wait_read();
      }
      __syncwarp();
      if (ch < NCH + 2) bar_arrive(13, 160);
    }
  }
  if (elect_one()) bulk_done_signal(F_Z + pj);
}

template <int TA>
__device__ __forceinline__ void gemm_step(float (&a0)[64], float (&a1)[64], uint32_t so, uint32_t rel) {
  WG_FENCE();
#pragma unroll
  for (int k = 0; k < 4; k++) {
    const uint64_t db = mkdesc(so + dlo(sb + 16384 + 32 * k, 16), 1024, 1);
    if (TA == 0) {
      wgmma_ss128<0, 0, 1>(a0, mkdesc(so + dlo(sb + 32 * k, 16), 1024, 1), db);
      wgmma_ss128<0, 0, 1>(a1, mkdesc(so + dlo(sb + 8192 + 32 * k, 16), 1024, 1), db);
    } else {
      wgmma_ss128<1, 0, 1>(a0, mkdesc(so + dlo(sb + 1024 * k, 4096), 512, 2), db);
      wgmma_ss128<1, 0, 1>(a1, mkdesc(so + dlo(sb + 8192 + 1024 * k, 4096), 512, 2), db);
    }
  }
  WG_COMMIT();
  WG_WAIT(1);
  if (rel && elect_one()) mbar_arrive(rel);
}

__global__ void __launch_bounds__(512, 1) fused_kernel(const __grid_constant__ Maps m, const __grid_constant__ Ptrs p) {
  extern __shared__ __align__(1024) uint8_t smem_raw[];
  const int b = blockIdx.x;
#define GRID 128
  const int ti = ((b >> 5) << 2) | (b & 3), pj = (((b >> 4) & 1) << 2) | ((b >> 2) & 3);
  const int wid = __shfl_sync(~0u, threadIdx.x >> 5, 0), wg = wid >> 2, tid = threadIdx.x & 127, lane = threadIdx.x & 31;
  if (wg == 0) TIM(0);
  const unsigned t_start = clock();
  if (wid == 12) {
    if (elect_one()) {
      asm volatile("prefetch.tensormap [%0];" ::"l"(&m.x) : "memory");
      asm volatile("prefetch.tensormap [%0];" ::"l"(&m.bre) : "memory");
      asm volatile("prefetch.tensormap [%0];" ::"l"(&m.bim) : "memory");
#pragma unroll
      for (int i = 0; i < NS; i++) mbar_init(B_FULL + 8 * i, 1);
      fence_async_smem();
#pragma unroll
      for (int s = 0; s < EARLY; s++) issue_g1(m, s, s, ti, pj);
    }
  } else if (wid == 13) {
    if (elect_one()) {
      trap_if((uint32_t)__cvta_generic_to_shared(smem_raw) != sb);
      asm volatile("st.shared.u32 [%0], 0;" ::"r"(S_MIR) : "memory");
#pragma unroll
      for (uint32_t bar = B_EMPTY; bar < S_MIR; bar += 8) mbar_init(bar, bar < B_CINF ? 4 : 1);
      fence_async_smem();
    }
  }
  __syncwarp();
  if (wg == 3) {
    asm volatile("setmaxnreg.dec.sync.aligned.u32 24;");
    bar_sync(0, 512);
    if (wid == 12) { if (elect_one()) producer(m, b, ti, pj); }
    else if (wid == 13) poller(b, ti, pj, lane, ld_relaxed(g_epoch + b));
    else if (wid == 14) storer(m, ti, pj);
    else conv_loader(m, p, b, ti, pj, t_start);
  } else if (wg == 2) {
    asm volatile("setmaxnreg.inc.sync.aligned.u32 160;");
    bar_sync(0, 512);
    conv_tables(tid);
    conv_main(p, ti, pj, tid);
  } else {
    asm volatile("setmaxnreg.inc.sync.aligned.u32 160;");
    if (wg == 1) {
      bar_sync(0, 512);
      const int ch = (tid >> 6) * 512 + pj * 64 + (tid & 63);
      const unsigned ep = ld_relaxed(g_epoch + b);
      const float lr = __bfloat162float(p.lre[ch]), li = __bfloat162float(p.lim[ch]);
      const float dt = bf_round(expf(__bfloat162float(p.ldt[ch])));
      float sn, cs;
      sincosf(dt * li, &sn, &cs);
      const float ex = expf(dt * lr);
      const float ar = ex * cs, ai = ex * sn;
      const float inv = 2.f / (lr * lr + li * li);
      const float cr = ((ar - 1.f) * lr + ai * li) * inv, ci = (ai * lr - (ar - 1.f) * li) * inv;
      sts128(S_PAR + tid * 16, __float_as_uint(ar), __float_as_uint(-ai), __float_as_uint(cr), __float_as_uint(-ci));
      const cx l32 = csq(csq(csq(csq(csq({ar, -ai}))))), l128 = csq(csq(l32));
      sts128(S_PAR + 2048 + tid * 16, __float_as_uint(l32.r), __float_as_uint(l32.i), __float_as_uint(l128.r), __float_as_uint(l128.i));
      if (tid == 0) asm volatile("st.shared.u32 [%0], %1;" ::"r"(S_EP), "r"(ep) : "memory");
      bar_arrive(6, 256);
      prep<0>(p, ti, pj, wid & 3, lane);
    }
    float a0[64], a1[64];
    int sl = wg ? 16 % NS : 0, par = wg ? (16 / NS) & 1 : 0;
    uint32_t rel = 0;
    zero(a0); zero(a1);
    reg_fence(a0); reg_fence(a1);
    if (wg == 1) bar_sync(7, 256); else bar_sync(0, 512);
#pragma unroll 1
    for (int s = 0; s < 16; s++) {
      mbar_wait(B_FULL + 8 * sl, par);
      if (s == 0) TIM(2 + wg * 2);
      if (s == 15) bar_arrive(7 + wg, 256);
      gemm_step<0>(a0, a1, sl * (STAGE >> 4), rel);
      rel = B_EMPTY + 8 * sl;
      if (++sl == NS) { sl = 0; par ^= 1; }
    }
    if (wg == 0) bar_sync(6, 256);
    scan_epilogue(a0, a1, rel, wg, ti, pj, tid);
    if (wg == 1) {
      eterm(p, ti, pj, tid, (lds32(S_EP) + 1) & 3);
    } else {
      sl = 32 % NS; par = (32 / NS) & 1; rel = 0;
      zero(a0); zero(a1);
      reg_fence(a0); reg_fence(a1);
      bar_sync(8, 256);
#pragma unroll 1
      for (int s = 0; s < 32; s++) {
        mbar_wait(B_FULL + 8 * sl, par);
        if (s == 0) TIM(6);
        if (s == 16) TIM(18);
        gemm_step<1>(a0, a1, sl * (STAGE >> 4), rel);
        rel = B_EMPTY + 8 * sl;
        if (++sl == NS) { sl = 0; par ^= 1; }
      }
      TIM(26);
      bar_sync(5, 256);
      const int w = tid >> 5, trow = 64 * (w & 1) + 8 * (w >> 1) + (lane >> 2);
      float g[4];
#pragma unroll
      for (int i = 0; i < 4; i++)
        asm volatile("ld.shared.f32 %0, [%1];" : "=f"(g[i]) : "r"(S_G + (trow + 16 * (i >> 1) + 32 * (i & 1)) * 4) : "memory");
      WG_WAIT(0);
      reg_fence(a0); reg_fence(a1);
      TIM(7);
      float* op = p.out + (size_t)(ti * 128 + trow) * DM + pj * 128 + 4 * (lane & 3);
      store_half(a0, op, S_STG + tid * 16, g[0], g[1]);
      store_half(a1, op + 16 * DM, S_STG + 16384 + tid * 16, g[2], g[3]);
      if (tid == 0) g_epoch[b] = lds32(S_EP) + 1;
      TIM(19);
    }
  }
}

typedef CUresult (*EncFn)(CUtensorMap*, CUtensorMapDataType, cuuint32_t, void*, const cuuint64_t*, const cuuint64_t*,
                          const cuuint32_t*, const cuuint32_t*, CUtensorMapInterleave, CUtensorMapSwizzle,
                          CUtensorMapL2promotion, CUtensorMapFloatOOBfill);

void encode(EncFn enc, CUtensorMap* m, const void* ptr, int rank, const cuuint64_t* dims, const cuuint64_t* strides,
            const cuuint32_t* box, CUtensorMapSwizzle sw) {
  cuuint32_t es[5] = {1, 1, 1, 1, 1};
  enc(m, CU_TENSOR_MAP_DATA_TYPE_BFLOAT16, rank, const_cast<void*>(ptr), dims, strides, box, es, CU_TENSOR_MAP_INTERLEAVE_NONE,
      sw, PROMO, CU_TENSOR_MAP_FLOAT_OOB_FILL_NONE);
}

}

extern "C" void kernel_launch(void* const* d_in, const int* in_sizes, int n_in, void* d_out, int out_size) {
  typedef const __nv_bfloat16* bp;
  Ptrs p;
  p.x = (bp)d_in[0]; p.lre = (bp)d_in[1]; p.lim = (bp)d_in[2]; p.bre = (bp)d_in[3]; p.bim = (bp)d_in[4];
  p.cre = (bp)d_in[5]; p.cim = (bp)d_in[6]; p.ldt = (bp)d_in[7]; p.dskip = (bp)d_in[8];
  p.k = (bp)d_in[10]; p.v = (bp)d_in[11]; p.shift = (bp)d_in[12]; p.f = (bp)d_in[13]; p.ssmd = (bp)d_in[14];
  p.gw = (bp)d_in[15]; p.out = (float*)d_out;

  EncFn enc = nullptr;
  cudaDriverEntryPointQueryResult qr;
  cudaGetDriverEntryPoint("cuTensorMapEncodeTiled", (void**)&enc, cudaEnableDefault, &qr);
  void *zptr = nullptr, *uptr = nullptr;
  cudaGetSymbolAddress(&zptr, g_z);
  cudaGetSymbolAddress(&uptr, g_u);

  Maps m;
  {
    cuuint64_t d[4] = {1024, 2, 64, 16}, s[3] = {2048, 65536, 4096};
    cuuint32_t bx[4] = {64, 2, 4, 16};
    encode(enc, &m.x, p.x, 4, d, s, bx, CU_TENSOR_MAP_SWIZZLE_128B);
  }
  {
    cuuint64_t d[2] = {1024, 1024}, s[1] = {2048};
    cuuint32_t bx[2] = {64, 64};
    encode(enc, &m.bre, p.bre, 2, d, s, bx, CU_TENSOR_MAP_SWIZZLE_128B);
    encode(enc, &m.bim, p.bim, 2, d, s, bx, CU_TENSOR_MAP_SWIZZLE_128B);
  }
  {
    cuuint64_t d[5] = {1024, 2, 4, 2, 64}, s[4] = {2048, 8192, 4096, 32768};
    cuuint32_t bx[5] = {64, 2, 4, 2, 8};
    encode(enc, &m.cre, p.cre, 5, d, s, bx, CU_TENSOR_MAP_SWIZZLE_128B);
    encode(enc, &m.cim, p.cim, 5, d, s, bx, CU_TENSOR_MAP_SWIZZLE_128B);
  }
  {
    cuuint64_t d[2] = {16, 1024 * 128}, s[1] = {32};
    cuuint32_t bx[2] = {16, 128};
    encode(enc, &m.f, p.f, 2, d, s, bx, CU_TENSOR_MAP_SWIZZLE_32B);
  }
  {
    cuuint64_t d[3] = {16, 128, 1024}, s[2] = {32, 4096};
    cuuint32_t bx[3] = {16, 4, 32};
    encode(enc, &m.u, uptr, 3, d, s, bx, CU_TENSOR_MAP_SWIZZLE_32B);
  }
  {
    cuuint64_t d[3] = {1024, 256, 8}, s[2] = {16384, 2048};
    cuuint32_t bx[3] = {64, 8, 4}, bh[3] = {64, 1, 3};
    encode(enc, &m.k, p.k, 3, d, s, bx, CU_TENSOR_MAP_SWIZZLE_128B);
    encode(enc, &m.kh, p.k, 3, d, s, bh, CU_TENSOR_MAP_SWIZZLE_NONE);
    encode(enc, &m.v, p.v, 3, d, s, bx, CU_TENSOR_MAP_SWIZZLE_128B);
  }
  {
    cuuint64_t d[5] = {2048, 2, 4, 2, 64}, s[4] = {4096, 16384, 8192, 65536};
    cuuint32_t bx[5] = {64, 2, 4, 2, 8};
    encode(enc, &m.z, zptr, 5, d, s, bx, CU_TENSOR_MAP_SWIZZLE_128B);
  }
  {
    cuuint64_t d[4] = {1024, 2, 4, 256}, s[3] = {8192, 2048, 16384};
    cuuint32_t bx[4] = {64, 2, 4, 16};
    encode(enc, &m.x2, p.x, 4, d, s, bx, CU_TENSOR_MAP_SWIZZLE_128B);
  }
  cudaFuncSetAttribute(fused_kernel, cudaFuncAttributeMaxDynamicSharedMemorySize, SMEM_BYTES);
  fused_kernel<<<GRID, 512, SMEM_BYTES, cudaStreamPerThread>>>(m, p);
}
```

```cpp
#include <cuda_runtime.h>
#include <cuda_bf16.h>
#include <cuda.h>
#include <stdint.h>

namespace {

constexpr int SEQ = 2048, DM = 1024;
constexpr int NS = 5;
constexpr int STAGE = 32768;
#define LEAD 4
#define GRP 16
#define PACE 280
#define KV0_AT 600
#define KV_GAP 600
#define KV_GAP0 600
#define KV_GAP1 600
#define EARLY 1
#define SFM 0x17
#define RV 1
#define POLL_NS 60
#define PACE0 120
#define SPF_AT 9000
#define RELK 0
#define RES 4
#define LD_GAP 400
#define LDQ ""
#define PROMO CU_TENSOR_MAP_L2_PROMOTION_L2_128B
constexpr uint32_t sb = 1024;
constexpr uint32_t S_STG = sb + NS * STAGE;
constexpr uint32_t S_CIN = S_STG + 32768;
constexpr uint32_t S_T = S_CIN + 16384;
constexpr uint32_t S_M1 = S_T + 8192;
constexpr uint32_t S_M2 = S_M1 + 4096;
constexpr uint32_t S_PAR = S_M2 + 2048;
constexpr uint32_t S_G = S_PAR + 4096;
constexpr uint32_t S_BAR = S_G + 512;
constexpr int SMEM_BYTES = S_BAR + 512 - sb;
constexpr uint32_t B_FULL = S_BAR, B_EMPTY = B_FULL + 8 * NS, B_CINF = B_EMPTY + 8 * NS,
                   B_FLG = B_CINF + 24, B_SFREE = B_FLG + 72, B_ZT = B_SFREE + 16,
                   B_XT = B_ZT + 24, B_PIN = B_XT + 16, B_DUMMY = B_PIN + 32, S_MIR = B_DUMMY + 8, S_EP = S_MIR + 40;
constexpr int SPIN_LIMIT = 1 << 21;
constexpr int F_GRP = 0, F_H = 8, F_U = 72, F_Z = 88;

struct alignas(64) Maps { CUtensorMap x, bre, bim, cre, cim, u, z, x2, k, kh, v; };
struct Ptrs {
  const __nv_bfloat16 *x, *lre, *lim, *ldt, *dskip, *k, *v, *shift, *f, *ssmd, *gw, *bre, *bim, *cre, *cim;
  float* out;
  uint64_t dc1[12][NS], dc2[12][NS];
};

__device__ uint4 g_h[16 * 32 * 1024];
__device__ uint4 g_u[1024 * 256];
__device__ uint4 g_z[1024 * 256];
__device__ uint4 g_agg[2 * 16 * 256];
__device__ unsigned g_gate[8 * SEQ];
__device__ unsigned g_flag[112 * 32];
__device__ unsigned g_epoch[132];
#define TIM(i)
#define TIMC(i)

#define WG_FENCE() asm volatile("wgmma.fence.sync.aligned;" ::: "memory")
#define WG_COMMIT() asm volatile("wgmma.commit_group.sync.aligned;" ::: "memory")
#define WG_WAIT(n) asm volatile("wgmma.wait_group.sync.aligned %0;" ::"n"(n) : "memory")
#define R8(d, o) "+f"(d[o + 0]), "+f"(d[o + 1]), "+f"(d[o + 2]), "+f"(d[o + 3]), "+f"(d[o + 4]), "+f"(d[o + 5]), "+f"(d[o + 6]), "+f"(d[o + 7])
#define W8(d, o) "=f"(d[o + 0]), "=f"(d[o + 1]), "=f"(d[o + 2]), "=f"(d[o + 3]), "=f"(d[o + 4]), "=f"(d[o + 5]), "=f"(d[o + 6]), "=f"(d[o + 7])
#define L16 "%0,%1,%2,%3,%4,%5,%6,%7,%8,%9,%10,%11,%12,%13,%14,%15"
#define L64 L16 ",%16,%17,%18,%19,%20,%21,%22,%23,%24,%25,%26,%27,%28,%29,%30,%31," \
  "%32,%33,%34,%35,%36,%37,%38,%39,%40,%41,%42,%43,%44,%45,%46,%47,%48,%49,%50,%51,%52,%53,%54,%55,%56,%57,%58,%59,%60,%61,%62,%63"

template <int TA, int TB, int ACC>
__device__ __forceinline__ void wgmma_ss128(float (&d)[64], uint64_t da, uint64_t db) {
  if (ACC)
    asm volatile("wgmma.mma_async.sync.aligned.m64n128k16.f32.bf16.bf16 {" L64 "}, %64, %65, 1, 1, 1, %66, %67;"
                 : R8(d, 0), R8(d, 8), R8(d, 16), R8(d, 24), R8(d, 32), R8(d, 40), R8(d, 48), R8(d, 56)
                 : "l"(da), "l"(db), "n"(TA), "n"(TB));
  else
    asm volatile("wgmma.mma_async.sync.aligned.m64n128k16.f32.bf16.bf16 {" L64 "}, %64, %65, 0, 1, 1, %66, %67;"
                 : W8(d, 0), W8(d, 8), W8(d, 16), W8(d, 24), W8(d, 32), W8(d, 40), W8(d, 48), W8(d, 56)
                 : "l"(da), "l"(db), "n"(TA), "n"(TB));
}
template <int ACC, int TB = 0>
__device__ __forceinline__ void wgmma_rs32(float (&d)[16], uint32_t a0, uint32_t a1, uint32_t a2, uint32_t a3, uint64_t db) {
  if (ACC)
    asm volatile("wgmma.mma_async.sync.aligned.m64n32k16.f32.bf16.bf16 {" L16 "}, {%16,%17,%18,%19}, %20, 1, 1, 1, %21;"
                 : R8(d, 0), R8(d, 8) : "r"(a0), "r"(a1), "r"(a2), "r"(a3), "l"(db), "n"(TB));
  else
    asm volatile("wgmma.mma_async.sync.aligned.m64n32k16.f32.bf16.bf16 {" L16 "}, {%16,%17,%18,%19}, %20, 0, 1, 1, %21;"
                 : W8(d, 0), W8(d, 8) : "r"(a0), "r"(a1), "r"(a2), "r"(a3), "l"(db), "n"(TB));
}
template <int N>
__device__ __forceinline__ void reg_fence(float (&d)[N]) {
#pragma unroll
  for (int i = 0; i < N; i++) asm volatile("" : "+f"(d[i])::"memory");
}
__host__ __device__ __forceinline__ constexpr uint32_t dlo(uint32_t addr, uint32_t lbo) { return (addr >> 4) + ((lbo >> 4) << 16); }
__device__ __forceinline__ uint64_t mkdesc(uint32_t lo, uint32_t sbo, uint32_t mode) {
  uint64_t d;
  asm("mov.b64 %0, {%1, %2};" : "=l"(d) : "r"(lo), "r"((sbo >> 4) | (mode << 30)));
  return d;
}
template <int N>
__device__ __forceinline__ void zero(float (&d)[N]) {
#pragma unroll
  for (int i = 0; i < N; i++) d[i] = 0.f;
}
__device__ __forceinline__ void trap_if(int c) {
  asm volatile("{.reg .pred p; .reg .b64 z; setp.ne.s32 p, %0, 0; mov.b64 z, 0; @p st.global.u32 [z], %0;}" ::"r"(c) : "memory");
}
template <int K>
__device__ __forceinline__ void sched_fence() {
  asm volatile("{.reg .pred p; setp.eq.u32 p, %0, %1; @p exit;}" ::"r"(gridDim.x), "n"(256 + K) : "memory");
}
template <int K>
__device__ __forceinline__ void sched_fence_async() {
  asm volatile("{.reg .pred p; .reg .u32 r; setp.ne.u32 p, %0, %1; @p bra.uni SFE;\n"
               "SFL: nanosleep.u32 1000; mov.u32 r, %%clock; setp.eq.u32 p, r, 0; @p bra.uni SFL;\nSFE: }" ::"r"(gridDim.x), "n"(256 + K) : "memory");
}
__device__ __forceinline__ bool elect_one() {
  uint32_t pred;
  asm volatile("{.reg .pred p; elect.sync _|p, 0xffffffff; selp.u32 %0, 1, 0, p;}" : "=r"(pred));
  return pred;
}
__device__ __forceinline__ void mbar_init(uint32_t bar, uint32_t cnt) {
  asm volatile("mbarrier.init.shared::cta.b64 [%0], %1;" ::"r"(bar), "r"(cnt) : "memory");
}
__device__ __forceinline__ bool mbar_try(uint32_t bar, uint32_t par) {
  uint32_t ok;
  asm volatile("{.reg .pred p; mbarrier.try_wait.parity.shared::cta.b64 p, [%1], %2; selp.u32 %0, 1, 0, p;}"
               : "=r"(ok) : "r"(bar), "r"(par) : "memory");
  return ok;
}
#undef DBGV
#define DBGV ((bar - S_BAR) * 2 + par)
__device__ __forceinline__ void mbar_wait(uint32_t bar, uint32_t par) {
  if (__builtin_expect(!mbar_try(bar, par), 0)) {
    int n = SPIN_LIMIT;
    while (!mbar_try(bar, par) && --n) {}
    trap_if(n == 0);
  }
}
#define full_wait(bar, par, slot) mbar_wait(bar, par)
__device__ __forceinline__ void mbar_wait_long(uint32_t bar, uint32_t par) {
  int n = SPIN_LIMIT;
  while (!mbar_try(bar, par) && --n) __nanosleep(100);
  trap_if(n == 0);
}
#undef DBGV
#define DBGV 0
__device__ __forceinline__ void mbar_arrive(uint32_t bar) {
  asm volatile("mbarrier.arrive.shared::cta.b64 _, [%0];" ::"r"(bar) : "memory");
}
__device__ __forceinline__ void mbar_expect(uint32_t bar, uint32_t bytes) {
  asm volatile("mbarrier.arrive.expect_tx.shared::cta.b64 _, [%0], %1;" ::"r"(bar), "r"(bytes) : "memory");
}
__device__ __forceinline__ void tma2d(uint32_t dst, const CUtensorMap* m, uint32_t bar, int c0, int c1) {
  asm volatile("cp.async.bulk.tensor.2d.shared::cluster.global.mbarrier::complete_tx::bytes [%0], [%1, {%3, %4}], [%2];"
               ::"r"(dst), "l"(m), "r"(bar), "r"(c0), "r"(c1) : "memory");
}
__device__ __forceinline__ void tma3d(uint32_t dst, const CUtensorMap* m, uint32_t bar, int c0, int c1, int c2) {
  asm volatile("cp.async.bulk.tensor.3d.shared::cluster.global.mbarrier::complete_tx::bytes [%0], [%1, {%3, %4, %5}], [%2];"
               ::"r"(dst), "l"(m), "r"(bar), "r"(c0), "r"(c1), "r"(c2) : "memory");
}
__device__ __forceinline__ void tma4d(uint32_t dst, const CUtensorMap* m, uint32_t bar, int c0, int c1, int c2, int c3) {
  asm volatile("cp.async.bulk.tensor.4d.shared::cluster.global.mbarrier::complete_tx::bytes [%0], [%1, {%3, %4, %5, %6}], [%2];"
               ::"r"(dst), "l"(m), "r"(bar), "r"(c0), "r"(c1), "r"(c2), "r"(c3) : "memory");
}
__device__ __forceinline__ void tma5d(uint32_t dst, const CUtensorMap* m, uint32_t bar, int c0, int c1, int c2, int c3, int c4) {
  asm volatile("cp.async.bulk.tensor.5d.shared::cluster.global.mbarrier::complete_tx::bytes [%0], [%1, {%3, %4, %5, %6, %7}], [%2];"
               ::"r"(dst), "l"(m), "r"(bar), "r"(c0), "r"(c1), "r"(c2), "r"(c3), "r"(c4) : "memory");
}
__device__ __forceinline__ void bulk_load(uint32_t dst, const void* src, uint32_t bytes, uint32_t bar) {
  asm volatile("cp.async.bulk.shared::cluster.global.mbarrier::complete_tx::bytes [%0], [%1], %2, [%3];"
               ::"r"(dst), "l"(src), "r"(bytes), "r"(bar) : "memory");
}
__device__ __forceinline__ void l2_prefetch(const void* src, uint32_t bytes) {
  asm volatile("cp.async.bulk.prefetch.L2.global [%0], %1;" ::"l"(src), "r"(bytes) : "memory");
}
__device__ __forceinline__ void bar_sync(int id, int n) { asm volatile("bar.sync %0, %1;" ::"r"(id), "r"(n) : "memory"); }
__device__ __forceinline__ void bar_arrive(int id, int n) { asm volatile("bar.arrive %0, %1;" ::"r"(id), "r"(n) : "memory"); }
__device__ __forceinline__ void bulk_store(void* dst, uint32_t src, uint32_t bytes) {
  asm volatile("cp.async.bulk.global.shared::cta.bulk_group [%0], [%1], %2;" ::"l"(dst), "r"(src), "r"(bytes) : "memory");
}
__device__ __forceinline__ void bulk_commit() { asm volatile("cp.async.bulk.commit_group;" ::: "memory"); }
__device__ __forceinline__ void bulk_wait_read() { asm volatile("cp.async.bulk.wait_group.read 0;" ::: "memory"); }
__device__ __forceinline__ void fence_async_smem() { asm volatile("fence.proxy.async.shared::cta;" ::: "memory"); }
__device__ __forceinline__ void fence_async_global() { asm volatile("fence.proxy.async.global;" ::: "memory"); }
__device__ __forceinline__ void flag_add(int f) {
  asm volatile("red.relaxed.gpu.global.add.u32 [%0], 1;" ::"l"(g_flag + f * 32) : "memory");
}
template <int N = 0>
__device__ __forceinline__ void bulk_done_signal(int f) {
  asm volatile("cp.async.bulk.wait_group %0;" ::"n"(N) : "memory");
  fence_async_global();
  flag_add(f);
}
__device__ __forceinline__ unsigned ld_relaxed(const unsigned* p) {
  unsigned v;
  asm volatile("ld.relaxed.gpu.global.u32 %0, [%1];" : "=r"(v) : "l"(p) : "memory");
  return v;
}
__device__ __forceinline__ void wait_clock(unsigned t) {
  int d;
  while ((d = (int)(t - (unsigned)clock())) > 0) __nanosleep(d > 600 ? 200 : 40);
}
__device__ __forceinline__ uint32_t pack2(float lo, float hi) {
  uint32_t r;
  asm("cvt.rn.bf16x2.f32 %0, %1, %2;" : "=r"(r) : "f"(hi), "f"(lo));
  return r;
}
__device__ __forceinline__ float bf_lo(uint32_t v) { return __uint_as_float(v << 16); }
__device__ __forceinline__ float bf_hi(uint32_t v) { return __uint_as_float(v & 0xffff0000u); }
__device__ __forceinline__ float bf_round(float v) { return __bfloat162float(__float2bfloat16_rn(v)); }
__device__ __forceinline__ uint32_t hmul2(uint32_t a, uint32_t b) {
  uint32_t r;
  asm("mul.rn.bf16x2 %0, %1, %2;" : "=r"(r) : "r"(a), "r"(b));
  return r;
}
__device__ __forceinline__ uint32_t hadd2(uint32_t a, uint32_t b) {
  uint32_t r;
  asm("add.rn.bf16x2 %0, %1, %2;" : "=r"(r) : "r"(a), "r"(b));
  return r;
}
__device__ __forceinline__ uint32_t hsub2(uint32_t a, uint32_t b) {
  uint32_t r;
  asm("sub.rn.bf16x2 %0, %1, %2;" : "=r"(r) : "r"(a), "r"(b));
  return r;
}
__device__ __forceinline__ uint32_t hfma2(uint32_t a, uint32_t b, uint32_t c) {
  uint32_t r;
  asm("fma.rn.bf16x2 %0, %1, %2, %3;" : "=r"(r) : "r"(a), "r"(b), "r"(c));
  return r;
}
__device__ __forceinline__ uint32_t hneg2(uint32_t a) {
  uint32_t r;
  asm("neg.bf16x2 %0, %1;" : "=r"(r) : "r"(a));
  return r;
}
__device__ __forceinline__ uint4 ldg128(const void* p) {
  uint4 v;
  asm volatile("ld.global.nc" LDQ ".v4.u32 {%0,%1,%2,%3}, [%4];" : "=r"(v.x), "=r"(v.y), "=r"(v.z), "=r"(v.w) : "l"(p));
  return v;
}
__device__ __forceinline__ uint2 ldg64(const void* p) {
  uint2 v;
  asm volatile("ld.global.nc.v2.u32 {%0,%1}, [%2];" : "=r"(v.x), "=r"(v.y) : "l"(p));
  return v;
}
__device__ __forceinline__ void stg128(void* p, uint32_t a, uint32_t b, uint32_t c, uint32_t d) {
  asm volatile("st.global.v4.u32 [%0], {%1,%2,%3,%4};" ::"l"(p), "r"(a), "r"(b), "r"(c), "r"(d) : "memory");
}
__device__ __forceinline__ void sts128(uint32_t a, uint32_t x, uint32_t y, uint32_t z, uint32_t w) {
  asm volatile("st.shared.v4.u32 [%0], {%1,%2,%3,%4};" ::"r"(a), "r"(x), "r"(y), "r"(z), "r"(w) : "memory");
}
__device__ __forceinline__ uint32_t lds32(uint32_t a) {
  uint32_t v;
  asm volatile("ld.shared.u32 %0, [%1];" : "=r"(v) : "r"(a) : "memory");
  return v;
}
__device__ __forceinline__ uint4 lds128(uint32_t a) {
  uint4 v;
  asm volatile("ld.shared.v4.u32 {%0,%1,%2,%3}, [%4];" : "=r"(v.x), "=r"(v.y), "=r"(v.z), "=r"(v.w) : "r"(a) : "memory");
  return v;
}
__device__ __forceinline__ void stsm4(uint32_t a, uint32_t x, uint32_t y, uint32_t z, uint32_t w) {
  asm volatile("stmatrix.sync.aligned.m8n8.x4.shared.b16 [%0], {%1,%2,%3,%4};" ::"r"(a), "r"(x), "r"(y), "r"(z), "r"(w) : "memory");
}
__device__ __forceinline__ void stsm4t(uint32_t a, uint32_t x, uint32_t y, uint32_t z, uint32_t w) {
  asm volatile("stmatrix.sync.aligned.m8n8.x4.trans.shared.b16 [%0], {%1,%2,%3,%4};" ::"r"(a), "r"(x), "r"(y), "r"(z), "r"(w) : "memory");
}
__device__ __forceinline__ uint4 ldsm4t(uint32_t a) {
  uint4 v;
  asm volatile("ldmatrix.sync.aligned.m8n8.x4.trans.shared.b16 {%0,%1,%2,%3}, [%4];" : "=r"(v.x), "=r"(v.y), "=r"(v.z), "=r"(v.w) : "r"(a) : "memory");
  return v;
}
struct cx { float r, i; };
__device__ __forceinline__ cx cmul(cx a, cx b) { return {a.r * b.r - a.i * b.i, a.r * b.i + a.i * b.r}; }
__device__ __forceinline__ cx cfma(cx a, cx b, cx c) { return {fmaf(a.r, b.r, fmaf(-a.i, b.i, c.r)), fmaf(a.r, b.i, fmaf(a.i, b.r, c.i))}; }
__device__ __forceinline__ cx csq(cx a) { return {a.r * a.r - a.i * a.i, 2.f * a.r * a.i}; }
__device__ __forceinline__ cx unit(int num, int den) {
  int m = num & (den - 1);
  if (m >= den / 2) m -= den;
  float s, c;
  __sincosf((float)m * (-6.283185307179586f / (float)den), &s, &c);
  return {c, s};
}

__device__ __forceinline__ uint2 lds64(uint32_t a) {
  uint2 v;
  asm volatile("ld.shared.v2.u32 {%0,%1}, [%2];" : "=r"(v.x), "=r"(v.y) : "r"(a) : "memory");
  return v;
}
template <int PG>
__device__ __forceinline__ void prep(const Ptrs& p, int ti, int pj, int w, int lane) {
  const int tb = lane & 7, chunk = 2 * w + (lane >> 4), ch = chunk * 8 + ((lane >> 3) & 1) * 4;
  uint32_t s[2][4];
#pragma unroll
  for (int e = 0; e < 2; e++) {
    const uint4 sh = ldg128(p.shift + (pj * 128 + PG * 64 + ch) * 4 + e * 8);
    s[e][0] = __byte_perm(sh.x, sh.z, 0x5410); s[e][1] = __byte_perm(sh.x, sh.z, 0x7632);
    s[e][2] = __byte_perm(sh.y, sh.w, 0x5410); s[e][3] = __byte_perm(sh.y, sh.w, 0x7632);
  }
#pragma unroll 1
  for (int th = 0; th < 2; th++) {
    const uint32_t in = S_STG + th * 16384 + (lane & 8);
    const uint32_t a0 = in + tb * 128 + ((chunk ^ tb) << 4);
    const uint32_t hb = tb ? in + (39 + tb) * 128 + ((chunk ^ (tb - 1)) << 4) : S_T + (PG * 2 + th) * 512 + ch * 2;
    const uint32_t hs = tb ? 1024 : 128;
    uint2 kk[11], vv[8];
    mbar_wait_long(B_PIN + 16 * PG + 8 * th, 0);
    if (th) TIM(29 + PG);
#pragma unroll
    for (int i = 0; i < 3; i++) kk[i] = lds64(hb + i * hs);
#pragma unroll
    for (int i = 0; i < 8; i++) { kk[3 + i] = lds64(a0 + i * 1024); vv[i] = lds64(a0 + 8192 + i * 1024); }
#pragma unroll
    for (int i = 0; i < 8; i++)
#pragma unroll
      for (int e = 0; e < 2; e++) {
        uint32_t a = hmul2((&kk[i].x)[e], s[e][3]);
        a = hfma2((&kk[i + 1].x)[e], s[e][2], a);
        a = hfma2((&kk[i + 2].x)[e], s[e][1], a);
        a = hfma2((&kk[i + 3].x)[e], s[e][0], a);
        (&vv[i].x)[e] = hmul2(a, (&vv[i].x)[e]);
      }
    if (PG) bar_sync(12, 128); else bar_arrive(th ? 14 : 3, 160);
    const uint32_t dst = (PG ? S_STG + 8192 + th * 16384 : S_CIN + th * 8192) + ch * 128 + (tb ^ th) * 16;
#pragma unroll
    for (int e = 0; e < 2; e++) {
#define U(i) (&vv[i].x)[e]
      sts128(dst + (2 * e) * 128, __byte_perm(U(0), U(1), 0x5410), __byte_perm(U(2), U(3), 0x5410),
             __byte_perm(U(4), U(5), 0x5410), __byte_perm(U(6), U(7), 0x5410));
      sts128(dst + (2 * e + 1) * 128, __byte_perm(U(0), U(1), 0x7632), __byte_perm(U(2), U(3), 0x7632),
             __byte_perm(U(4), U(5), 0x7632), __byte_perm(U(6), U(7), 0x7632));
#undef U
    }
    bar_arrive(PG ? 9 + th : 4 + 7 * th, 160);
  }
}

__device__ __forceinline__ void conv_tables(int tid) {
  {
    const int s = tid >> 5, n1 = tid & 31;
    uint32_t re[4], im[4];
#pragma unroll
    for (int e = 0; e < 4; e++) {
      cx a = unit(n1 * (4 * (8 * s + 2 * e) + 1), 128), b = unit(n1 * (4 * (8 * s + 2 * e + 1) + 1), 128);
      re[e] = pack2(a.r * 0.125f, b.r * 0.125f); im[e] = pack2(a.i * 0.125f, b.i * 0.125f);
    }
    sts128(S_M1 + (2 * s) * 512 + n1 * 16, re[0], re[1], re[2], re[3]);
    sts128(S_M1 + (2 * s + 1) * 512 + n1 * 16, im[0], im[1], im[2], im[3]);
  }
  {
    const int kg = tid >> 5, n = tid & 31;
    const int pi = kg >> 1, po = n >> 4, f2 = n & 15;
    uint32_t fw[4];
#pragma unroll
    for (int e = 0; e < 4; e++) {
      int n2 = (kg & 1) * 8 + 2 * e;
      cx a = unit(n2 * f2, 16), b = unit((n2 + 1) * f2, 16);
      float sg = pi ? -1.f : 1.f;
      float x0 = (pi == po) ? a.r : sg * a.i, x1 = (pi == po) ? b.r : sg * b.i;
      fw[e] = pack2(x0, x1);
    }
    sts128(S_M2 + kg * 512 + n * 16, fw[0], fw[1], fw[2], fw[3]);
  }
  fence_async_smem();
}
__device__ __forceinline__ constexpr int jj_of(int o) { return o == 7 ? 3 : o + (o >= 3); }
__device__ __forceinline__ int conv_chan(int ti, int pj, int jj) { return pj * 128 + jj * 16 + ti; }

struct ConvCtx {
  uint32_t buf, inbar;
  int nb, n;
  int ti, pj, j;
  __device__ __forceinline__ int chan(int c) const {
    return j < 0 ? conv_chan(ti, pj, c + (c >= 3)) : conv_chan((j + 12 * c) >> 3, (j + 12 * c) & 7, 3);
  }
};
__device__ __forceinline__ ConvCtx conv_ctx(int spare, int wg, int ti, int pj) {
  const int j = spare < 0 ? -1 : spare * 3 + wg;
  return {wg == 2 ? S_CIN : sb + wg * 32768, wg == 2 ? B_CINF : (wg ? B_PIN : B_FULL), 4 + 4 * wg, j < 0 ? 7 : (j < 8 ? 11 : 10), ti, pj, j};
}
#define CDESC(a) mkdesc(dlo(a, 512), 128, 0)
struct ConvTw { uint32_t r[2], i[2], n[2]; };

__device__ __forceinline__ void cv_tw1(float (&d)[64], uint32_t (&R)[16], uint32_t (&I)[16], const ConvTw& t, int i) {
#pragma unroll
  for (int j = 8 * (i & 1); j < 8 * (i & 1) + 8; j++) {
    if (i < 2) {
      R[j] = pack2(d[4 * j], d[4 * j + 1]); I[j] = pack2(d[4 * j + 2], d[4 * j + 3]);
    } else {
      const uint32_t xr = R[j], xi = I[j];
      R[j] = hfma2(xr, t.r[j & 1], hmul2(xi, t.n[j & 1]));
      I[j] = hfma2(xr, t.i[j & 1], hmul2(xi, t.r[j & 1]));
    }
  }
}
template <int N>
__device__ __forceinline__ void cv_pack(float (&X)[16], uint32_t (&P)[N][2][2], int q) {
#pragma unroll
  for (int k = 0; k < 2; k++)
#pragma unroll
    for (int j = 0; j < 4; j++) P[2 * q + k][j >> 1][j & 1] = pack2(X[4 * j + 2 * k], X[4 * j + 2 * k + 1]);
}
__device__ __forceinline__ void cv_overlap(uint32_t (&P)[8][2][2]) {
#pragma unroll
  for (int k = 3; k > 0; k--)
#pragma unroll
    for (int hh = 0; hh < 2; hh++) {
      P[k][0][hh] = hsub2(P[k][0][hh], P[k - 1][1][hh]);
      P[k][1][hh] = hadd2(P[k][1][hh], P[k - 1][0][hh]);
    }
}
__device__ __forceinline__ void cv_pw(uint32_t (&P)[8][2][2], uint32_t (&Q)[4][2][2]) {
#pragma unroll
  for (int jh = 0; jh < 8; jh++) {
    const int j = jh >> 1, hh = jh & 1;
    uint32_t qr = hmul2(P[4 + j][0][hh], P[0][0][hh]), qi = hmul2(P[4 + j][0][hh], P[0][1][hh]);
    qr = hfma2(hneg2(P[4 + j][1][hh]), P[0][1][hh], qr);
    qi = hfma2(P[4 + j][1][hh], P[0][0][hh], qi);
#pragma unroll
    for (int k = j - 1; k >= 0; k--) {
      qr = hfma2(P[4 + k][0][hh], P[j - k][0][hh], qr);
      qi = hfma2(P[4 + k][0][hh], P[j - k][1][hh], qi);
      qr = hfma2(hneg2(P[4 + k][1][hh]), P[j - k][1][hh], qr);
      qi = hfma2(P[4 + k][1][hh], P[j - k][0][hh], qi);
    }
    Q[j][0][hh] = qr; Q[j][1][hh] = qi;
  }
}
__device__ __forceinline__ void cv_tw2(uint32_t (&Q)[4][2][2], const ConvTw& t, int k) {
#pragma unroll
  for (int hh = 0; hh < 2; hh++) {
    const uint32_t xr = Q[k][0][hh], xi = Q[k][1][hh];
    Q[k][0][hh] = hfma2(xr, t.r[hh], hmul2(xi, t.i[hh]));
    Q[k][1][hh] = hfma2(xr, t.n[hh], hmul2(xi, t.r[hh]));
  }
}
__device__ __forceinline__ void cv_out0(float (&Y)[16], uint32_t T, int w, int lane) {
  reg_fence(Y);
  const uint32_t za = T + w * 2048 + (lane >> 4) * 256 + (lane & 7) * 32 + ((lane >> 3) & 1) * 16;
#pragma unroll
  for (int jj = 0; jj < 2; jj++)
    stsm4t(za + jj * 512, pack2(Y[8 * jj], Y[8 * jj + 1]), pack2(Y[8 * jj + 2], Y[8 * jj + 3]),
           pack2(Y[8 * jj + 4], Y[8 * jj + 5]), pack2(Y[8 * jj + 6], Y[8 * jj + 7]));
}

template <bool FW, bool BW, int K>
__device__ __forceinline__ void conv_step(uint32_t (&Q)[4][2][2], const ConvTw& t, const ConvCtx& cc, float dl, int ch, int w, int lane) {
#define SF(n) if ((SFM >> (n)) & 1) sched_fence_async<K + (n)>()
  float d[64], X[4][16], Z[2][16], Y[16];
  uint32_t R[16], I[16];
  uint4 a[4];
  const int nx = ch + 1;
  const uint32_t T = cc.buf + 16384;
  float dv;
  TIMC(1);
  if (FW) {
    dv = __shfl_sync(~0u, dl, nx);
    mbar_wait(cc.inbar + 8 * (nx & 1), (nx >> 1) & 1);
  }
  TIMC(2);
  WG_FENCE();
  if (BW) {
#pragma unroll
    for (int q = 0; q < 2; q++) {
      wgmma_rs32<0, 1>(Z[q], Q[2 * q][0][0], Q[2 * q + 1][0][0], Q[2 * q][0][1], Q[2 * q + 1][0][1], mkdesc(dlo(S_M2, 128), 512, 0));
      wgmma_rs32<1, 1>(Z[q], Q[2 * q][1][0], Q[2 * q + 1][1][0], Q[2 * q][1][1], Q[2 * q + 1][1][1], mkdesc(dlo(S_M2 + 256, 128), 512, 0));
    }
    WG_COMMIT();
  }
  if (FW) {
    const uint32_t lo = dlo(0, 1024) + (cc.buf >> 4) + (nx & 1) * 512;
    wgmma_ss128<1, 1, 0>(d, mkdesc(dlo(S_M1, 128), 512, 0), mkdesc(lo, 256, 3));
    wgmma_ss128<1, 1, 1>(d, mkdesc(dlo(S_M1 + 256, 128), 512, 0), mkdesc(lo + 32, 256, 3));
    WG_COMMIT();
  }
  TIMC(3);
  if (BW) {
    TIMC(4);
    WG_WAIT(FW ? 1 : 0);
    TIMC(5);
    reg_fence(Z[0]); reg_fence(Z[1]);
    uint32_t V[4][2][2];
    cv_pack(Z[0], V, 0); cv_pack(Z[1], V, 1);
    SF(0);
#pragma unroll
    for (int k = 0; k < 4; k++) cv_tw2(V, t, k);
    sched_fence_async<K + 6>();
    bar_sync(cc.nb + 3, 160);
#pragma unroll
    for (int k = 0; k < 4; k++) stsm4(T + w * 512 + lane * 16 + k * 2048, V[k][0][0], V[k][0][1], V[k][1][0], V[k][1][1]);
    SF(1);
    TIMC(6);
  }
  if (FW) {
    WG_WAIT(0);
    reg_fence(d);
    if (nx + 2 < cc.n) bar_arrive(cc.nb + 2, 160);
    cv_tw1(d, R, I, t, 0); cv_tw1(d, R, I, t, 1);
    SF(2);
    TIMC(7);
  }
  if (BW) {
    bar_sync(cc.nb, 128);
#pragma unroll
    for (int s = 0; s < 4; s++) a[s] = ldsm4t(T + (4 * w + s) * 512 + lane * 16);
  }
  if (FW) { cv_tw1(d, R, I, t, 2); cv_tw1(d, R, I, t, 3); }
  sched_fence<K + 3>();
  TIMC(8);
  WG_FENCE();
  if (BW) {
    wgmma_rs32<0>(Y, a[0].x, a[0].y, a[0].z, a[0].w, CDESC(S_M1));
#pragma unroll
    for (int i = 1; i < 4; i++) wgmma_rs32<1>(Y, a[i].x, a[i].y, a[i].z, a[i].w, CDESC(S_M1 + 1024 * i));
  }
  if (FW) {
#pragma unroll
    for (int q = 0; q < 4; q++) {
      if (q == 2) WG_COMMIT();
      wgmma_rs32<0>(X[q], R[4 * q], R[4 * q + 2], R[4 * q + 1], R[4 * q + 3], CDESC(S_M2));
      wgmma_rs32<1>(X[q], I[4 * q], I[4 * q + 2], I[4 * q + 1], I[4 * q + 3], CDESC(S_M2 + 1024));
    }
  }
  WG_COMMIT();
  TIMC(9);
  WG_WAIT(FW ? 1 : 0);
  TIMC(10);
  if (BW) { cv_out0(Y, T, w, lane); bar_arrive(cc.nb + 1, 160); }
  if (FW) {
    uint32_t P[8][2][2];
    reg_fence(X[0]); reg_fence(X[1]);
    cv_pack(X[0], P, 0); cv_pack(X[1], P, 1);
    cv_overlap(P);
    sched_fence_async<K + 7>();
    WG_WAIT(0);
    reg_fence(X[2]); reg_fence(X[3]);
    X[2][0] += dv; X[2][1] += dv; X[2][4] += dv; X[2][5] += dv;
    cv_pack(X[2], P, 2); cv_pack(X[3], P, 3);
    SF(4);
    TIMC(11);
    cv_pw(P, Q);
  }
  sched_fence<K + 5>();
  TIMC(13);
#undef SF
}

__device__ __forceinline__ void conv_main(const Ptrs& p, const ConvCtx& cc, int tid) {
  const int ti = cc.ti, pj = cc.pj;
  const int w = tid >> 5, lane = tid & 31;
  ConvTw t;
#pragma unroll
  for (int hh = 0; hh < 2; hh++) {
    const int n2 = 8 * hh + 2 * (lane & 3), m = 4 * (8 * w + (lane >> 2)) + 1;
    cx a = unit(n2 * m, 2048), b = unit((n2 + 1) * m, 2048);
    t.r[hh] = pack2(a.r, b.r); t.i[hh] = pack2(a.i, b.i); t.n[hh] = pack2(-a.i, -b.i);
  }
  const float dl = 0.125f * __bfloat162float(p.ssmd[cc.chan(min(lane, cc.n - 1))]);
  if (cc.j < 0) prep<1>(p, ti, pj, w, lane);
  {
    uint32_t P[4][2][2];
    mbar_wait_long(cc.inbar, 0);
    TIM(20);
    conv_step<true, false, 10>(P, t, cc, dl, -1, w, lane);
#pragma unroll 1
    for (int ch = 0; ch < cc.n - 1; ch++) {
      conv_step<true, true, 20>(P, t, cc, dl, ch, w, lane);
      if (ch == 0) TIM(21);
    }
    conv_step<false, true, 30>(P, t, cc, dl, cc.n - 1, w, lane);
  }
  TIM(22);
}

__device__ __forceinline__ cx csel(bool k, cx a, cx b) { return {k ? a.r : b.r, k ? a.i : b.i}; }
__device__ __forceinline__ void ld2cx(uint32_t a, cx& x, cx& y) {
  const uint4 v = lds128(a);
  x = {__uint_as_float(v.x), __uint_as_float(v.y)};
  y = {__uint_as_float(v.z), __uint_as_float(v.w)};
}
__device__ __forceinline__ cx ldcx(uint32_t a) {
  cx x;
  asm volatile("ld.shared.v2.f32 {%0,%1}, [%2];" : "=f"(x.r), "=f"(x.i) : "r"(a) : "memory");
  return x;
}

__device__ __forceinline__ void scan_epilogue(float (&aR)[64], float (&aI)[64], uint32_t last_empty, int ph, int ti, int pj, int tid) {
  const int w = tid >> 5, lane = tid & 31, r = lane >> 2, c = lane & 3;
  const uint32_t par = S_PAR + (ph * 64 + 16 * w + r) * 16;
  uint4* agg = g_agg + ph * 16 * 256 + pj * 32 + 8 * w + r;
  const uint32_t tag = (lds32(S_EP) + 1) & 3;
  {
    cx lam[2], cf[2], l32[2], h[2];
#pragma unroll
    for (int q = 0; q < 2; q++) { ld2cx(par + q * 128, lam[q], cf[q]); l32[q] = ldcx(par + 2048 + q * 128); }
    WG_WAIT(0);
    if (elect_one()) mbar_arrive(last_empty);
    asm volatile("setmaxnreg.inc.sync.aligned.u32 168;");
    reg_fence(aR); reg_fence(aI);
    TIM(3 + ph * 2);
#pragma unroll
    for (int q = 0; q < 2; q++) h[q] = {aR[2 * q], -aI[2 * q]};
#pragma unroll
    for (int s = 1; s < 32; s++)
#pragma unroll
      for (int q = 0; q < 2; q++) {
        const int i = 4 * (s >> 1) + 2 * q + (s & 1);
        h[q] = cfma(lam[q], h[q], {aR[i], -aI[i]});
      }
    sched_fence<1>();
    cx t[2][3];
#pragma unroll
    for (int q = 0; q < 2; q++)
#pragma unroll
      for (int k = 0; k < 3; k++) t[q][k] = {__shfl_up_sync(~0u, h[q].r, k + 1, 4), __shfl_up_sync(~0u, h[q].i, k + 1, 4)};
#pragma unroll
    for (int q = 0; q < 2; q++) {
      const cx z = {0.f, 0.f};
      cx ex = cfma(l32[q], csel(c >= 3, t[q][2], z), csel(c >= 2, t[q][1], z));
      ex = cfma(l32[q], ex, csel(c >= 1, t[q][0], z));
      h[q] = cmul(cf[q], cfma(l32[q], ex, h[q]));
      const cx u = cfma(lam[q], ex, {aR[2 * q], -aI[2 * q]});
      aR[2 * q] = u.r; aI[2 * q] = -u.i;
    }
    if (c == 3)
      asm volatile("st.relaxed.gpu.global.v4.u32 [%0], {%1,%2,%3,%4};" ::"l"(agg + ti * 256),
                   "r"((__float_as_uint(h[0].r) & ~3u) | tag), "r"((__float_as_uint(h[0].i) & ~3u) | tag),
                   "r"((__float_as_uint(h[1].r) & ~3u) | tag), "r"((__float_as_uint(h[1].i) & ~3u) | tag) : "memory");
    TIM(8 + ph * 4);
    sched_fence<2>();
#pragma unroll
    for (int i = 0; i < 64; i++) {
      const cx u = cmul(cf[(i >> 1) & 1], {aR[i], -aI[i]});
      aR[i] = u.r; aI[i] = u.i;
    }
    reg_fence(aR); reg_fence(aI);
    sched_fence<3>();
  }
  TIM(27 + ph);
  cx h[2] = {{0.f, 0.f}, {0.f, 0.f}};
  if (ti > 0) {
    const uint2* ap = (const uint2*)(agg + (ti - 1 - (c >> 1)) * 256) + (c & 1);
    const int cnt = ti - (c >> 1);
    const cx l128 = ldcx(par + 2048 + 8 + (c & 1) * 128);
    uint2 v[8];
    int n = SPIN_LIMIT;
    bool bad;
    do {
      uint32_t x = 0;
#pragma unroll
      for (int j = 0; j < 8; j++) {
        v[j] = make_uint2(tag, tag);
        asm volatile("{.reg .pred p; setp.lt.s32 p, %3, %4; @p ld.relaxed.gpu.global.v2.u32 {%0,%1}, [%2];}"
                     : "+r"(v[j].x), "+r"(v[j].y) : "l"(ap - j * 1024), "r"(2 * j), "r"(cnt) : "memory");
      }
#pragma unroll
      for (int j = 0; j < 8; j++) x |= (v[j].x ^ tag) | (v[j].y ^ tag);
      bad = __any_sync(~0u, x & 3);
    } while (bad && --n);
    trap_if(n == 0);
    const cx l256 = csq(l128);
    cx a = {__uint_as_float(v[7].x), __uint_as_float(v[7].y)};
#pragma unroll
    for (int j = 6; j >= 0; j--) a = cfma(l256, a, {__uint_as_float(v[j].x), __uint_as_float(v[j].y)});
    if (c & 2) a = cmul(a, l128);
    const cx l32a = ldcx(par + 2048), l32b = ldcx(par + 2048 + 128);
    const cx t1 = {__shfl_xor_sync(~0u, a.r, 1), __shfl_xor_sync(~0u, a.i, 1)};
    const cx t2 = {__shfl_xor_sync(~0u, a.r, 2), __shfl_xor_sync(~0u, a.i, 2)};
    const cx t3 = {__shfl_xor_sync(~0u, a.r, 3), __shfl_xor_sync(~0u, a.i, 3)};
    const cx own = {a.r + t2.r, a.i + t2.i}, oth = {t1.r + t3.r, t1.i + t3.i};
#pragma unroll
    for (int q = 0; q < 2; q++) {
      const cx l32 = q ? l32b : l32a;
      cx x = csel((c & 1) == q, own, oth);
      if (c & 1) x = cmul(x, l32);
      if (c & 2) x = cmul(x, csq(l32));
      h[q] = x;
    }
  }
  TIM(9 + ph * 4);
  const cx lam[2] = {ldcx(par), ldcx(par + 128)};
  mbar_wait(B_SFREE + 8 * ph, 0);
  const uint32_t hs = S_STG + w * 1024 + r * 64 + ((c ^ (r >> 1)) << 4);
  uint32_t pi[4][2][4];
#pragma unroll
  for (int i = 0; i < 4; i++) {
    uint32_t pr[2][4];
#pragma unroll
    for (int s2 = 0; s2 < 4; s2++)
#pragma unroll
      for (int q = 0; q < 2; q++) {
        const int k = 4 * (4 * i + s2) + 2 * q;
        cx h0 = cfma(lam[q], h[q], {aR[k], aI[k]});
        h[q] = cfma(lam[q], h0, {aR[k + 1], aI[k + 1]});
        pr[q][s2] = pack2(h0.r, h[q].r);
        pi[i][q][s2] = pack2(h0.i, h[q].i);
      }
#pragma unroll
    for (int q = 0; q < 2; q++) sts128(hs + i * 4096 + q * 512, pr[q][0], pr[q][1], pr[q][2], pr[q][3]);
    if (i & 1) {
      bar_arrive(9 + (i >> 1), 160);
      if (i == 1) sched_fence<8>(); else sched_fence<9>();
    }
  }
  TIM(10 + ph * 4);
#pragma unroll
  for (int i = 0; i < 4; i++)
#pragma unroll
    for (int q = 0; q < 2; q++) sts128(hs + 16384 + i * 4096 + q * 512, pi[i][q][0], pi[i][q][1], pi[i][q][2], pi[i][q][3]);
  bar_arrive(11, 160);
  bar_sync(1 + ph, 128);
  asm volatile("setmaxnreg.dec.sync.aligned.u32 160;");
}

__device__ __forceinline__ constexpr uint32_t e_addr(int o, int mh) { return S_STG + ((o < 4 ? o : o ^ 2) * 2 + mh) * 2048; }
__device__ __forceinline__ void eterm(const Ptrs& p, int ti, int pj, int tid, uint32_t tag) {
  const int w = tid >> 5, lane = tid & 31, r = lane >> 2, c = lane & 3;
  const int trow = 64 * (w & 1) + 8 * (w >> 1) + r;
  const int rs = 2 * (r & 3) + (r >> 2);
  uint2 xv[2][8][2], ds[8];
  {
    uint2 gw[8];
#pragma unroll
    for (int jj = 0; jj < 8; jj++) {
      gw[jj] = ldg64(p.gw + pj * 128 + 16 * jj + 4 * c);
      ds[jj] = ldg64(p.dskip + pj * 128 + 16 * jj + 4 * c);
    }
    float s[4] = {0.f, 0.f, 0.f, 0.f};
#pragma unroll
    for (int g = 0; g < 2; g++) {
      mbar_wait_long(B_XT + 8 * g, 0);
#pragma unroll
      for (int i = 0; i < 4; i++)
#pragma unroll
        for (int j2 = 0; j2 < 2; j2++) {
          uint32_t q;
#pragma unroll
          for (int jj = 4 * g + 2 * j2; jj < 4 * g + 2 * j2 + 2; jj++) {
            uint2& x = xv[i >> 1][jj][i & 1];
            x = lds64(S_STG + g * 16384 + (trow - r + rs + 16 * (i >> 1) + 32 * (i & 1)) * 128 + (((2 * (jj & 3) + (c >> 1)) ^ rs) << 4) + (c & 1) * 8);
            q = hfma2(x.x, gw[jj].x, (jj & 1) ? hfma2(x.y, gw[jj].y, q) : hmul2(x.y, gw[jj].y));
          }
          s[i] += bf_lo(q) + bf_hi(q);
        }
    }
    bar_arrive(9, 160);
    float u0 = (c & 1) ? s[1] : s[0], v0 = (c & 1) ? s[0] : s[1];
    float u1 = (c & 1) ? s[3] : s[2], v1 = (c & 1) ? s[2] : s[3];
    u0 += __shfl_xor_sync(~0u, v0, 1);
    u1 += __shfl_xor_sync(~0u, v1, 1);
    float u = (c & 2) ? u1 : u0;
    u += __shfl_xor_sync(~0u, (c & 2) ? u0 : u1, 2);
    asm volatile("st.relaxed.gpu.global.u32 [%0], %1;" ::"l"(g_gate + pj * SEQ + ti * 128 + trow + 16 * (c >> 1) + 32 * (c & 1)),
                 "r"((__float_as_uint(u) & ~3u) | tag) : "memory");
  }
  {
    float l;
    int n = 0;
    while (true) {
      __nanosleep(n ? 60 : 250);
      uint32_t v[8], bad = 0;
#pragma unroll
      for (int j = 0; j < 8; j++) v[j] = ld_relaxed(g_gate + j * SEQ + ti * 128 + tid) ^ tag;
      l = 0.f;
#pragma unroll
      for (int j = 0; j < 8; j++) { bad |= v[j]; l += __uint_as_float(v[j]); }
      if (!__any_sync(~0u, bad & 3)) break;
      trap_if(++n >= SPIN_LIMIT);
    }
    const float g = bf_round(1.f / (1.f + __expf(-bf_round(l))));
    asm volatile("st.shared.f32 [%0], %1;" ::"r"(S_G + tid * 4), "f"(g) : "memory");
  }
  bar_sync(2, 128);
  TIM(31);
  uint32_t g2[2][2], og2[2][2];
#pragma unroll
  for (int mh = 0; mh < 2; mh++)
#pragma unroll
    for (int hf = 0; hf < 2; hf++) {
      uint32_t g;
      asm volatile("ld.shared.u32 %0, [%1];" : "=r"(g) : "r"(S_G + (trow + 16 * mh + 32 * hf) * 4) : "memory");
      g2[mh][hf] = __byte_perm(g, g, 0x3232);
      og2[mh][hf] = hsub2(0x3f803f80u, g2[mh][hf]);
    }
  const int dl = lane & 15;
#pragma unroll
  for (int g = 0; g < 3; g++) {
    const int n = g ? 2 : 4, o0 = g ? 2 + 2 * g : 0;
    if (g) bar_sync(2, 128);
    if (g == 2) mbar_wait(B_ZT + 16, 0); else mbar_wait_long(B_ZT + 8 * g, 0);
    if (g == 2) TIM(16);
    const uint32_t za = (g == 2 ? S_CIN : S_STG + 16384) + (w & 1) * n * 2048 + dl * 128;
#pragma unroll
    for (int mh = 0; mh < 2; mh++) {
      const uint32_t zb = za + (((4 * (lane >> 4) + 2 * mh + (w >> 1)) ^ (dl & 7)) << 4);
#pragma unroll
      for (int i = 0; i < n; i++) {
        const int jj = jj_of(o0 + i);
        uint4 z = ldsm4t(zb + i * 2048);
#pragma unroll
        for (int hf = 0; hf < 2; hf++) {
          uint2& x = xv[mh][jj][hf];
          x.x = hmul2(x.x, hfma2(og2[mh][hf], hf ? z.z : z.x, hmul2(g2[mh][hf], ds[jj].x)));
          x.y = hmul2(x.y, hfma2(og2[mh][hf], hf ? z.w : z.y, hmul2(g2[mh][hf], ds[jj].y)));
        }
        sts128(e_addr(o0 + i, mh) + tid * 16, xv[mh][jj][0].x, xv[mh][jj][0].y, xv[mh][jj][1].x, xv[mh][jj][1].y);
      }
    }
    if (g == 0) { bar_arrive(10, 160); TIM(1); }
    if (g == 1) TIM(23);
    bar_arrive(5 + g, 256);
  }
  TIM(17);
}

__device__ __forceinline__ void store_piece(float (&a)[64], float* op, int jj, const uint4& e, float g0, float g1) {
  stg128(op + 16 * jj, __float_as_uint(fmaf(g0, a[8 * jj], bf_lo(e.x))), __float_as_uint(fmaf(g0, a[8 * jj + 1], bf_hi(e.x))),
         __float_as_uint(fmaf(g0, a[8 * jj + 4], bf_lo(e.y))), __float_as_uint(fmaf(g0, a[8 * jj + 5], bf_hi(e.y))));
  stg128(op + 32 * DM + 16 * jj, __float_as_uint(fmaf(g1, a[8 * jj + 2], bf_lo(e.z))), __float_as_uint(fmaf(g1, a[8 * jj + 3], bf_hi(e.z))),
         __float_as_uint(fmaf(g1, a[8 * jj + 6], bf_lo(e.w))), __float_as_uint(fmaf(g1, a[8 * jj + 7], bf_hi(e.w))));
}

__device__ __forceinline__ void ring_acquire(int s, int sl, int par, int grp) {
  mbar_wait(B_EMPTY + 8 * sl, par);
  flag_add(F_GRP + grp);
  const int need = (s - NS - LEAD + 1) * GRP;
  int v, n = 0;
  while (true) {
    asm volatile("ld.volatile.shared.u32 %0, [%1];" : "=r"(v) : "r"(S_MIR) : "memory");
    if (v >= need) break;
    __nanosleep(40);
    trap_if(++n >= SPIN_LIMIT);
  }
}

__device__ __forceinline__ void issue_g1(const Maps& m, int s, int sl, int ti, int pj) {
  const uint32_t bar = B_FULL + 8 * sl, dst = sb + sl * STAGE;
  const int k0 = (s & 15) * 64, ch = (s >> 4) * 512 + pj * 64;
  mbar_expect(bar, STAGE);
  tma4d(dst + 16384, &m.x, bar, k0, 0, 4 * ti, 0);
  tma2d(dst, &m.bre, bar, k0, ch);
  tma2d(dst + 8192, &m.bim, bar, k0, ch);
}
__device__ __forceinline__ void producer(const Maps& m, int b, int ti, int pj) {
#pragma unroll
  for (int s = EARLY; s < NS; s++) issue_g1(m, s, s, ti, pj);
  int sl = 0, par = 0;
#pragma unroll 1
  for (int s = NS; s < 32; s++) {
    ring_acquire(s, sl, par, b / GRP);
    issue_g1(m, s, sl, ti, pj);
    if (++sl == NS) { sl = 0; par ^= 1; }
  }
#pragma unroll 1
  for (int q = 0; q < 32; q++) {
    ring_acquire(q + 32, sl, par, b / GRP);
    const uint32_t bar = B_FULL + 8 * sl, dst = sb + sl * STAGE;
    mbar_expect(bar, STAGE);
    tma5d(dst + 16384, (q & 8) ? &m.cim : &m.cre, bar, (q >> 4) * 512 + (q & 7) * 64, 0, 0, 0, pj * 8);
    if ((q & 7) == 0) {
      mbar_wait(B_FLG + q, 0);
      fence_async_global();
      if ((q & 15) == 0) TIM(24 + (q >> 4));
    }
    bulk_load(dst, g_h + (size_t)(ti * 32 + q) * 1024, 16384, bar);
    if (++sl == NS) { sl = 0; par ^= 1; }
  }
}

__device__ __forceinline__ void poller(int b, int ti, int pj, int lane, unsigned ep) {
  if (lane < 10) {
    const int f = lane == 0 ? F_GRP + b / GRP : (lane < 5 ? F_H + (lane - 1) * 16 + ti : (lane < 7 ? F_U + pj * 2 + lane - 5 : F_Z + pj * 3 + lane - 7));
    const unsigned per = lane == 0 ? GRP * (64 - NS) : (lane < 5 ? 8 : (lane == 9 ? 32 : 16));
    const unsigned base = ep * per;
    int need = lane ? per : GRP * (64 - NS - LEAD);
    int n = SPIN_LIMIT, left = 10;
    do {
      const int v = ld_relaxed(g_flag + f * 32) - base;
      asm volatile("st.volatile.shared.u32 [%0], %1;" ::"r"(S_MIR + 4 * lane), "r"(v) : "memory");
      const unsigned hit = __ballot_sync(0x3ffu, v >= need);
      if (hit) {
        if (v >= need) {
          need = 0x7fffffff;
          if (lane) {
            asm volatile("fence.acquire.gpu;" ::: "memory");
            mbar_arrive(B_FLG - 8 + 8 * lane);
          }
        }
        left -= __popc(hit);
      }
      if (POLL_NS) __nanosleep(POLL_NS);
    } while (left && --n);
    trap_if(n == 0);
  }
}

__device__ __forceinline__ void poller_spare(int b, int lane) {
  const unsigned ep = ld_relaxed(g_epoch + b);
  int n = SPIN_LIMIT;
  while (!__all_sync(~0u, (int)(ld_relaxed(g_flag + (F_U + (lane & 7) * 2) * 32) - (ep + 1) * 16) >= 0) && --n) {}
  trap_if(n == 0);
  asm volatile("fence.acquire.gpu;" ::: "memory");
  __syncwarp();
  if (lane == 0) { mbar_arrive(B_FLG + 32); mbar_arrive(B_FLG + 40); g_epoch[b] = ep + 1; }
}

__device__ __forceinline__ void storer(const Maps& m, int ti, int pj) {
  unsigned t = clock();
#pragma unroll 1
  for (int job = -2; job < 4; job++) {
#pragma unroll 1
    for (int i = 0; i < 4; i++) {
      if (job > 0 && (job & 1)) { if (i == 0) bar_sync(11, 160); }
      else if (!(i & 1)) bar_sync(job == -2 ? (i ? 11 : 4) : 9 + (i >> 1), 160);
      if (!(i & 1)) fence_async_smem();
      const uint32_t src = job >= 0 ? S_STG + (job & 1) * 16384 + i * 4096
                                    : (job == -2 ? S_CIN + i * 4096 : S_STG + 8192 + (i >> 1) * 16384 + (i & 1) * 4096);
      uint4* dst = job < 0 ? g_u + (size_t)((pj * 4 + (job + 2) * 2 + (i & 1)) * 32 + ti * 2 + (i >> 1)) * 256
                           : g_h + (size_t)(ti * 32 + job * 8 + pj) * 1024 + i * 256;
      wait_clock(t);
      t = clock() + ((job == 0 || job == 2) ? PACE0 : PACE);
      if (elect_one()) bulk_store(dst, src, 4096);
    }
    if (elect_one()) {
      bulk_commit();
      bulk_done_signal(job < 0 ? F_U + pj * 2 + job + 2 : F_H + job * 16 + ti);
      if (job == -1 || job == 1) mbar_arrive(B_SFREE + 4 + 4 * job);
      if (job >= 2) {
        mbar_expect(B_XT + 8 * (job & 1), 16384);
        tma4d(S_STG + (job & 1) * 16384, &m.x2, B_XT + 8 * (job & 1), pj * 128 + (job & 1) * 64, 0, 0, ti * 16);
      }
    }
    __syncwarp();
    if (job == 0 || job == 2) TIM(11 + job * 2);
  }
#pragma unroll 1
  for (int g = 0; g < 3; g++) {
    if (g < 2) bar_sync(9 + g, 160);
    if (elect_one()) {
      const int n = g ? 2 : 4, o0 = g ? 2 + 2 * g : 0;
      const uint32_t dst = g == 2 ? S_CIN : S_STG + 16384, bar = B_ZT + 8 * g;
      if (g == 0) mbar_wait_long(B_FLG + 48, 0); else mbar_wait(B_FLG + 48 + 8 * g, 0);
      fence_async_global();
      mbar_expect(bar, n * 4096);
#pragma unroll 1
      for (int i = 0; i < n; i++) {
        tma5d(dst + i * 2048, &m.z, bar, ti * 128, 0, 0, 0, pj * 8 + jj_of(o0 + i));
        tma5d(dst + (n + i) * 2048, &m.z, bar, ti * 128 + 64, 0, 0, 0, pj * 8 + jj_of(o0 + i));
      }
    }
    __syncwarp();
  }
}

__device__ __forceinline__ void conv_loader(const Maps& m, const Ptrs& p, const ConvCtx& cc, int lane, unsigned t_start) {
  const int ti = cc.ti, pj = cc.pj;
  bar_arrive(cc.nb + 3, 160);
  unsigned tt = t_start + KV0_AT;
#pragma unroll 1
  for (int st = cc.j < 0 ? 0 : 4; st < 4; st++) {
    const int d = pj * 128 + (st >> 1) * 64, tb = ti * 16 + (st & 1) * 8;
    const uint32_t bar = B_PIN + 8 * st;
    if (st >= 2) bar_sync(st == 2 ? 3 : 14, 160);
    if (elect_one()) {
      mbar_expect(bar, 16384 + 384);
      if ((int)(clock() - tt) > 0) tt = clock();
#pragma unroll 1
      for (int i = 0; i < 4; i++) {
        wait_clock(tt);
        tt += st == 3 ? KV_GAP1 : (st == 0 ? KV_GAP0 : KV_GAP);
        tma3d(S_STG + (st & 1) * 16384 + i * 4096, (i & 2) ? &m.v : &m.k, bar, d, tb, (i & 1) * 4);
        if (i == 0) tma3d(S_T + st * 512, &m.kh, bar, d, tb - 1, 5);
      }
      if (st >= 2) l2_prefetch(p.f + (size_t)conv_chan(ti, pj, st - 2) * SEQ, 4096);
    }
    tt = __shfl_sync(~0u, tt, 0);
  }
  if (cc.j >= 0 && elect_one()) {
    wait_clock(t_start + SPF_AT);
#pragma unroll 1
    for (int ch = 0; ch < cc.n; ch++) l2_prefetch(p.f + (size_t)cc.chan(ch) * SEQ, 4096);
  }
  __syncwarp();
#pragma unroll 1
  for (int ch = 0; ch < cc.n + 3; ch++) {
    if (ch < cc.n) {
      const int d = cc.chan(ch);
      const uint32_t bar = cc.inbar + 16, dst = cc.buf + (ch & 1) * 8192;
      if (ch > 2) bar_sync(cc.nb + 2, 160);
      if (elect_one()) {
        mbar_expect(bar, 8192);
        if (ch == 0 || ch == 3) {
          mbar_wait_long(B_FLG + (ch ? 40 : 32), 0);
          fence_async_global();
        }
        bulk_load(dst + 4096, p.f + (size_t)d * SEQ, 4096, bar);
        tma3d(dst, &m.u, bar, 0, d & 31, d & ~31);
      }
      __syncwarp();
    }
    if (ch >= 3) {
      const int d = cc.chan(ch - 3);
      bar_sync(cc.nb + 1, 160);
      fence_async_smem();
      if (elect_one()) {
#pragma unroll
        for (int i = 0; i < 4; i++) bulk_store(g_z + (size_t)d * 256 + i * 64, cc.buf + 16384 + i * 2048, 1024);
        bulk_commit();
        bulk_wait_read();
      }
      __syncwarp();
      if (ch < cc.n + 2) bar_arrive(cc.nb + 3, 160);
      if (ch > 3 && cc.j >= 0 && elect_one()) bulk_done_signal<1>(F_Z + (cc.chan(ch - 4) >> 7) * 3 + 2);
      __syncwarp();
    }
    if (ch < cc.n) {
      const uint32_t a = cc.buf + (ch & 1) * 8192 + 4096 + 128 + (lane >> 3) * 256 + (lane & 7) * 16;
      mbar_wait(cc.inbar + 16, ch & 1);
#pragma unroll
      for (int i = 0; i < 2; i++) {
        const uint4 x = lds128(a + i * 2048), y = lds128(a + i * 2048 + 1024);
        __syncwarp();
        sts128((a + i * 2048) ^ 16, x.x, x.y, x.z, x.w);
        sts128((a + i * 2048 + 1024) ^ 16, y.x, y.y, y.z, y.w);
      }
      fence_async_smem();
      __syncwarp();
      if (ch == 1) bar_sync(cc.nb + 2, 160);
      if (elect_one()) mbar_arrive(cc.inbar + 8 * (ch & 1));
      __syncwarp();
    }
    if ((ch == cc.n + 2 || (cc.j < 0 && (ch == 6 || ch == 8))) && elect_one())
      bulk_done_signal<0>(F_Z + (cc.chan(ch - 3) >> 7) * 3 + (ch == cc.n + 2 ? 2 : (ch >> 3)));
    __syncwarp();
  }
}

struct Ring { uint32_t off, par, rel; };
__device__ __forceinline__ void desc_touch(const uint64_t (&c)[12][NS]) {
  uint32_t x = 0;
#pragma unroll
  for (int i = 0; i < 12 * NS; i += 4) x |= (uint32_t)(&c[0][0])[i];
  trap_if((x | (uint32_t)c[11][NS - 1]) == 0);
}
template <int TA, bool TAB>
__device__ __forceinline__ void gemm_steps(float (&a0)[64], float (&a1)[64], Ring& r, int n, const uint64_t (&c)[12][NS], int slot) {
#pragma unroll 1
  do {
    const uint32_t off = r.off, rel = r.rel;
    full_wait(B_FULL + off, r.par, slot);
    r.rel = off;
    r.off += 8;
    if (r.off == 8 * NS) { r.off = 0; r.par ^= 1; }
    WG_FENCE();
#define DESC(i) (*(const uint64_t*)((const char*)c[i] + off))
#pragma unroll
    for (int k = 0; k < 4; k++) {
      const uint64_t db = TAB ? DESC(3 * k) : mkdesc(off * 256 + dlo(sb + 16384 + 32 * k, 16), 1024, 1);
      wgmma_ss128<TA, 0, 1>(a0, TAB ? DESC(3 * k + 1) : mkdesc(off * 256 + dlo(sb + 32 * k, 16), 1024, 1), db);
      wgmma_ss128<TA, 0, 1>(a1, TAB ? DESC(3 * k + 2) : mkdesc(off * 256 + dlo(sb + 8192 + 32 * k, 16), 1024, 1), db);
      if (k == RELK) {
        WG_COMMIT();
        WG_WAIT(1);
        if (elect_one()) mbar_arrive(B_EMPTY + rel);
      }
    }
#undef DESC
    if (RELK < 3) WG_COMMIT();
  } while (--n);
}

__global__ void __launch_bounds__(512, 1) fused_kernel(const __grid_constant__ Maps m, const __grid_constant__ Ptrs p) {
  extern __shared__ __align__(1024) uint8_t smem_raw[];
  int b = blockIdx.x;
  {
    int sm, nsm;
    asm volatile("mov.u32 %0, %%smid;" : "=r"(sm));
    asm volatile("mov.u32 %0, %%nsmid;" : "=r"(nsm));
    const int tp = sm >> 1, q = ((tp - 32) * 37) >> 8;
    const int g = tp < 32 ? tp & 7 : (tp < 60 ? tp - 31 - 7 * q : (tp < 62 ? 8 : 0));
    const int j = tp < 32 ? tp >> 3 : (tp < 60 ? 4 + q : (tp < 62 ? tp - 60 : tp - 58));
    if (nsm == 132) b = g * 16 + j * 2 + (sm & 1);
    b = __shfl_sync(~0u, b, 0);
  }
  const int spare = b - 128;
  const int ti = ((b >> 5) << 2) | (b & 3), pj = (((b >> 4) & 1) << 2) | ((b >> 2) & 3);
  const int wid = __shfl_sync(~0u, threadIdx.x >> 5, 0), wg = wid >> 2, tid = threadIdx.x & 127, lane = threadIdx.x & 31;
  if (wg == 0) TIM(0);
  const unsigned t_start = clock();
  if (wid == 12) {
    if (elect_one()) {
      asm volatile("prefetch.tensormap [%0];" ::"l"(&m.x) : "memory");
      asm volatile("prefetch.tensormap [%0];" ::"l"(&m.bre) : "memory");
      asm volatile("prefetch.tensormap [%0];" ::"l"(&m.bim) : "memory");
#pragma unroll
      for (int i = 0; i < NS; i++) mbar_init(B_FULL + 8 * i, 1);
      fence_async_smem();
#pragma unroll
      for (int s = 0; s < EARLY; s++) if (spare < 0) issue_g1(m, s, s, ti, pj);
    }
  } else if (wid == 13) {
    if (elect_one()) {
      trap_if((uint32_t)__cvta_generic_to_shared(smem_raw) != sb);
      asm volatile("st.shared.u32 [%0], 0;" ::"r"(S_MIR) : "memory");
#pragma unroll
      for (uint32_t bar = B_EMPTY; bar < S_MIR; bar += 8) mbar_init(bar, bar < B_CINF ? 4 : 1);
      fence_async_smem();
    }
  }
  __syncwarp();
  if (wg == 3) {
    asm volatile("setmaxnreg.dec.sync.aligned.u32 %0;" ::"n"(RV == 2 ? 32 : 24));
    bar_sync(1, 128);
    if (spare < 0) {
      if (wid == 13) { bar_arrive(2, 160); bar_arrive(12, 160); }
      bar_arrive(0, 256);
    } else {
      bar_arrive(0, 512);
    }
    if (wid == 13) {
      if (spare < 0) poller(b, ti, pj, lane, ld_relaxed(g_epoch + b));
      else poller_spare(b, lane);
    } else if (wid == 15 || spare >= 0) {
      conv_loader(m, p, conv_ctx(spare, wid == 12 ? 0 : wid - 13, ti, pj), lane, t_start);
    } else if (wid == 12) {
      if (elect_one()) producer(m, b, ti, pj);
    } else {
      storer(m, ti, pj);
    }
  } else if (wg == 2 || spare >= 0) {
    asm volatile("setmaxnreg.inc.sync.aligned.u32 160;");
    if (wg == 2) conv_tables(tid);
    if (spare < 0) bar_sync(12, 160); else bar_sync(0, 512);
    conv_main(p, conv_ctx(spare, wg, ti, pj), tid);
  } else {
    asm volatile("setmaxnreg.inc.sync.aligned.u32 %0;" ::"n"(RV == 3 ? 168 : 160));
    if (wg == 1) {
      const int ch = (tid >> 6) * 512 + pj * 64 + (tid & 63);
      const unsigned ep = ld_relaxed(g_epoch + b);
      const float lr = __bfloat162float(p.lre[ch]), li = __bfloat162float(p.lim[ch]);
      const float dt = bf_round(expf(__bfloat162float(p.ldt[ch])));
      float sn, cs;
      sincosf(dt * li, &sn, &cs);
      const float ex = expf(dt * lr);
      const float ar = ex * cs, ai = ex * sn;
      const float inv = 2.f / (lr * lr + li * li);
      const float cr = ((ar - 1.f) * lr + ai * li) * inv, ci = (ai * lr - (ar - 1.f) * li) * inv;
      sts128(S_PAR + tid * 16, __float_as_uint(ar), __float_as_uint(-ai), __float_as_uint(cr), __float_as_uint(-ci));
      const cx l32 = csq(csq(csq(csq(csq({ar, -ai}))))), l128 = csq(csq(l32));
      sts128(S_PAR + 2048 + tid * 16, __float_as_uint(l32.r), __float_as_uint(l32.i), __float_as_uint(l128.r), __float_as_uint(l128.i));
      if (tid == 0) asm volatile("st.shared.u32 [%0], %1;" ::"r"(S_EP), "r"(ep) : "memory");
      bar_arrive(6, 256);
      bar_sync(2, 160);
      desc_touch(p.dc1);
      prep<0>(p, ti, pj, wid & 3, lane);
    }
    float a0[64], a1[64];
    Ring ring = {8u * wg * (16 % NS), wg * ((16u / NS) & 1), B_DUMMY - B_EMPTY};
    zero(a0); zero(a1);
    reg_fence(a0); reg_fence(a1);
    sched_fence<61>();
    bar_sync(wg * 7, 256);
    TIM(2 + wg * 2);
    if (wg == 0) gemm_steps<0, false>(a0, a1, ring, 15, p.dc1, 0);
    else gemm_steps<0, true>(a0, a1, ring, 15, p.dc1, 4);
    bar_arrive(7 + wg, 256);
    gemm_steps<0, false>(a0, a1, ring, 1, p.dc1, wg * 4 + 3);
    if (wg == 0) bar_sync(6, 256);
    scan_epilogue(a0, a1, B_EMPTY + ring.rel, wg, ti, pj, tid);
    if (wg == 1) {
      eterm(p, ti, pj, tid, (lds32(S_EP) + 1) & 3);
    } else {
      ring = {8 * (32 % NS), (32 / NS) & 1, B_DUMMY - B_EMPTY};
      desc_touch(p.dc2);
      zero(a0); zero(a1);
      reg_fence(a0); reg_fence(a1);
      sched_fence<62>();
      bar_sync(8, 256);
      TIM(6);
      gemm_steps<1, true>(a0, a1, ring, 32 - RES, p.dc2, 0);
#pragma unroll
      for (int i = 0; i < RES; i++) {
        const int sl = (64 - RES + i) % NS;
        full_wait(B_FULL + 8 * sl, ((64 - RES + i) / NS) & 1, 15);
        WG_FENCE();
#pragma unroll
        for (int k = 0; k < 4; k++) wgmma_ss128<1, 0, 1>(a0, p.dc2[3 * k + 1][sl], p.dc2[3 * k][sl]);
        WG_COMMIT();
        if (i == 0 && RES == NS) { WG_WAIT(1); if (elect_one()) mbar_arrive(B_EMPTY + ring.rel); }
      }
      const int w = tid >> 5, trow = 16 * 0 + 64 * (w & 1) + 8 * (w >> 1) + (lane >> 2);
      float* op = p.out + (size_t)(ti * 128 + trow) * DM + pj * 128 + 4 * (lane & 3);
      float g[4];
      uint4 e;
#pragma unroll
      for (int i = 0; i < RES; i++) {
        const int sl = (64 - RES + i) % NS;
        if (i == 0) WG_FENCE();
#pragma unroll
        for (int k = 0; k < 4; k++) wgmma_ss128<1, 0, 1>(a1, p.dc2[3 * k + 2][sl], p.dc2[3 * k][sl]);
        WG_COMMIT();
        if (i == 0) {
          bar_sync(5, 256);
#pragma unroll
          for (int q = 0; q < 4; q++) g[q] = __uint_as_float(lds32(S_G + (trow + 16 * (q >> 1) + 32 * (q & 1)) * 4));
          e = lds128(e_addr(0, 0) + tid * 16);
          WG_WAIT(1);
          reg_fence(a0);
        }
        if (i < 4) {
          const uint4 e0 = e;
          e = lds128(e_addr((i + 1) & 3, i == 3) + tid * 16);
          store_piece(a0, op, jj_of(i), e0, g[0], g[1]);
        }
        if (i == 0) sched_fence_async<70>(); if (i == 1) sched_fence_async<71>(); if (i == 2) sched_fence_async<72>(); if (i == 3) sched_fence_async<73>();
      }
      TIM(26);
      WG_WAIT(0);
      reg_fence(a1);
      TIM(7);
#pragma unroll
      for (int o = 0; o < 8; o++) {
        if (o == 4 || o == 6) bar_sync(4 + (o >> 1), 256);
        if (o >= 4) store_piece(a0, op, jj_of(o), lds128(e_addr(o, 0) + tid * 16), g[0], g[1]);
        store_piece(a1, op + 16 * DM, jj_of(o), o ? lds128(e_addr(o, 1) + tid * 16) : e, g[2], g[3]);
      }
      if (tid == 0) g_epoch[b] = lds32(S_EP) + 1;
      TIM(19);
    }
  }
}

typedef CUresult (*EncFn)(CUtensorMap*, CUtensorMapDataType, cuuint32_t, void*, const cuuint64_t*, const cuuint64_t*,
                          const cuuint32_t*, const cuuint32_t*, CUtensorMapInterleave, CUtensorMapSwizzle,
                          CUtensorMapL2promotion, CUtensorMapFloatOOBfill);

void encode(EncFn enc, CUtensorMap* m, const void* ptr, int rank, const cuuint64_t* dims, const cuuint64_t* strides,
            const cuuint32_t* box, CUtensorMapSwizzle sw) {
  cuuint32_t es[5] = {1, 1, 1, 1, 1};
  enc(m, CU_TENSOR_MAP_DATA_TYPE_BFLOAT16, rank, const_cast<void*>(ptr), dims, strides, box, es, CU_TENSOR_MAP_INTERLEAVE_NONE,
      sw, PROMO, CU_TENSOR_MAP_FLOAT_OOB_FILL_NONE);
}

}

extern "C" void kernel_launch(void* const* d_in, const int* in_sizes, int n_in, void* d_out, int out_size) {
  typedef const __nv_bfloat16* bp;
  Ptrs p;
  p.x = (bp)d_in[0]; p.lre = (bp)d_in[1]; p.lim = (bp)d_in[2]; p.bre = (bp)d_in[3]; p.bim = (bp)d_in[4];
  p.cre = (bp)d_in[5]; p.cim = (bp)d_in[6]; p.ldt = (bp)d_in[7]; p.dskip = (bp)d_in[8];
  p.k = (bp)d_in[10]; p.v = (bp)d_in[11]; p.shift = (bp)d_in[12]; p.f = (bp)d_in[13]; p.ssmd = (bp)d_in[14];
  p.gw = (bp)d_in[15]; p.out = (float*)d_out;

  for (int sl = 0; sl < NS; sl++)
    for (int k = 0; k < 4; k++) {
      const uint64_t h128 = (uint64_t)(64u | (1u << 30)) << 32, h64 = (uint64_t)(32u | (2u << 30)) << 32;
      const uint32_t st = sb + sl * STAGE;
      p.dc1[3 * k][sl] = p.dc2[3 * k][sl] = h128 | dlo(st + 16384 + 32 * k, 16);
      p.dc1[3 * k + 1][sl] = h128 | dlo(st + 32 * k, 16);
      p.dc1[3 * k + 2][sl] = h128 | dlo(st + 8192 + 32 * k, 16);
      p.dc2[3 * k + 1][sl] = h64 | dlo(st + 1024 * k, 4096);
      p.dc2[3 * k + 2][sl] = h64 | dlo(st + 8192 + 1024 * k, 4096);
    }
  EncFn enc = nullptr;
  cudaDriverEntryPointQueryResult qr;
  cudaGetDriverEntryPoint("cuTensorMapEncodeTiled", (void**)&enc, cudaEnableDefault, &qr);
  void *zptr = nullptr, *uptr = nullptr;
  cudaGetSymbolAddress(&zptr, g_z);
  cudaGetSymbolAddress(&uptr, g_u);

  Maps m;
  {
    cuuint64_t d[4] = {1024, 2, 64, 16}, s[3] = {2048, 65536, 4096};
    cuuint32_t bx[4] = {64, 2, 4, 16};
    encode(enc, &m.x, p.x, 4, d, s, bx, CU_TENSOR_MAP_SWIZZLE_128B);
  }
  {
    cuuint64_t d[2] = {1024, 1024}, s[1] = {2048};
    cuuint32_t bx[2] = {64, 64};
    encode(enc, &m.bre, p.bre, 2, d, s, bx, CU_TENSOR_MAP_SWIZZLE_128B);
    encode(enc, &m.bim, p.bim, 2, d, s, bx, CU_TENSOR_MAP_SWIZZLE_128B);
  }
  {
    cuuint64_t d[5] = {1024, 2, 4, 2, 64}, s[4] = {2048, 8192, 4096, 32768};
    cuuint32_t bx[5] = {64, 2, 4, 2, 8};
    encode(enc, &m.cre, p.cre, 5, d, s, bx, CU_TENSOR_MAP_SWIZZLE_128B);
    encode(enc, &m.cim, p.cim, 5, d, s, bx, CU_TENSOR_MAP_SWIZZLE_128B);
  }
  {
    cuuint64_t d[3] = {64, 32, 1024}, s[2] = {128, 4096};
    cuuint32_t bx[3] = {64, 1, 32};
    encode(enc, &m.u, uptr, 3, d, s, bx, CU_TENSOR_MAP_SWIZZLE_NONE);
  }
  {
    cuuint64_t d[3] = {1024, 256, 8}, s[2] = {16384, 2048};
    cuuint32_t bx[3] = {64, 8, 4}, bh[3] = {64, 1, 3};
    encode(enc, &m.k, p.k, 3, d, s, bx, CU_TENSOR_MAP_SWIZZLE_128B);
    encode(enc, &m.kh, p.k, 3, d, s, bh, CU_TENSOR_MAP_SWIZZLE_NONE);
    encode(enc, &m.v, p.v, 3, d, s, bx, CU_TENSOR_MAP_SWIZZLE_128B);
  }
  {
    cuuint64_t d[5] = {2048, 2, 4, 2, 64}, s[4] = {4096, 16384, 8192, 65536};
    cuuint32_t bx[5] = {64, 2, 4, 2, 1};
    encode(enc, &m.z, zptr, 5, d, s, bx, CU_TENSOR_MAP_SWIZZLE_128B);
  }
  {
    cuuint64_t d[4] = {1024, 2, 4, 256}, s[3] = {8192, 2048, 16384};
    cuuint32_t bx[4] = {64, 2, 4, 16};
    encode(enc, &m.x2, p.x, 4, d, s, bx, CU_TENSOR_MAP_SWIZZLE_128B);
  }
  cudaFuncSetAttribute(fused_kernel, cudaFuncAttributeMaxDynamicSharedMemorySize, SMEM_BYTES);
  fused_kernel<<<132, 512, SMEM_BYTES, cudaStreamPerThread>>>(m, p);
}
```

```cpp
#include <cuda_runtime.h>
#include <cuda_bf16.h>
#include <cuda.h>
#include <stdint.h>

namespace {

constexpr int SEQ = 2048, DM = 1024;
constexpr int NS = 5;
constexpr int STAGE = 32768;
#define KV0_AT 300
#define KV_GAP 550
#define KV_GAP0 500
#define KV_GAP1 400
#define EARLY 2
#define SFM 0x2
#define RV 1
#define POLL_NS 60
#define IM_NS 60
#define SPF_AT 9000
#define RELK 0
#define RES 4
#define AGG_NS 200
#define LD_GAP 400
#define LDQ ""
#define PROMO CU_TENSOR_MAP_L2_PROMOTION_L2_128B
constexpr uint32_t sb = 1024;
constexpr uint32_t S_STG = sb + NS * STAGE;
constexpr uint32_t S_CIN = S_STG + 32768;
constexpr uint32_t S_T = S_CIN + 16384;
constexpr uint32_t S_M1 = S_T + 8192;
constexpr uint32_t S_M2 = S_M1 + 4096;
constexpr uint32_t S_PAR = S_M2 + 2048;
constexpr uint32_t S_G = S_PAR + 4096;
constexpr uint32_t S_BAR = S_G + 512;
constexpr int SMEM_BYTES = S_BAR + 512 - sb;
constexpr uint32_t B_FULL = S_BAR, B_EMPTY = B_FULL + 8 * NS, B_CINF = B_EMPTY + 8 * NS,
                   B_FLG = B_CINF + 24, B_SFREE = B_FLG + 72, B_LOC = B_SFREE + 24, B_GATE = B_LOC + 24, B_ZT = B_GATE + 16,
                   B_XT = B_ZT + 24, B_PIN = B_XT + 24, B_DUMMY = B_PIN + 32, S_EP = B_DUMMY + 8;
constexpr int SPIN_LIMIT = 1 << 21;
constexpr int F_H = 0, F_U = 64, F_Z = 80;

struct alignas(64) Maps { CUtensorMap x, bre, bim, cre, cim, u, z, x2, k, kh, v; };
struct Ptrs {
  const __nv_bfloat16 *x, *lre, *lim, *ldt, *dskip, *k, *v, *shift, *f, *ssmd, *gw, *bre, *bim, *cre, *cim;
  float* out;
  uint64_t dc1[12][NS], dc2[12][NS];
};

__device__ uint4 g_h[16 * 32 * 1024];
__device__ uint4 g_u[1024 * 256];
__device__ uint4 g_z[1024 * 256];
__device__ uint4 g_agg[2 * 16 * 256];
__device__ unsigned g_gate[8 * SEQ];
__device__ unsigned g_flag[104 * 32];
__device__ unsigned g_epoch[132];
#define TIM(i)
#define TIMC(i)

#define WG_FENCE() asm volatile("wgmma.fence.sync.aligned;" ::: "memory")
#define WG_COMMIT() asm volatile("wgmma.commit_group.sync.aligned;" ::: "memory")
#define WG_WAIT(n) asm volatile("wgmma.wait_group.sync.aligned %0;" ::"n"(n) : "memory")
#define R8(d, o) "+f"(d[o + 0]), "+f"(d[o + 1]), "+f"(d[o + 2]), "+f"(d[o + 3]), "+f"(d[o + 4]), "+f"(d[o + 5]), "+f"(d[o + 6]), "+f"(d[o + 7])
#define W8(d, o) "=f"(d[o + 0]), "=f"(d[o + 1]), "=f"(d[o + 2]), "=f"(d[o + 3]), "=f"(d[o + 4]), "=f"(d[o + 5]), "=f"(d[o + 6]), "=f"(d[o + 7])
#define L16 "%0,%1,%2,%3,%4,%5,%6,%7,%8,%9,%10,%11,%12,%13,%14,%15"
#define L64 L16 ",%16,%17,%18,%19,%20,%21,%22,%23,%24,%25,%26,%27,%28,%29,%30,%31," \
  "%32,%33,%34,%35,%36,%37,%38,%39,%40,%41,%42,%43,%44,%45,%46,%47,%48,%49,%50,%51,%52,%53,%54,%55,%56,%57,%58,%59,%60,%61,%62,%63"

template <int TA, int TB, int ACC>
__device__ __forceinline__ void wgmma_ss128(float (&d)[64], uint64_t da, uint64_t db) {
  if (ACC)
    asm volatile("wgmma.mma_async.sync.aligned.m64n128k16.f32.bf16.bf16 {" L64 "}, %64, %65, 1, 1, 1, %66, %67;"
                 : R8(d, 0), R8(d, 8), R8(d, 16), R8(d, 24), R8(d, 32), R8(d, 40), R8(d, 48), R8(d, 56)
                 : "l"(da), "l"(db), "n"(TA), "n"(TB));
  else
    asm volatile("wgmma.mma_async.sync.aligned.m64n128k16.f32.bf16.bf16 {" L64 "}, %64, %65, 0, 1, 1, %66, %67;"
                 : W8(d, 0), W8(d, 8), W8(d, 16), W8(d, 24), W8(d, 32), W8(d, 40), W8(d, 48), W8(d, 56)
                 : "l"(da), "l"(db), "n"(TA), "n"(TB));
}
template <int ACC, int TB = 0>
__device__ __forceinline__ void wgmma_rs32(float (&d)[16], uint32_t a0, uint32_t a1, uint32_t a2, uint32_t a3, uint64_t db) {
  if (ACC)
    asm volatile("wgmma.mma_async.sync.aligned.m64n32k16.f32.bf16.bf16 {" L16 "}, {%16,%17,%18,%19}, %20, 1, 1, 1, %21;"
                 : R8(d, 0), R8(d, 8) : "r"(a0), "r"(a1), "r"(a2), "r"(a3), "l"(db), "n"(TB));
  else
    asm volatile("wgmma.mma_async.sync.aligned.m64n32k16.f32.bf16.bf16 {" L16 "}, {%16,%17,%18,%19}, %20, 0, 1, 1, %21;"
                 : W8(d, 0), W8(d, 8) : "r"(a0), "r"(a1), "r"(a2), "r"(a3), "l"(db), "n"(TB));
}
template <int N>
__device__ __forceinline__ void reg_fence(float (&d)[N]) {
#pragma unroll
  for (int i = 0; i < N; i++) asm volatile("" : "+f"(d[i])::"memory");
}
__host__ __device__ __forceinline__ constexpr uint32_t dlo(uint32_t addr, uint32_t lbo) { return (addr >> 4) + ((lbo >> 4) << 16); }
__device__ __forceinline__ uint64_t mkdesc(uint32_t lo, uint32_t sbo, uint32_t mode) {
  uint64_t d;
  asm("mov.b64 %0, {%1, %2};" : "=l"(d) : "r"(lo), "r"((sbo >> 4) | (mode << 30)));
  return d;
}
template <int N>
__device__ __forceinline__ void zero(float (&d)[N]) {
#pragma unroll
  for (int i = 0; i < N; i++) d[i] = 0.f;
}
__device__ __forceinline__ void trap_if(int c) {
  asm volatile("{.reg .pred p; .reg .b64 z; setp.ne.s32 p, %0, 0; mov.b64 z, 0; @p st.global.u32 [z], %0;}" ::"r"(c) : "memory");
}
template <int K>
__device__ __forceinline__ void sched_fence() {
  asm volatile("{.reg .pred p; setp.eq.u32 p, %0, %1; @p exit;}" ::"r"(gridDim.x), "n"(256 + K) : "memory");
}
template <int K>
__device__ __forceinline__ void sched_fence_async() {
  asm volatile("{.reg .pred p; .reg .u32 r; setp.ne.u32 p, %0, %1; @p bra.uni SFE;\n"
               "SFL: nanosleep.u32 1000; mov.u32 r, %%clock; setp.eq.u32 p, r, 0; @p bra.uni SFL;\nSFE: }" ::"r"(gridDim.x), "n"(256 + K) : "memory");
}
__device__ __forceinline__ bool elect_one() {
  uint32_t pred;
  asm volatile("{.reg .pred p; elect.sync _|p, 0xffffffff; selp.u32 %0, 1, 0, p;}" : "=r"(pred));
  return pred;
}
__device__ __forceinline__ void mbar_init(uint32_t bar, uint32_t cnt) {
  asm volatile("mbarrier.init.shared::cta.b64 [%0], %1;" ::"r"(bar), "r"(cnt) : "memory");
}
__device__ __forceinline__ bool mbar_try(uint32_t bar, uint32_t par) {
  uint32_t ok;
  asm volatile("{.reg .pred p; mbarrier.try_wait.parity.shared::cta.b64 p, [%1], %2; selp.u32 %0, 1, 0, p;}"
               : "=r"(ok) : "r"(bar), "r"(par) : "memory");
  return ok;
}
#undef DBGV
#define DBGV ((bar - S_BAR) * 2 + par)
__device__ __forceinline__ void mbar_wait(uint32_t bar, uint32_t par) {
  if (__builtin_expect(!mbar_try(bar, par), 0)) {
    int n = SPIN_LIMIT;
    while (!mbar_try(bar, par) && --n) {}
    trap_if(n == 0);
  }
}
#define full_wait(bar, par, slot) mbar_wait(bar, par)
__device__ __forceinline__ void mbar_wait_long(uint32_t bar, uint32_t par) {
  int n = SPIN_LIMIT;
  while (!mbar_try(bar, par) && --n) __nanosleep(100);
  trap_if(n == 0);
}
#undef DBGV
#define DBGV 0
__device__ __forceinline__ void mbar_arrive(uint32_t bar) {
  asm volatile("mbarrier.arrive.shared::cta.b64 _, [%0];" ::"r"(bar) : "memory");
}
__device__ __forceinline__ void mbar_expect(uint32_t bar, uint32_t bytes) {
  asm volatile("mbarrier.arrive.expect_tx.shared::cta.b64 _, [%0], %1;" ::"r"(bar), "r"(bytes) : "memory");
}
__device__ __forceinline__ void tma2d(uint32_t dst, const CUtensorMap* m, uint32_t bar, int c0, int c1) {
  asm volatile("cp.async.bulk.tensor.2d.shared::cluster.global.mbarrier::complete_tx::bytes [%0], [%1, {%3, %4}], [%2];"
               ::"r"(dst), "l"(m), "r"(bar), "r"(c0), "r"(c1) : "memory");
}
__device__ __forceinline__ void tma3d(uint32_t dst, const CUtensorMap* m, uint32_t bar, int c0, int c1, int c2) {
  asm volatile("cp.async.bulk.tensor.3d.shared::cluster.global.mbarrier::complete_tx::bytes [%0], [%1, {%3, %4, %5}], [%2];"
               ::"r"(dst), "l"(m), "r"(bar), "r"(c0), "r"(c1), "r"(c2) : "memory");
}
__device__ __forceinline__ void tma4d(uint32_t dst, const CUtensorMap* m, uint32_t bar, int c0, int c1, int c2, int c3) {
  asm volatile("cp.async.bulk.tensor.4d.shared::cluster.global.mbarrier::complete_tx::bytes [%0], [%1, {%3, %4, %5, %6}], [%2];"
               ::"r"(dst), "l"(m), "r"(bar), "r"(c0), "r"(c1), "r"(c2), "r"(c3) : "memory");
}
__device__ __forceinline__ void tma5d(uint32_t dst, const CUtensorMap* m, uint32_t bar, int c0, int c1, int c2, int c3, int c4) {
  asm volatile("cp.async.bulk.tensor.5d.shared::cluster.global.mbarrier::complete_tx::bytes [%0], [%1, {%3, %4, %5, %6, %7}], [%2];"
               ::"r"(dst), "l"(m), "r"(bar), "r"(c0), "r"(c1), "r"(c2), "r"(c3), "r"(c4) : "memory");
}
__device__ __forceinline__ void bulk_load(uint32_t dst, const void* src, uint32_t bytes, uint32_t bar) {
  asm volatile("cp.async.bulk.shared::cluster.global.mbarrier::complete_tx::bytes [%0], [%1], %2, [%3];"
               ::"r"(dst), "l"(src), "r"(bytes), "r"(bar) : "memory");
}
__device__ __forceinline__ void l2_prefetch(const void* src, uint32_t bytes) {
  asm volatile("cp.async.bulk.prefetch.L2.global [%0], %1;" ::"l"(src), "r"(bytes) : "memory");
}
__device__ __forceinline__ void bar_sync(int id, int n) { asm volatile("bar.sync %0, %1;" ::"r"(id), "r"(n) : "memory"); }
__device__ __forceinline__ void bar_arrive(int id, int n) { asm volatile("bar.arrive %0, %1;" ::"r"(id), "r"(n) : "memory"); }
__device__ __forceinline__ void fence_async_smem() { asm volatile("fence.proxy.async.shared::cta;" ::: "memory"); }
__device__ __forceinline__ void fence_async_global() { asm volatile("fence.proxy.async.global;" ::: "memory"); }
__device__ __forceinline__ void flag_add(int f) {
  asm volatile("red.relaxed.gpu.global.add.u32 [%0], 1;" ::"l"(g_flag + f * 32) : "memory");
}
__device__ __forceinline__ void flag_release(int f) {
  asm volatile("fence.release.gpu;" ::: "memory");
  flag_add(f);
}
__device__ __forceinline__ unsigned ld_relaxed(const unsigned* p) {
  unsigned v;
  asm volatile("ld.relaxed.gpu.global.u32 %0, [%1];" : "=r"(v) : "l"(p) : "memory");
  return v;
}
__device__ __forceinline__ void wait_clock(unsigned t) {
  int d;
  while ((d = (int)(t - (unsigned)clock())) > 0) __nanosleep(d > 600 ? 200 : 40);
}
__device__ __forceinline__ uint32_t pack2(float lo, float hi) {
  uint32_t r;
  asm("cvt.rn.bf16x2.f32 %0, %1, %2;" : "=r"(r) : "f"(hi), "f"(lo));
  return r;
}
__device__ __forceinline__ float bf_lo(uint32_t v) { return __uint_as_float(v << 16); }
__device__ __forceinline__ float bf_hi(uint32_t v) { return __uint_as_float(v & 0xffff0000u); }
__device__ __forceinline__ float bf_round(float v) { return __bfloat162float(__float2bfloat16_rn(v)); }
__device__ __forceinline__ uint32_t hmul2(uint32_t a, uint32_t b) {
  uint32_t r;
  asm("mul.rn.bf16x2 %0, %1, %2;" : "=r"(r) : "r"(a), "r"(b));
  return r;
}
__device__ __forceinline__ uint32_t hadd2(uint32_t a, uint32_t b) {
  uint32_t r;
  asm("add.rn.bf16x2 %0, %1, %2;" : "=r"(r) : "r"(a), "r"(b));
  return r;
}
__device__ __forceinline__ uint32_t hsub2(uint32_t a, uint32_t b) {
  uint32_t r;
  asm("sub.rn.bf16x2 %0, %1, %2;" : "=r"(r) : "r"(a), "r"(b));
  return r;
}
__device__ __forceinline__ uint32_t hfma2(uint32_t a, uint32_t b, uint32_t c) {
  uint32_t r;
  asm("fma.rn.bf16x2 %0, %1, %2, %3;" : "=r"(r) : "r"(a), "r"(b), "r"(c));
  return r;
}
__device__ __forceinline__ uint32_t hneg2(uint32_t a) {
  uint32_t r;
  asm("neg.bf16x2 %0, %1;" : "=r"(r) : "r"(a));
  return r;
}
__device__ __forceinline__ uint4 ldg128(const void* p) {
  uint4 v;
  asm volatile("ld.global.nc" LDQ ".v4.u32 {%0,%1,%2,%3}, [%4];" : "=r"(v.x), "=r"(v.y), "=r"(v.z), "=r"(v.w) : "l"(p));
  return v;
}
__device__ __forceinline__ uint2 ldg64(const void* p) {
  uint2 v;
  asm volatile("ld.global.nc.v2.u32 {%0,%1}, [%2];" : "=r"(v.x), "=r"(v.y) : "l"(p));
  return v;
}
__device__ __forceinline__ void stg128(void* p, uint32_t a, uint32_t b, uint32_t c, uint32_t d) {
  asm volatile("st.global.v4.u32 [%0], {%1,%2,%3,%4};" ::"l"(p), "r"(a), "r"(b), "r"(c), "r"(d) : "memory");
}
__device__ __forceinline__ void sts128(uint32_t a, uint32_t x, uint32_t y, uint32_t z, uint32_t w) {
  asm volatile("st.shared.v4.u32 [%0], {%1,%2,%3,%4};" ::"r"(a), "r"(x), "r"(y), "r"(z), "r"(w) : "memory");
}
__device__ __forceinline__ uint32_t lds32(uint32_t a) {
  uint32_t v;
  asm volatile("ld.shared.u32 %0, [%1];" : "=r"(v) : "r"(a) : "memory");
  return v;
}
__device__ __forceinline__ uint4 lds128(uint32_t a) {
  uint4 v;
  asm volatile("ld.shared.v4.u32 {%0,%1,%2,%3}, [%4];" : "=r"(v.x), "=r"(v.y), "=r"(v.z), "=r"(v.w) : "r"(a) : "memory");
  return v;
}
__device__ __forceinline__ void stsm4(uint32_t a, uint32_t x, uint32_t y, uint32_t z, uint32_t w) {
  asm volatile("stmatrix.sync.aligned.m8n8.x4.shared.b16 [%0], {%1,%2,%3,%4};" ::"r"(a), "r"(x), "r"(y), "r"(z), "r"(w) : "memory");
}
__device__ __forceinline__ void stsm4t(uint32_t a, uint32_t x, uint32_t y, uint32_t z, uint32_t w) {
  asm volatile("stmatrix.sync.aligned.m8n8.x4.trans.shared.b16 [%0], {%1,%2,%3,%4};" ::"r"(a), "r"(x), "r"(y), "r"(z), "r"(w) : "memory");
}
__device__ __forceinline__ uint4 ldsm4t(uint32_t a) {
  uint4 v;
  asm volatile("ldmatrix.sync.aligned.m8n8.x4.trans.shared.b16 {%0,%1,%2,%3}, [%4];" : "=r"(v.x), "=r"(v.y), "=r"(v.z), "=r"(v.w) : "r"(a) : "memory");
  return v;
}
struct cx { float r, i; };
__device__ __forceinline__ cx cmul(cx a, cx b) { return {a.r * b.r - a.i * b.i, a.r * b.i + a.i * b.r}; }
__device__ __forceinline__ cx cfma(cx a, cx b, cx c) { return {fmaf(a.r, b.r, fmaf(-a.i, b.i, c.r)), fmaf(a.r, b.i, fmaf(a.i, b.r, c.i))}; }
__device__ __forceinline__ cx csq(cx a) { return {a.r * a.r - a.i * a.i, 2.f * a.r * a.i}; }
__device__ __forceinline__ cx unit(int num, int den) {
  int m = num & (den - 1);
  if (m >= den / 2) m -= den;
  float s, c;
  __sincosf((float)m * (-6.283185307179586f / (float)den), &s, &c);
  return {c, s};
}

__device__ __forceinline__ uint2 lds64(uint32_t a) {
  uint2 v;
  asm volatile("ld.shared.v2.u32 {%0,%1}, [%2];" : "=r"(v.x), "=r"(v.y) : "r"(a) : "memory");
  return v;
}
template <int PG>
__device__ __forceinline__ void prep(const Ptrs& p, int ti, int pj, int w, int lane) {
  const int tb = lane & 7, chunk = 2 * w + (lane >> 4), ch = chunk * 8 + ((lane >> 3) & 1) * 4;
  uint32_t s[2][4];
#pragma unroll
  for (int e = 0; e < 2; e++) {
    const uint4 sh = ldg128(p.shift + (pj * 128 + PG * 64 + ch) * 4 + e * 8);
    s[e][0] = __byte_perm(sh.x, sh.z, 0x5410); s[e][1] = __byte_perm(sh.x, sh.z, 0x7632);
    s[e][2] = __byte_perm(sh.y, sh.w, 0x5410); s[e][3] = __byte_perm(sh.y, sh.w, 0x7632);
  }
#pragma unroll 1
  for (int th = 0; th < 2; th++) {
    const uint32_t in = S_STG + th * 16384 + (lane & 8);
    const uint32_t a0 = in + tb * 128 + ((chunk ^ tb) << 4);
    const uint32_t hb = tb ? in + (39 + tb) * 128 + ((chunk ^ (tb - 1)) << 4) : S_T + (PG * 2 + th) * 512 + ch * 2;
    const uint32_t hs = tb ? 1024 : 128;
    uint2 kk[11], vv[8];
    mbar_wait_long(B_PIN + 16 * PG + 8 * th, 0);
    if (th) TIM(29 + PG);
#pragma unroll
    for (int i = 0; i < 3; i++) kk[i] = lds64(hb + i * hs);
#pragma unroll
    for (int i = 0; i < 8; i++) { kk[3 + i] = lds64(a0 + i * 1024); vv[i] = lds64(a0 + 8192 + i * 1024); }
#pragma unroll
    for (int i = 0; i < 8; i++)
#pragma unroll
      for (int e = 0; e < 2; e++) {
        uint32_t a = hmul2((&kk[i].x)[e], s[e][3]);
        a = hfma2((&kk[i + 1].x)[e], s[e][2], a);
        a = hfma2((&kk[i + 2].x)[e], s[e][1], a);
        a = hfma2((&kk[i + 3].x)[e], s[e][0], a);
        (&vv[i].x)[e] = hmul2(a, (&vv[i].x)[e]);
      }
    sched_fence<52 + PG>();
    if (!PG) bar_arrive(th ? 14 : 3, 160);
    else if (elect_one()) mbar_arrive(B_SFREE + 8 * th);
    uint4* dst = g_u + (size_t)((pj * 4 + PG * 2 + (w >> 1)) * 32 + ti * 2 + th) * 256 + (ch & 31) * 8 + (tb ^ th);
#pragma unroll
    for (int e = 0; e < 2; e++) {
#define U(i) (&vv[i].x)[e]
      stg128(dst + (2 * e) * 8, __byte_perm(U(0), U(1), 0x5410), __byte_perm(U(2), U(3), 0x5410),
             __byte_perm(U(4), U(5), 0x5410), __byte_perm(U(6), U(7), 0x5410));
      stg128(dst + (2 * e + 1) * 8, __byte_perm(U(0), U(1), 0x7632), __byte_perm(U(2), U(3), 0x7632),
             __byte_perm(U(4), U(5), 0x7632), __byte_perm(U(6), U(7), 0x7632));
#undef U
    }
  }
  bar_arrive(4 + PG, 160);
}

__device__ __forceinline__ int gate_step(int pj) { return pj ? 2 * pj : 16; }
__device__ __forceinline__ void gate_partial(const Ptrs& p, int b, int ti, int pj, int w, int lane) {
  const int ck = lane & 7, s0 = gate_step(pj);
  const uint4 gw[2] = {ldg128(p.gw + pj * 128 + ck * 8), ldg128(p.gw + pj * 128 + 64 + ck * 8)};
  const uint32_t tag = (ld_relaxed(g_epoch + b) + 1) & 3;
  float s[8];
  mbar_wait_long(B_GATE, 0);
#pragma unroll
  for (int h = 0; h < 2; h++) {
    const int sl = (s0 + h) % NS;
    mbar_wait(B_FULL + 8 * sl, ((s0 + h) / NS) & 1);
#pragma unroll
    for (int i = 0; i < 8; i++) {
      const uint4 x = lds128(sb + sl * STAGE + 16384 + (32 * w + (lane >> 3) * 8 + i) * 128 + ((ck ^ i) << 4));
      const uint32_t q = hfma2(x.x, gw[h].x, hfma2(x.y, gw[h].y, hfma2(x.z, gw[h].z, hmul2(x.w, gw[h].w))));
      s[i] = h ? s[i] + (bf_lo(q) + bf_hi(q)) : bf_lo(q) + bf_hi(q);
    }
  }
  fence_async_smem();
  __syncwarp();
  if (elect_one()) mbar_arrive(B_GATE + 8);
#pragma unroll
  for (int o = 4; o > 0; o >>= 1)
#pragma unroll
    for (int i = 0; i < o; i++) {
      const bool up = ck & o;
      s[i] = (up ? s[i + o] : s[i]) + __shfl_xor_sync(~0u, up ? s[i] : s[i + o], o);
    }
  const int j = 4 * w + (lane >> 3);
  asm volatile("st.relaxed.gpu.global.u32 [%0], %1;" ::"l"(g_gate + pj * SEQ + ti * 128 + 32 * (ck >> 1) + 2 * j + (ck & 1)),
               "r"((__float_as_uint(s[0]) & ~3u) | tag) : "memory");
}
__device__ __forceinline__ void gate_finish(int ti, int tid) {
  const uint32_t tag = (lds32(S_EP) + 1) & 3;
  float l;
  int n = SPIN_LIMIT;
  bool bad;
  do {
    uint32_t v[8], x = 0;
#pragma unroll
    for (int j = 0; j < 8; j++) v[j] = ld_relaxed(g_gate + j * SEQ + ti * 128 + tid);
    l = 0.f;
#pragma unroll
    for (int j = 0; j < 8; j++) { x |= v[j] ^ tag; l += __uint_as_float(v[j]); }
    bad = __any_sync(~0u, x & 3);
  } while (bad && --n);
  trap_if(n == 0);
  const float g = bf_round(__fdividef(1.f, 1.f + __expf(-bf_round(l))));
  asm volatile("st.shared.f32 [%0], %1;" ::"r"(S_G + tid * 4), "f"(g) : "memory");
}

__device__ __forceinline__ void conv_tables(int tid) {
  {
    const int s = tid >> 5, n1 = tid & 31;
    uint32_t re[4], im[4];
#pragma unroll
    for (int e = 0; e < 4; e++) {
      cx a = unit(n1 * (4 * (8 * s + 2 * e) + 1), 128), b = unit(n1 * (4 * (8 * s + 2 * e + 1) + 1), 128);
      re[e] = pack2(a.r * 0.125f, b.r * 0.125f); im[e] = pack2(a.i * 0.125f, b.i * 0.125f);
    }
    sts128(S_M1 + (2 * s) * 512 + n1 * 16, re[0], re[1], re[2], re[3]);
    sts128(S_M1 + (2 * s + 1) * 512 + n1 * 16, im[0], im[1], im[2], im[3]);
  }
  {
    const int kg = tid >> 5, n = tid & 31;
    const int pi = kg >> 1, po = n >> 4, f2 = n & 15;
    uint32_t fw[4];
#pragma unroll
    for (int e = 0; e < 4; e++) {
      int n2 = (kg & 1) * 8 + 2 * e;
      cx a = unit(n2 * f2, 16), b = unit((n2 + 1) * f2, 16);
      float sg = pi ? -1.f : 1.f;
      float x0 = (pi == po) ? a.r : sg * a.i, x1 = (pi == po) ? b.r : sg * b.i;
      fw[e] = pack2(x0, x1);
    }
    sts128(S_M2 + kg * 512 + n * 16, fw[0], fw[1], fw[2], fw[3]);
  }
  fence_async_smem();
}
__device__ __forceinline__ constexpr int jj_of(int o) { return o == 7 ? 3 : o + (o >= 3); }
__device__ __forceinline__ int conv_chan(int ti, int pj, int jj) { return pj * 128 + jj * 16 + ti; }

struct ConvCtx {
  uint32_t buf, inbar;
  int nb, n;
  int ti, pj, j;
  __device__ __forceinline__ int chan(int c) const {
    return j < 0 ? conv_chan(ti, pj, c + (c >= 3)) : conv_chan((j + 12 * c) >> 3, (j + 12 * c) & 7, 3);
  }
};
__device__ __forceinline__ ConvCtx conv_ctx(int spare, int wg, int ti, int pj) {
  const int j = spare < 0 ? -1 : spare * 3 + wg;
  return {wg == 2 ? S_CIN : sb + wg * 32768, wg == 2 ? B_CINF : (wg ? B_PIN : B_FULL), 4 + 4 * wg, j < 0 ? 7 : (j < 8 ? 11 : 10), ti, pj, j};
}
#define CDESC(a) mkdesc(dlo(a, 512), 128, 0)
struct ConvTw { uint32_t r[2], i[2], n[2]; };

__device__ __forceinline__ void cv_tw1(float (&d)[64], uint32_t (&R)[16], uint32_t (&I)[16], const ConvTw& t, int i) {
#pragma unroll
  for (int j = 8 * (i & 1); j < 8 * (i & 1) + 8; j++) {
    if (i < 2) {
      R[j] = pack2(d[4 * j], d[4 * j + 1]); I[j] = pack2(d[4 * j + 2], d[4 * j + 3]);
    } else {
      const uint32_t xr = R[j], xi = I[j];
      R[j] = hfma2(xr, t.r[j & 1], hmul2(xi, t.n[j & 1]));
      I[j] = hfma2(xr, t.i[j & 1], hmul2(xi, t.r[j & 1]));
    }
  }
}
template <int N>
__device__ __forceinline__ void cv_pack(float (&X)[16], uint32_t (&P)[N][2][2], int q) {
#pragma unroll
  for (int k = 0; k < 2; k++)
#pragma unroll
    for (int j = 0; j < 4; j++) P[2 * q + k][j >> 1][j & 1] = pack2(X[4 * j + 2 * k], X[4 * j + 2 * k + 1]);
}
__device__ __forceinline__ void cv_overlap(uint32_t (&P)[8][2][2]) {
#pragma unroll
  for (int k = 3; k > 0; k--)
#pragma unroll
    for (int hh = 0; hh < 2; hh++) {
      P[k][0][hh] = hsub2(P[k][0][hh], P[k - 1][1][hh]);
      P[k][1][hh] = hadd2(P[k][1][hh], P[k - 1][0][hh]);
    }
}
__device__ __forceinline__ void cv_pw(uint32_t (&P)[8][2][2], uint32_t (&Q)[4][2][2]) {
#pragma unroll
  for (int jh = 0; jh < 8; jh++) {
    const int j = jh >> 1, hh = jh & 1;
    uint32_t qr = hmul2(P[4 + j][0][hh], P[0][0][hh]), qi = hmul2(P[4 + j][0][hh], P[0][1][hh]);
    qr = hfma2(hneg2(P[4 + j][1][hh]), P[0][1][hh], qr);
    qi = hfma2(P[4 + j][1][hh], P[0][0][hh], qi);
#pragma unroll
    for (int k = j - 1; k >= 0; k--) {
      qr = hfma2(P[4 + k][0][hh], P[j - k][0][hh], qr);
      qi = hfma2(P[4 + k][0][hh], P[j - k][1][hh], qi);
      qr = hfma2(hneg2(P[4 + k][1][hh]), P[j - k][1][hh], qr);
      qi = hfma2(P[4 + k][1][hh], P[j - k][0][hh], qi);
    }
    Q[j][0][hh] = qr; Q[j][1][hh] = qi;
  }
}
__device__ __forceinline__ void cv_tw2(uint32_t (&Q)[4][2][2], const ConvTw& t, int k) {
#pragma unroll
  for (int hh = 0; hh < 2; hh++) {
    const uint32_t xr = Q[k][0][hh], xi = Q[k][1][hh];
    Q[k][0][hh] = hfma2(xr, t.r[hh], hmul2(xi, t.i[hh]));
    Q[k][1][hh] = hfma2(xr, t.n[hh], hmul2(xi, t.r[hh]));
  }
}
__device__ __forceinline__ void cv_out0(float (&Y)[16], uint32_t T, int w, int lane) {
  reg_fence(Y);
  const uint32_t za = T + w * 2048 + (lane >> 4) * 256 + (lane & 7) * 32 + ((lane >> 3) & 1) * 16;
#pragma unroll
  for (int jj = 0; jj < 2; jj++)
    stsm4t(za + jj * 512, pack2(Y[8 * jj], Y[8 * jj + 1]), pack2(Y[8 * jj + 2], Y[8 * jj + 3]),
           pack2(Y[8 * jj + 4], Y[8 * jj + 5]), pack2(Y[8 * jj + 6], Y[8 * jj + 7]));
}

template <bool FW, bool BW, int K>
__device__ __forceinline__ void conv_step(uint32_t (&Q)[4][2][2], const ConvTw& t, const ConvCtx& cc, float dl, int ch, int w, int lane) {
#define SF(n) if ((SFM >> (n)) & 1) sched_fence_async<K + (n)>()
  float d[64], X[4][16], Z[2][16], Y[16];
  uint32_t R[16], I[16];
  uint4 a[4];
  const int nx = ch + 1;
  const uint32_t T = cc.buf + 16384;
  float dv;
  TIMC(1);
  if (FW) {
    dv = __shfl_sync(~0u, dl, nx);
    mbar_wait(cc.inbar + 8 * (nx & 1), (nx >> 1) & 1);
  }
  TIMC(2);
  WG_FENCE();
  if (BW) {
#pragma unroll
    for (int q = 0; q < 2; q++) {
      wgmma_rs32<0, 1>(Z[q], Q[2 * q][0][0], Q[2 * q + 1][0][0], Q[2 * q][0][1], Q[2 * q + 1][0][1], mkdesc(dlo(S_M2, 128), 512, 0));
      wgmma_rs32<1, 1>(Z[q], Q[2 * q][1][0], Q[2 * q + 1][1][0], Q[2 * q][1][1], Q[2 * q + 1][1][1], mkdesc(dlo(S_M2 + 256, 128), 512, 0));
    }
    WG_COMMIT();
  }
  if (FW) {
    const uint32_t lo = dlo(0, 1024) + (cc.buf >> 4) + (nx & 1) * 512;
    wgmma_ss128<1, 1, 0>(d, mkdesc(dlo(S_M1, 128), 512, 0), mkdesc(lo, 256, 3));
    wgmma_ss128<1, 1, 1>(d, mkdesc(dlo(S_M1 + 256, 128), 512, 0), mkdesc(lo + 32, 256, 3));
    WG_COMMIT();
  }
  TIMC(3);
  if (BW) {
    TIMC(4);
    WG_WAIT(FW ? 1 : 0);
    TIMC(5);
    reg_fence(Z[0]); reg_fence(Z[1]);
    uint32_t V[4][2][2];
    cv_pack(Z[0], V, 0); cv_pack(Z[1], V, 1);
    SF(0);
#pragma unroll
    for (int k = 0; k < 4; k++) cv_tw2(V, t, k);
    sched_fence_async<K + 6>();
    bar_sync(cc.nb + 3, 160);
#pragma unroll
    for (int k = 0; k < 4; k++) stsm4(T + w * 512 + lane * 16 + k * 2048, V[k][0][0], V[k][0][1], V[k][1][0], V[k][1][1]);
    SF(1);
    TIMC(6);
  }
  if (FW) {
    WG_WAIT(0);
    reg_fence(d);
    if (nx + 2 < cc.n) bar_arrive(cc.nb + 2, 160);
    cv_tw1(d, R, I, t, 0); cv_tw1(d, R, I, t, 1);
    SF(2);
    TIMC(7);
  }
  if (BW) {
    bar_sync(cc.nb, 128);
#pragma unroll
    for (int s = 0; s < 4; s++) a[s] = ldsm4t(T + (4 * w + s) * 512 + lane * 16);
  }
  if (FW) { cv_tw1(d, R, I, t, 2); cv_tw1(d, R, I, t, 3); }
  sched_fence<K + 3>();
  TIMC(8);
  WG_FENCE();
  if (BW) {
    wgmma_rs32<0>(Y, a[0].x, a[0].y, a[0].z, a[0].w, CDESC(S_M1));
#pragma unroll
    for (int i = 1; i < 4; i++) wgmma_rs32<1>(Y, a[i].x, a[i].y, a[i].z, a[i].w, CDESC(S_M1 + 1024 * i));
  }
  if (FW) {
#pragma unroll
    for (int q = 0; q < 4; q++) {
      if (q == 2) WG_COMMIT();
      wgmma_rs32<0>(X[q], R[4 * q], R[4 * q + 2], R[4 * q + 1], R[4 * q + 3], CDESC(S_M2));
      wgmma_rs32<1>(X[q], I[4 * q], I[4 * q + 2], I[4 * q + 1], I[4 * q + 3], CDESC(S_M2 + 1024));
    }
  }
  WG_COMMIT();
  TIMC(9);
  WG_WAIT(FW ? 1 : 0);
  TIMC(10);
  if (BW) { cv_out0(Y, T, w, lane); bar_arrive(cc.nb + 1, 160); }
  if (FW) {
    uint32_t P[8][2][2];
    reg_fence(X[0]); reg_fence(X[1]);
    cv_pack(X[0], P, 0); cv_pack(X[1], P, 1);
    cv_overlap(P);
    sched_fence_async<K + 7>();
    WG_WAIT(0);
    reg_fence(X[2]); reg_fence(X[3]);
    X[2][0] += dv; X[2][1] += dv; X[2][4] += dv; X[2][5] += dv;
    cv_pack(X[2], P, 2); cv_pack(X[3], P, 3);
    SF(4);
    TIMC(11);
    cv_pw(P, Q);
  }
  sched_fence<K + 5>();
  TIMC(13);
#undef SF
}

__device__ __forceinline__ void conv_main(const Ptrs& p, const ConvCtx& cc, int b, int tid) {
  const int ti = cc.ti, pj = cc.pj;
  const int w = tid >> 5, lane = tid & 31;
  ConvTw t;
#pragma unroll
  for (int hh = 0; hh < 2; hh++) {
    const int n2 = 8 * hh + 2 * (lane & 3), m = 4 * (8 * w + (lane >> 2)) + 1;
    cx a = unit(n2 * m, 2048), b = unit((n2 + 1) * m, 2048);
    t.r[hh] = pack2(a.r, b.r); t.i[hh] = pack2(a.i, b.i); t.n[hh] = pack2(-a.i, -b.i);
  }
  const float dl = 0.125f * __bfloat162float(p.ssmd[cc.chan(min(lane, cc.n - 1))]);
  if (cc.j < 0) {
    gate_partial(p, b, ti, pj, w, lane);
    prep<1>(p, ti, pj, w, lane);
  }
  {
    uint32_t P[4][2][2];
    mbar_wait_long(cc.inbar, 0);
    TIM(20);
    conv_step<true, false, 10>(P, t, cc, dl, -1, w, lane);
#pragma unroll 1
    for (int ch = 0; ch < cc.n - 1; ch++) {
      conv_step<true, true, 20>(P, t, cc, dl, ch, w, lane);
      if (ch == 0) TIM(21);
    }
    conv_step<false, true, 30>(P, t, cc, dl, cc.n - 1, w, lane);
  }
  TIM(22);
}

__device__ __forceinline__ cx csel(bool k, cx a, cx b) { return {k ? a.r : b.r, k ? a.i : b.i}; }
__device__ __forceinline__ void ld2cx(uint32_t a, cx& x, cx& y) {
  const uint4 v = lds128(a);
  x = {__uint_as_float(v.x), __uint_as_float(v.y)};
  y = {__uint_as_float(v.z), __uint_as_float(v.w)};
}
__device__ __forceinline__ cx ldcx(uint32_t a) {
  cx x;
  asm volatile("ld.shared.v2.f32 {%0,%1}, [%2];" : "=f"(x.r), "=f"(x.i) : "r"(a) : "memory");
  return x;
}

__device__ __forceinline__ void scan_epilogue(float (&aR)[64], float (&aI)[64], uint32_t last_empty, int ph, int ti, int pj, int tid) {
  const int w = tid >> 5, lane = tid & 31, r = lane >> 2, c = lane & 3;
  const uint32_t par = S_PAR + (ph * 64 + 16 * w + r) * 16;
  uint4* agg = g_agg + ph * 16 * 256 + pj * 32 + 8 * w + r;
  const uint32_t tag = (lds32(S_EP) + 1) & 3;
  cx h[2];
  {
    cx lam[2], a[2];
#pragma unroll
    for (int q = 0; q < 2; q++) { lam[q] = ldcx(par + q * 128); h[q] = ldcx(par + 2048 + q * 128); }
    WG_WAIT(0);
    if (elect_one()) mbar_arrive(last_empty);
    asm volatile("setmaxnreg.inc.sync.aligned.u32 168;");
    reg_fence(aR); reg_fence(aI);
    TIM(3 + ph * 2);
#pragma unroll
    for (int q = 0; q < 2; q++) a[q] = {aR[2 * q], aI[2 * q]};
#pragma unroll
    for (int s = 1; s < 32; s++)
#pragma unroll
      for (int q = 0; q < 2; q++) {
        const int i = 4 * (s >> 1) + 2 * q + (s & 1);
        a[q] = cfma(lam[q], a[q], {aR[i], aI[i]});
      }
    sched_fence<1>();
    cx t[2][3];
#pragma unroll
    for (int q = 0; q < 2; q++)
#pragma unroll
      for (int k = 0; k < 3; k++) t[q][k] = {__shfl_up_sync(~0u, a[q].r, k + 1, 4), __shfl_up_sync(~0u, a[q].i, k + 1, 4)};
#pragma unroll
    for (int q = 0; q < 2; q++) {
      const cx z = {0.f, 0.f};
      cx ex = cfma(h[q], csel(c >= 3, t[q][2], z), csel(c >= 2, t[q][1], z));
      ex = cfma(h[q], ex, csel(c >= 1, t[q][0], z));
      a[q] = cfma(h[q], ex, a[q]);
      const cx u = cfma(lam[q], ex, {aR[2 * q], aI[2 * q]});
      aR[2 * q] = u.r; aI[2 * q] = u.i;
    }
    if (c == 3)
      asm volatile("st.relaxed.gpu.global.v4.u32 [%0], {%1,%2,%3,%4};" ::"l"(agg + ti * 256),
                   "r"((__float_as_uint(a[0].r) & ~3u) | tag), "r"((__float_as_uint(a[0].i) & ~3u) | tag),
                   "r"((__float_as_uint(a[1].r) & ~3u) | tag), "r"((__float_as_uint(a[1].i) & ~3u) | tag) : "memory");
    TIM(8 + ph * 4);
  }
  if (ti > 0) {
    const uint2* ap = (const uint2*)(agg + (ti - 1 - (c >> 1)) * 256) + (c & 1);
    const int cnt = ti - (c >> 1);
    const cx one = {1.f, 0.f};
    const cx l128 = ldcx(par + 2048 + 8 + (c & 1) * 128), l256 = csq(l128), fa = csel(c & 2, l128, one);
#pragma unroll
    for (int q = 0; q < 2; q++) h[q] = cmul(csel(c & 1, h[q], one), csel(c & 2, csq(h[q]), one));
    uint2 v[8];
    int n = SPIN_LIMIT;
    bool bad;
    __nanosleep(AGG_NS);
    TIM(27 + ph);
    do {
      uint32_t x = 0;
#pragma unroll
      for (int j = 0; j < 8; j++) {
        v[j] = make_uint2(tag, tag);
        asm volatile("{.reg .pred p; setp.lt.s32 p, %3, %4; @p ld.relaxed.gpu.global.v2.u32 {%0,%1}, [%2];}"
                     : "+r"(v[j].x), "+r"(v[j].y) : "l"(ap - j * 1024), "r"(2 * j), "r"(cnt) : "memory");
      }
#pragma unroll
      for (int j = 0; j < 8; j++) x |= (v[j].x ^ tag) | (v[j].y ^ tag);
      bad = __any_sync(~0u, x & 3);
    } while (bad && --n);
    trap_if(n == 0);
    cx a = {__uint_as_float(v[7].x), __uint_as_float(v[7].y)};
#pragma unroll
    for (int j = 6; j >= 0; j--) a = cfma(l256, a, {__uint_as_float(v[j].x), __uint_as_float(v[j].y)});
    a = cmul(a, fa);
    const cx t1 = {__shfl_xor_sync(~0u, a.r, 1), __shfl_xor_sync(~0u, a.i, 1)};
    const cx t2 = {__shfl_xor_sync(~0u, a.r, 2), __shfl_xor_sync(~0u, a.i, 2)};
    const cx t3 = {__shfl_xor_sync(~0u, a.r, 3), __shfl_xor_sync(~0u, a.i, 3)};
    const cx own = {a.r + t2.r, a.i + t2.i}, oth = {t1.r + t3.r, t1.i + t3.i};
#pragma unroll
    for (int q = 0; q < 2; q++) h[q] = cmul(csel((c & 1) == q, own, oth), h[q]);
  } else {
    h[0] = h[1] = {0.f, 0.f};
  }
  TIM(9 + ph * 4);
  cx lam[2];
  uint32_t cr[2], nci[2];
#pragma unroll
  for (int q = 0; q < 2; q++) {
    const uint4 v = lds128(par + q * 128);
    lam[q] = {__uint_as_float(v.x), __uint_as_float(v.y)};
    cr[q] = v.z; nci[q] = v.w;
  }
  mbar_wait(B_SFREE + 16 * ph, 0);
  const uint32_t hs = S_STG + w * 1024 + r * 64 + ((c ^ (r >> 1)) << 4);
  uint4* hg = g_h + (size_t)(ti * 32 + ph * 16 + pj) * 1024 + w * 64 + r * 4 + (c ^ (r >> 1));
  uint32_t pr[4][2][4], pi[4][2][4];
#pragma unroll
  for (int i = 0; i < 4; i++) {
    uint32_t o[2][4];
#pragma unroll
    for (int s2 = 0; s2 < 4; s2++)
#pragma unroll
      for (int q = 0; q < 2; q++) {
        const int k = 4 * (4 * i + s2) + 2 * q;
        cx h0 = cfma(lam[q], h[q], {aR[k], aI[k]});
        h[q] = cfma(lam[q], h0, {aR[k + 1], aI[k + 1]});
        pr[i][q][s2] = pack2(h0.r, h[q].r);
        pi[i][q][s2] = pack2(h0.i, h[q].i);
        o[q][s2] = hfma2(pr[i][q][s2], cr[q], hmul2(pi[i][q][s2], nci[q]));
      }
#pragma unroll
    for (int q = 0; q < 2; q++) {
      stg128(hg + i * 256 + q * 32, o[q][0], o[q][1], o[q][2], o[q][3]);
      sts128(hs + i * 4096 + q * 512, o[q][0], o[q][1], o[q][2], o[q][3]);
    }
    if (i == 0) sched_fence<7>();
    if (i == 1) sched_fence<8>();
    if (i == 2) sched_fence<6>();
  }
  bar_arrive(9, 160);
  sched_fence<9>();
  TIM(10 + ph * 4);
  if (ph == 0) mbar_wait(B_SFREE + 8, 0);
#pragma unroll
  for (int q = 0; q < 2; q++) {
    const uint32_t ncr = cr[q] ^ 0x80008000u;
#pragma unroll
    for (int i = 0; i < 4; i++) {
      uint32_t o[4];
#pragma unroll
      for (int s2 = 0; s2 < 4; s2++) o[s2] = hfma2(pi[i][q][s2], ncr, hmul2(pr[i][q][s2], nci[q]));
      sts128(hs + 16384 + i * 4096 + q * 512, o[0], o[1], o[2], o[3]);
      if (IM_NS) __nanosleep(IM_NS);
      stg128(hg + 8192 + i * 256 + q * 32, o[0], o[1], o[2], o[3]);
    }
  }
  fence_async_smem();
  __syncwarp();
  if (elect_one()) mbar_arrive(B_LOC + 8 * ph);
  bar_arrive(10, 160);
  bar_sync(1 + ph, 128);
  asm volatile("setmaxnreg.dec.sync.aligned.u32 160;");
}

__device__ __forceinline__ constexpr uint32_t e_addr(int o, int mh) { return S_STG + (o * 2 + mh) * 2048; }
__device__ __forceinline__ void eterm(const Ptrs& p, int ti, int pj, int tid) {
  const int w = tid >> 5, lane = tid & 31, r = lane >> 2, c = lane & 3;
  const int trow = 64 * (w & 1) + 8 * (w >> 1) + r;
  const int rs = 2 * (r & 3) + (r >> 2);
  uint2 xv[2][8][2], ds[8];
#pragma unroll
  for (int jj = 0; jj < 8; jj++) ds[jj] = ldg64(p.dskip + pj * 128 + 16 * jj + 4 * c);
  gate_finish(ti, tid);
#pragma unroll
  for (int g = 0; g < 2; g++) {
    mbar_wait_long(B_XT + 8 * g, 0);
#pragma unroll
    for (int i = 0; i < 4; i++)
#pragma unroll
      for (int jj = 4 * g; jj < 4 * g + 4; jj++)
        xv[i >> 1][jj][i & 1] = lds64(sb + ((48 + g) % NS) * STAGE + (trow - r + rs + 16 * (i >> 1) + 32 * (i & 1)) * 128 + (((2 * (jj & 3) + (c >> 1)) ^ rs) << 4) + (c & 1) * 8);
  }
  fence_async_smem();
  __syncwarp();
  if (elect_one()) mbar_arrive(B_XT + 16);
  bar_sync(2, 128);
  TIM(31);
  uint32_t g2[2][2], og2[2][2];
#pragma unroll
  for (int mh = 0; mh < 2; mh++)
#pragma unroll
    for (int hf = 0; hf < 2; hf++) {
      uint32_t g;
      asm volatile("ld.shared.u32 %0, [%1];" : "=r"(g) : "r"(S_G + (trow + 16 * mh + 32 * hf) * 4) : "memory");
      g2[mh][hf] = __byte_perm(g, g, 0x3232);
      og2[mh][hf] = hsub2(0x3f803f80u, g2[mh][hf]);
    }
  const int dl = lane & 15;
  const uint32_t za = S_STG + (w & 1) * 2048 + dl * 128;
#pragma unroll
  for (int g = 0; g < 3; g++) {
    const int o0 = g ? 2 + 2 * g : 0, o1 = 4 + 2 * g;
    if (g == 2) mbar_wait(B_ZT + 16, 0); else mbar_wait_long(B_ZT + 8 * g, 0);
    if (g == 2) TIM(16);
#pragma unroll
    for (int mh = 0; mh < 2; mh++) {
      const uint32_t zb = za + (((4 * (lane >> 4) + 2 * mh + (w >> 1)) ^ (dl & 7)) << 4);
#pragma unroll
      for (int o = o0; o < o1; o++) {
        const int jj = jj_of(o);
        uint4 z = ldsm4t(zb + o * 4096);
#pragma unroll
        for (int hf = 0; hf < 2; hf++) {
          uint2& x = xv[mh][jj][hf];
          x.x = hmul2(x.x, hfma2(og2[mh][hf], hf ? z.z : z.x, hmul2(g2[mh][hf], ds[jj].x)));
          x.y = hmul2(x.y, hfma2(og2[mh][hf], hf ? z.w : z.y, hmul2(g2[mh][hf], ds[jj].y)));
        }
      }
    }
    bar_sync(2, 128);
#pragma unroll
    for (int o = o0; o < o1; o++)
#pragma unroll
      for (int mh = 0; mh < 2; mh++) {
        const int jj = jj_of(o);
        sts128(e_addr(o, mh) + tid * 16, xv[mh][jj][0].x, xv[mh][jj][0].y, xv[mh][jj][1].x, xv[mh][jj][1].y);
      }
    bar_arrive(5 + g, 256);
    if (g == 0) TIM(1);
    if (g == 1) TIM(23);
  }
  TIM(17);
}

__device__ __forceinline__ void store_piece(float (&a)[64], float* op, int jj, const uint4& e, float g0, float g1) {
  stg128(op + 16 * jj, __float_as_uint(fmaf(g0, a[8 * jj], bf_lo(e.x))), __float_as_uint(fmaf(g0, a[8 * jj + 1], bf_hi(e.x))),
         __float_as_uint(fmaf(g0, a[8 * jj + 4], bf_lo(e.y))), __float_as_uint(fmaf(g0, a[8 * jj + 5], bf_hi(e.y))));
  stg128(op + 32 * DM + 16 * jj, __float_as_uint(fmaf(g1, a[8 * jj + 2], bf_lo(e.z))), __float_as_uint(fmaf(g1, a[8 * jj + 3], bf_hi(e.z))),
         __float_as_uint(fmaf(g1, a[8 * jj + 6], bf_lo(e.w))), __float_as_uint(fmaf(g1, a[8 * jj + 7], bf_hi(e.w))));
}

__device__ __forceinline__ void issue_g1(const Maps& m, int s, int sl, int ti, int pj) {
  const uint32_t bar = B_FULL + 8 * sl, dst = sb + sl * STAGE;
  const int k0 = (s & 15) * 64, ch = (s >> 4) * 512 + pj * 64;
  mbar_expect(bar, STAGE);
  tma4d(dst + 16384, &m.x, bar, k0, 0, 4 * ti, 0);
  tma2d(dst, &m.bre, bar, k0, ch);
  tma2d(dst + 8192, &m.bim, bar, k0, ch);
}
__device__ __forceinline__ void producer(const Maps& m, int ti, int pj) {
#pragma unroll
  for (int s = EARLY; s < NS; s++) issue_g1(m, s, s, ti, pj);
  int sl = 0, par = 0;
  const int gs = gate_step(pj);
  if (gs + 1 < NS) mbar_arrive(B_GATE);
#pragma unroll 1
  for (int s = NS; s < 32; s++) {
    mbar_wait(B_EMPTY + 8 * sl, par);
    if (s == gs + NS) mbar_wait(B_GATE + 8, 0);
    issue_g1(m, s, sl, ti, pj);
    if (s == gs + 1) mbar_arrive(B_GATE);
    if (++sl == NS) { sl = 0; par ^= 1; }
  }
#pragma unroll 1
  for (int q = 0; q < 32; q++) {
    mbar_wait(B_EMPTY + 8 * sl, par);
    const uint32_t bar = B_FULL + 8 * sl, dst = sb + sl * STAGE;
    const int ph = q >> 4, u = q & 15, part = u < 2 ? u : u >= 9, i = u - 2 - 7 * part;
    const int src = u < 2 ? pj : (i < 4 ? (~pj & 4) + i : (pj & 4) + i - 4 + (i - 4 >= (pj & 3)));
    if (q == 16 + NS) mbar_wait(B_XT + 16, 0);
    mbar_expect(bar, u < 2 ? 16384 : STAGE);
    tma5d(dst + 16384, part ? &m.cim : &m.cre, bar, ph * 512 + src * 64, 0, 0, 0, pj * 8);
    if (u < 2) {
      if (ph) {
        mbar_expect(B_XT + 8 * u, 16384);
        tma4d(dst, &m.x2, B_XT + 8 * u, pj * 128 + u * 64, 0, 0, ti * 16);
      }
    } else {
      if (i == 0) {
        mbar_wait(B_FLG + 8 * (2 * ph + part), 0);
        fence_async_global();
        if (part == 0) TIM(24 + ph);
      }
      bulk_load(dst, g_h + (size_t)(ti * 32 + ph * 16 + part * 8 + src) * 1024, 16384, bar);
    }
    if (++sl == NS) { sl = 0; par ^= 1; }
  }
}

__device__ __forceinline__ void poller(int ti, int pj, int lane, unsigned ep) {
  if (lane < 9) {
    const int f = lane < 4 ? F_H + lane * 16 + ti : (lane < 6 ? F_U + pj * 2 + lane - 4 : F_Z + pj * 3 + lane - 6);
    const unsigned need = (ep + 1) * (lane < 4 ? 8 : (lane == 8 ? 19 : 16));
    int n = SPIN_LIMIT;
    bool done = false;
    do {
      if (!done && (int)(ld_relaxed(g_flag + f * 32) - need) >= 0) {
        done = true;
        asm volatile("fence.acquire.gpu;" ::: "memory");
        mbar_arrive(B_FLG + 8 * lane);
      }
      if (POLL_NS) __nanosleep(POLL_NS);
    } while (!__all_sync(0x1ffu, done) && --n);
    trap_if(n == 0);
  }
}
__device__ __forceinline__ void poller_spare(int b, int lane) {
  const unsigned ep = ld_relaxed(g_epoch + b);
  int n = SPIN_LIMIT;
  while (!__all_sync(~0u, (int)(ld_relaxed(g_flag + (F_U + (lane & 7) * 2) * 32) - (ep + 1) * 16) >= 0) && --n) {}
  trap_if(n == 0);
  asm volatile("fence.acquire.gpu;" ::: "memory");
  __syncwarp();
  if (lane == 0) { mbar_arrive(B_FLG + 32); mbar_arrive(B_FLG + 40); g_epoch[b] = ep + 1; }
}

__device__ __forceinline__ void storer(const Maps& m, int ti, int pj) {
#pragma unroll 1
  for (int job = 0; job < 6; job++) {
    bar_sync(job < 2 ? 4 + job : 9 + (job & 1), 160);
    if (elect_one()) flag_release(job < 2 ? F_U + pj * 2 + job : F_H + (job - 2) * 16 + ti);
    __syncwarp();
    if (job == 2 || job == 4) TIM(7 + job * 2);
  }
  if (elect_one()) {
    mbar_wait_long(B_LOC + 16, 0);
#pragma unroll 1
    for (int o = 0; o < 8; o++) {
      const int g = o < 4 ? 0 : (o >> 1) - 1;
      if (o == 0 || o == 4 || o == 6) {
        if (o == 6) mbar_wait(B_FLG + 64, 0); else mbar_wait_long(B_FLG + 48 + 8 * g, 0);
        fence_async_global();
        mbar_expect(B_ZT + 8 * g, o ? 8192 : 16384);
      }
      tma5d(S_STG + o * 4096, &m.z, B_ZT + 8 * g, ti * 128, 0, 0, 0, pj * 8 + jj_of(o));
      tma5d(S_STG + o * 4096 + 2048, &m.z, B_ZT + 8 * g, ti * 128 + 64, 0, 0, 0, pj * 8 + jj_of(o));
    }
  }
}

__device__ __forceinline__ void conv_loader(const Maps& m, const Ptrs& p, const ConvCtx& cc, int lane, unsigned t_start) {
  const int ti = cc.ti, pj = cc.pj;
  bar_arrive(cc.nb + 3, 160);
  unsigned tt = t_start + KV0_AT;
#pragma unroll 1
  for (int st = cc.j < 0 ? 0 : 4; st < 4; st++) {
    const int d = pj * 128 + (st >> 1) * 64, tb = ti * 16 + (st & 1) * 8;
    const uint32_t bar = B_PIN + 8 * st;
    if (st >= 2) { bar_sync(st == 2 ? 3 : 14, 160); fence_async_smem(); }
    if (elect_one()) {
      mbar_expect(bar, 16384 + 384);
      if ((int)(clock() - tt) > 0) tt = clock();
#pragma unroll 1
      for (int i = 0; i < 4; i++) {
        wait_clock(tt);
        tt += st == 3 ? KV_GAP1 : (st == 0 ? KV_GAP0 : KV_GAP);
        tma3d(S_STG + (st & 1) * 16384 + i * 4096, (i & 2) ? &m.v : &m.k, bar, d, tb, (i & 1) * 4);
        if (i == 0) tma3d(S_T + st * 512, &m.kh, bar, d, tb - 1, 5);
      }
      if (st >= 2) l2_prefetch(p.f + (size_t)conv_chan(ti, pj, st - 2) * SEQ, 4096);
    }
    tt = __shfl_sync(~0u, tt, 0);
  }
  if (cc.j >= 0 && elect_one()) {
    wait_clock(t_start + SPF_AT);
#pragma unroll 1
    for (int ch = 0; ch < cc.n; ch++) l2_prefetch(p.f + (size_t)cc.chan(ch) * SEQ, 4096);
  }
  __syncwarp();
#pragma unroll 1
  for (int ch = 0; ch < cc.n + 3; ch++) {
    if (ch < cc.n) {
      const int d = cc.chan(ch);
      const uint32_t bar = cc.inbar + 16, dst = cc.buf + (ch & 1) * 8192;
      if (ch > 2) bar_sync(cc.nb + 2, 160);
      if (elect_one()) {
        mbar_expect(bar, 8192);
        bulk_load(dst + 4096, p.f + (size_t)d * SEQ, 4096, bar);
        if (ch == 0 || ch == 3) {
          mbar_wait_long(B_FLG + (ch ? 40 : 32), 0);
          fence_async_global();
        }
        tma3d(dst, &m.u, bar, 0, d & 31, d & ~31);
      }
      __syncwarp();
    }
    if (ch >= 3) {
      const int d = cc.chan(ch - 3);
      bar_sync(cc.nb + 1, 160);
#pragma unroll 1
      for (int i = 0; i < 4; i++) {
        const uint4 x = lds128(cc.buf + 16384 + i * 2048 + lane * 16), y = lds128(cc.buf + 16384 + 512 + i * 2048 + lane * 16);
        uint4* zp = g_z + (size_t)d * 256 + i * 64 + lane;
        stg128(zp, x.x, x.y, x.z, x.w);
        stg128(zp + 32, y.x, y.y, y.z, y.w);
      }
      if (ch < cc.n + 2) bar_arrive(cc.nb + 3, 160);
    }
    if (ch < cc.n) {
      const uint32_t a = cc.buf + (ch & 1) * 8192 + 4096 + 128 + (lane >> 3) * 256 + (lane & 7) * 16;
      mbar_wait(cc.inbar + 16, ch & 1);
#pragma unroll 1
      for (uint32_t i = a; i < a + 4096; i += 1024) {
        const uint4 x = lds128(i);
        __syncwarp();
        sts128(i ^ 16, x.x, x.y, x.z, x.w);
      }
      fence_async_smem();
      __syncwarp();
      if (ch == 1) bar_sync(cc.nb + 2, 160);
      if (elect_one()) mbar_arrive(cc.inbar + 8 * (ch & 1));
      __syncwarp();
    }
    if (cc.j < 0 ? (ch == 6 || ch >= 8) : ch == cc.n + 2) {
      __syncwarp();
      if (elect_one()) {
        flag_release(F_Z + (cc.chan(ch - 3) >> 7) * 3 + (cc.j >= 0 ? 2 : (ch == 6 ? 0 : ch - 7)));
        if (cc.j >= 0) flag_add(F_Z + (cc.chan(ch - 4) >> 7) * 3 + 2);
      }
      __syncwarp();
    }
  }
}

struct Ring { uint32_t off, par, rel; };
__device__ __forceinline__ void desc_touch(const uint64_t (&c)[12][NS]) {
  uint32_t x = 0;
#pragma unroll
  for (int i = 0; i < 12 * NS; i += 4) x |= (uint32_t)(&c[0][0])[i];
  trap_if((x | (uint32_t)c[11][NS - 1]) == 0);
}
template <int TA, bool TAB, bool LOC = false>
__device__ __forceinline__ void gemm_steps(float (&a0)[64], float (&a1)[64], Ring& r, int n, const uint64_t (&c)[12][NS], int slot) {
#pragma unroll 1
  do {
    const uint32_t off = r.off, rel = r.rel;
    full_wait(B_FULL + off, r.par, slot);
    r.rel = off;
    r.off += 8;
    if (r.off == 8 * NS) { r.off = 0; r.par ^= 1; }
    WG_FENCE();
#define DESC(i) (*(const uint64_t*)((const char*)c[i] + off))
#pragma unroll
    for (int k = 0; k < 4; k++) {
      const uint64_t db = TAB ? DESC(3 * k) : mkdesc(off * 256 + dlo(sb + 16384 + 32 * k, 16), 1024, 1);
      if (LOC) {
        wgmma_ss128<TA, 0, 1>(a0, mkdesc(dlo(S_STG + 32768 + 1024 * k, 4096) - n * 1024, 512, 2), db);
        wgmma_ss128<TA, 0, 1>(a1, mkdesc(dlo(S_STG + 32768 + 8192 + 1024 * k, 4096) - n * 1024, 512, 2), db);
      } else {
        wgmma_ss128<TA, 0, 1>(a0, TAB ? DESC(3 * k + 1) : mkdesc(off * 256 + dlo(sb + 32 * k, 16), 1024, 1), db);
        wgmma_ss128<TA, 0, 1>(a1, TAB ? DESC(3 * k + 2) : mkdesc(off * 256 + dlo(sb + 8192 + 32 * k, 16), 1024, 1), db);
      }
      if (k == RELK) {
        WG_COMMIT();
        WG_WAIT(1);
        if (elect_one()) mbar_arrive(B_EMPTY + rel);
      }
    }
#undef DESC
    if (RELK < 3) WG_COMMIT();
  } while (--n);
}

__global__ void __launch_bounds__(512, 1) fused_kernel(const __grid_constant__ Maps m, const __grid_constant__ Ptrs p) {
  extern __shared__ __align__(1024) uint8_t smem_raw[];
  int b = blockIdx.x;
  {
    int sm, nsm;
    asm volatile("mov.u32 %0, %%smid;" : "=r"(sm));
    asm volatile("mov.u32 %0, %%nsmid;" : "=r"(nsm));
    const int tp = sm >> 1, q = ((tp - 32) * 37) >> 8;
    const int g = tp < 32 ? tp & 7 : (tp < 60 ? tp - 31 - 7 * q : (tp < 62 ? 8 : 0));
    const int j = tp < 32 ? tp >> 3 : (tp < 60 ? 4 + q : (tp < 62 ? tp - 60 : tp - 58));
    if (nsm == 132) b = g * 16 + j * 2 + (sm & 1);
    b = __shfl_sync(~0u, b, 0);
  }
  const int spare = b - 128;
  const int ti = ((b >> 5) << 2) | (b & 3), pj = (((b >> 4) & 1) << 2) | ((b >> 2) & 3);
  const int wid = __shfl_sync(~0u, threadIdx.x >> 5, 0), wg = wid >> 2, tid = threadIdx.x & 127, lane = threadIdx.x & 31;
  if (wg == 0) TIM(0);
  const unsigned t_start = clock();
  if (wid == 12) {
    if (elect_one()) {
      asm volatile("prefetch.tensormap [%0];" ::"l"(&m.x) : "memory");
      asm volatile("prefetch.tensormap [%0];" ::"l"(&m.bre) : "memory");
      asm volatile("prefetch.tensormap [%0];" ::"l"(&m.bim) : "memory");
#pragma unroll
      for (int i = 0; i < NS; i++) mbar_init(B_FULL + 8 * i, 1);
      fence_async_smem();
#pragma unroll
      for (int s = 0; s < EARLY; s++) if (spare < 0) issue_g1(m, s, s, ti, pj);
    }
  } else if (wid == 13) {
    if (elect_one()) {
      trap_if((uint32_t)__cvta_generic_to_shared(smem_raw) != sb);
#pragma unroll
      for (uint32_t bar = B_EMPTY; bar < S_EP; bar += 8) mbar_init(bar, (bar < B_CINF || (bar >= B_SFREE && bar < B_GATE) || bar == B_GATE + 8 || bar == B_XT + 16) ? 4 : 1);
      fence_async_smem();
    }
  }
  __syncwarp();
  if (wg == 3) {
    asm volatile("setmaxnreg.dec.sync.aligned.u32 %0;" ::"n"(RV == 2 ? 32 : 24));
    bar_sync(1, 128);
    if (spare < 0) {
      if (wid == 13) { bar_arrive(2, 160); bar_arrive(12, 160); }
      bar_arrive(0, 256);
    } else {
      bar_arrive(0, 512);
    }
    if (wid == 13) {
      if (spare < 0) poller(ti, pj, lane, ld_relaxed(g_epoch + b));
      else poller_spare(b, lane);
    } else if (wid == 15 || spare >= 0) {
      conv_loader(m, p, conv_ctx(spare, wid == 12 ? 0 : wid - 13, ti, pj), lane, t_start);
    } else if (wid == 12) {
      if (elect_one()) producer(m, ti, pj);
    } else {
      storer(m, ti, pj);
    }
  } else if (wg == 2 || spare >= 0) {
    asm volatile("setmaxnreg.inc.sync.aligned.u32 160;");
    if (wg == 2) conv_tables(tid);
    if (spare < 0) bar_sync(12, 160); else bar_sync(0, 512);
    conv_main(p, conv_ctx(spare, wg, ti, pj), b, tid);
  } else {
    asm volatile("setmaxnreg.inc.sync.aligned.u32 %0;" ::"n"(RV == 3 ? 168 : 160));
    if (wg == 1) {
      const int ch = (tid >> 6) * 512 + pj * 64 + (tid & 63);
      const unsigned ep = ld_relaxed(g_epoch + b);
      const float lr = __bfloat162float(p.lre[ch]), li = __bfloat162float(p.lim[ch]);
      const float dt = bf_round(expf(__bfloat162float(p.ldt[ch])));
      float sn, cs;
      sincosf(dt * li, &sn, &cs);
      const float ex = expf(dt * lr);
      const float ar = ex * cs, ai = ex * sn;
      const float inv = 2.f / (lr * lr + li * li);
      const float cr = ((ar - 1.f) * lr + ai * li) * inv, ci = (ai * lr - (ar - 1.f) * li) * inv;
      sts128(S_PAR + tid * 16, __float_as_uint(ar), __float_as_uint(ai), pack2(cr, cr), pack2(-ci, -ci));
      const cx l32 = csq(csq(csq(csq(csq({ar, ai}))))), l128 = csq(csq(l32));
      sts128(S_PAR + 2048 + tid * 16, __float_as_uint(l32.r), __float_as_uint(l32.i), __float_as_uint(l128.r), __float_as_uint(l128.i));
      if (tid == 0) asm volatile("st.shared.u32 [%0], %1;" ::"r"(S_EP), "r"(ep) : "memory");
      bar_arrive(6, 256);
      bar_sync(2, 160);
      desc_touch(p.dc1);
      prep<0>(p, ti, pj, wid & 3, lane);
    }
    float a0[64], a1[64];
    Ring ring = {8u * wg * (16 % NS), wg * ((16u / NS) & 1), B_DUMMY - B_EMPTY};
    zero(a0); zero(a1);
    reg_fence(a0); reg_fence(a1);
    sched_fence<61>();
    bar_sync(wg * 7, 256);
    TIM(2 + wg * 2);
    if (wg == 0) gemm_steps<0, false>(a0, a1, ring, 15, p.dc1, 0);
    else gemm_steps<0, true>(a0, a1, ring, 15, p.dc1, 1);
    bar_arrive(7 + wg, 256);
    gemm_steps<0, false>(a0, a1, ring, 1, p.dc1, wg);
    if (wg == 0) bar_sync(6, 256);
    scan_epilogue(a0, a1, B_EMPTY + ring.rel, wg, ti, pj, tid);
    if (wg == 1) {
      eterm(p, ti, pj, tid);
    } else {
      ring = {8 * (32 % NS), (32 / NS) & 1, B_DUMMY - B_EMPTY};
      desc_touch(p.dc2);
      zero(a0); zero(a1);
      reg_fence(a0); reg_fence(a1);
      sched_fence<62>();
      bar_sync(8, 256);
      TIM(6);
#pragma unroll 1
      for (int o = 0; o < 4; o++) {
        if (!(o & 1)) {
          if (o) TIM(18);
          full_wait(B_LOC + 4 * o, 0, 2 + 2 * o);
          gemm_steps<1, true, true>(a0, a1, ring, 2, p.dc2, 3 + 2 * o);
        }
        gemm_steps<1, true>(a0, a1, ring, (o & 1) ? (o == 1 ? 13 : 13 - RES) : 1, p.dc2, 4 + 2 * o - (o & 1));
        if (!(o & 1) && elect_one()) {
          mbar_arrive(o ? B_LOC + 16 : B_SFREE + 16);
        }
      }
#pragma unroll
      for (int i = 0; i < RES; i++) {
        const int sl = (64 - RES + i) % NS;
        full_wait(B_FULL + 8 * sl, ((64 - RES + i) / NS) & 1, 10);
        WG_FENCE();
#pragma unroll
        for (int k = 0; k < 4; k++) wgmma_ss128<1, 0, 1>(a0, p.dc2[3 * k + 1][sl], p.dc2[3 * k][sl]);
        WG_COMMIT();
        if (i == 0 && RES == NS) { WG_WAIT(1); if (elect_one()) mbar_arrive(B_EMPTY + ring.rel); }
      }
      const int w = tid >> 5, trow = 16 * 0 + 64 * (w & 1) + 8 * (w >> 1) + (lane >> 2);
      float* op = p.out + (size_t)(ti * 128 + trow) * DM + pj * 128 + 4 * (lane & 3);
      float g[4];
      uint4 e;
#pragma unroll
      for (int i = 0; i < RES; i++) {
        const int sl = (64 - RES + i) % NS;
        if (i == 0) WG_FENCE();
#pragma unroll
        for (int k = 0; k < 4; k++) wgmma_ss128<1, 0, 1>(a1, p.dc2[3 * k + 2][sl], p.dc2[3 * k][sl]);
        WG_COMMIT();
        if (i == 0) {
          bar_sync(5, 256);
#pragma unroll
          for (int q = 0; q < 4; q++) g[q] = __uint_as_float(lds32(S_G + (trow + 16 * (q >> 1) + 32 * (q & 1)) * 4));
          e = lds128(e_addr(0, 0) + tid * 16);
          WG_WAIT(1);
          reg_fence(a0);
        }
        if (i < 4) {
          const uint4 e0 = e;
          e = lds128(e_addr((i + 1) & 3, i == 3) + tid * 16);
          store_piece(a0, op, jj_of(i), e0, g[0], g[1]);
        }
        if (i == 0) sched_fence_async<70>(); if (i == 1) sched_fence_async<71>(); if (i == 2) sched_fence_async<72>(); if (i == 3) sched_fence_async<73>();
      }
      TIM(26);
      WG_WAIT(0);
      reg_fence(a1);
      TIM(7);
#pragma unroll
      for (int o = 0; o < 8; o++) {
        if (o == 4 || o == 6) bar_sync(4 + (o >> 1), 256);
        if (o >= 4) store_piece(a0, op, jj_of(o), lds128(e_addr(o, 0) + tid * 16), g[0], g[1]);
        store_piece(a1, op + 16 * DM, jj_of(o), o ? lds128(e_addr(o, 1) + tid * 16) : e, g[2], g[3]);
      }
      if (tid == 0) g_epoch[b] = lds32(S_EP) + 1;
      TIM(19);
    }
  }
}

typedef CUresult (*EncFn)(CUtensorMap*, CUtensorMapDataType, cuuint32_t, void*, const cuuint64_t*, const cuuint64_t*,
                          const cuuint32_t*, const cuuint32_t*, CUtensorMapInterleave, CUtensorMapSwizzle,
                          CUtensorMapL2promotion, CUtensorMapFloatOOBfill);

void encode(EncFn enc, CUtensorMap* m, const void* ptr, int rank, const cuuint64_t* dims, const cuuint64_t* strides,
            const cuuint32_t* box, CUtensorMapSwizzle sw) {
  cuuint32_t es[5] = {1, 1, 1, 1, 1};
  enc(m, CU_TENSOR_MAP_DATA_TYPE_BFLOAT16, rank, const_cast<void*>(ptr), dims, strides, box, es, CU_TENSOR_MAP_INTERLEAVE_NONE,
      sw, PROMO, CU_TENSOR_MAP_FLOAT_OOB_FILL_NONE);
}

}

extern "C" void kernel_launch(void* const* d_in, const int* in_sizes, int n_in, void* d_out, int out_size) {
  typedef const __nv_bfloat16* bp;
  Ptrs p;
  p.x = (bp)d_in[0]; p.lre = (bp)d_in[1]; p.lim = (bp)d_in[2]; p.bre = (bp)d_in[3]; p.bim = (bp)d_in[4];
  p.cre = (bp)d_in[5]; p.cim = (bp)d_in[6]; p.ldt = (bp)d_in[7]; p.dskip = (bp)d_in[8];
  p.k = (bp)d_in[10]; p.v = (bp)d_in[11]; p.shift = (bp)d_in[12]; p.f = (bp)d_in[13]; p.ssmd = (bp)d_in[14];
  p.gw = (bp)d_in[15]; p.out = (float*)d_out;

  for (int sl = 0; sl < NS; sl++)
    for (int k = 0; k < 4; k++) {
      const uint64_t h128 = (uint64_t)(64u | (1u << 30)) << 32, h64 = (uint64_t)(32u | (2u << 30)) << 32;
      const uint32_t st = sb + sl * STAGE;
      p.dc1[3 * k][sl] = p.dc2[3 * k][sl] = h128 | dlo(st + 16384 + 32 * k, 16);
      p.dc1[3 * k + 1][sl] = h128 | dlo(st + 32 * k, 16);
      p.dc1[3 * k + 2][sl] = h128 | dlo(st + 8192 + 32 * k, 16);
      p.dc2[3 * k + 1][sl] = h64 | dlo(st + 1024 * k, 4096);
      p.dc2[3 * k + 2][sl] = h64 | dlo(st + 8192 + 1024 * k, 4096);
    }
  EncFn enc = nullptr;
  cudaDriverEntryPointQueryResult qr;
  cudaGetDriverEntryPoint("cuTensorMapEncodeTiled", (void**)&enc, cudaEnableDefault, &qr);
  void *zptr = nullptr, *uptr = nullptr;
  cudaGetSymbolAddress(&zptr, g_z);
  cudaGetSymbolAddress(&uptr, g_u);

  Maps m;
  {
    cuuint64_t d[4] = {1024, 2, 64, 16}, s[3] = {2048, 65536, 4096};
    cuuint32_t bx[4] = {64, 2, 4, 16};
    encode(enc, &m.x, p.x, 4, d, s, bx, CU_TENSOR_MAP_SWIZZLE_128B);
  }
  {
    cuuint64_t d[2] = {1024, 1024}, s[1] = {2048};
    cuuint32_t bx[2] = {64, 64};
    encode(enc, &m.bre, p.bre, 2, d, s, bx, CU_TENSOR_MAP_SWIZZLE_128B);
    encode(enc, &m.bim, p.bim, 2, d, s, bx, CU_TENSOR_MAP_SWIZZLE_128B);
  }
  {
    cuuint64_t d[5] = {1024, 2, 4, 2, 64}, s[4] = {2048, 8192, 4096, 32768};
    cuuint32_t bx[5] = {64, 2, 4, 2, 8};
    encode(enc, &m.cre, p.cre, 5, d, s, bx, CU_TENSOR_MAP_SWIZZLE_128B);
    encode(enc, &m.cim, p.cim, 5, d, s, bx, CU_TENSOR_MAP_SWIZZLE_128B);
  }
  {
    cuuint64_t d[3] = {64, 32, 1024}, s[2] = {128, 4096};
    cuuint32_t bx[3] = {64, 1, 32};
    encode(enc, &m.u, uptr, 3, d, s, bx, CU_TENSOR_MAP_SWIZZLE_NONE);
  }
  {
    cuuint64_t d[3] = {1024, 256, 8}, s[2] = {16384, 2048};
    cuuint32_t bx[3] = {64, 8, 4}, bh[3] = {64, 1, 3};
    encode(enc, &m.k, p.k, 3, d, s, bx, CU_TENSOR_MAP_SWIZZLE_128B);
    encode(enc, &m.kh, p.k, 3, d, s, bh, CU_TENSOR_MAP_SWIZZLE_NONE);
    encode(enc, &m.v, p.v, 3, d, s, bx, CU_TENSOR_MAP_SWIZZLE_128B);
  }
  {
    cuuint64_t d[5] = {2048, 2, 4, 2, 64}, s[4] = {4096, 16384, 8192, 65536};
    cuuint32_t bx[5] = {64, 2, 4, 2, 1};
    encode(enc, &m.z, zptr, 5, d, s, bx, CU_TENSOR_MAP_SWIZZLE_128B);
  }
  {
    cuuint64_t d[4] = {1024, 2, 4, 256}, s[3] = {8192, 2048, 16384};
    cuuint32_t bx[4] = {64, 2, 4, 16};
    encode(enc, &m.x2, p.x, 4, d, s, bx, CU_TENSOR_MAP_SWIZZLE_128B);
  }
  cudaFuncSetAttribute(fused_kernel, cudaFuncAttributeMaxDynamicSharedMemorySize, SMEM_BYTES);
  fused_kernel<<<132, 512, SMEM_BYTES, cudaStreamPerThread>>>(m, p);
}
```

```cpp
#include <cuda_runtime.h>
#include <cuda_bf16.h>
#include <cuda.h>
#include <stdint.h>

namespace {

constexpr int SEQ = 2048, DM = 1024;
constexpr int NS = 5;
constexpr int STAGE = 32768;
#define KV0_AT 300
#define KV_GAP 550
#define KV_GAP0 500
#define KV_GAP1 400
#define EARLY 2
#define SFM 0x2
#define RV 1
#define POLL_NS 60
#define IM_NS 60
#define SPF_AT 9000
#define RELK 0
#define RES 4
#define AGG_NS 200
#define ZL_NS 100
#define LD_GAP 400
#define LDQ ""
#define PROMO CU_TENSOR_MAP_L2_PROMOTION_L2_128B
constexpr uint32_t sb = 1024;
constexpr uint32_t S_STG = sb + NS * STAGE;
constexpr uint32_t S_CIN = S_STG + 32768;
constexpr uint32_t S_T = S_CIN + 16384;
constexpr uint32_t S_M1 = S_T + 8192;
constexpr uint32_t S_M2 = S_M1 + 4096;
constexpr uint32_t S_PAR = S_M2 + 2048;
constexpr uint32_t S_G = S_PAR + 4096;
constexpr uint32_t S_BAR = S_G + 512;
constexpr int SMEM_BYTES = S_BAR + 512 - sb;
constexpr uint32_t B_FULL = S_BAR, B_EMPTY = B_FULL + 8 * NS, B_CINF = B_EMPTY + 8 * NS,
                   B_FLG = B_CINF + 24, B_SFREE = B_FLG + 48, B_LOC = B_SFREE + 24, B_GATE = B_LOC + 24, B_ZT = B_GATE + 16,
                   B_XT = B_ZT + 16, B_PIN = B_XT + 24, B_DUMMY = B_PIN + 32, S_EP = B_DUMMY + 8;
constexpr int SPIN_LIMIT = 1 << 21;
constexpr int F_H = 0, F_U = 64, F_Z = 80;

struct alignas(64) Maps { CUtensorMap x, bre, bim, cre, cim, u, z, x2, k, kh, v; };
struct Ptrs {
  const __nv_bfloat16 *x, *lre, *lim, *ldt, *dskip, *k, *v, *shift, *f, *ssmd, *gw, *bre, *bim, *cre, *cim;
  float* out;
  uint64_t dc1[12][NS], dc2[12][NS];
};

__device__ uint4 g_h[16 * 32 * 1024];
__device__ uint4 g_u[1024 * 256];
__device__ uint4 g_z[1024 * 256];
__device__ uint4 g_agg[2 * 16 * 256];
__device__ unsigned g_gate[8 * SEQ];
__device__ unsigned g_flag[96 * 32];
__device__ unsigned g_epoch[140];
#define TIM(i)
#define TIMC(i)

#define WG_FENCE() asm volatile("wgmma.fence.sync.aligned;" ::: "memory")
#define WG_COMMIT() asm volatile("wgmma.commit_group.sync.aligned;" ::: "memory")
#define WG_WAIT(n) asm volatile("wgmma.wait_group.sync.aligned %0;" ::"n"(n) : "memory")
#define R8(d, o) "+f"(d[o + 0]), "+f"(d[o + 1]), "+f"(d[o + 2]), "+f"(d[o + 3]), "+f"(d[o + 4]), "+f"(d[o + 5]), "+f"(d[o + 6]), "+f"(d[o + 7])
#define W8(d, o) "=f"(d[o + 0]), "=f"(d[o + 1]), "=f"(d[o + 2]), "=f"(d[o + 3]), "=f"(d[o + 4]), "=f"(d[o + 5]), "=f"(d[o + 6]), "=f"(d[o + 7])
#define L16 "%0,%1,%2,%3,%4,%5,%6,%7,%8,%9,%10,%11,%12,%13,%14,%15"
#define L64 L16 ",%16,%17,%18,%19,%20,%21,%22,%23,%24,%25,%26,%27,%28,%29,%30,%31," \
  "%32,%33,%34,%35,%36,%37,%38,%39,%40,%41,%42,%43,%44,%45,%46,%47,%48,%49,%50,%51,%52,%53,%54,%55,%56,%57,%58,%59,%60,%61,%62,%63"

template <int TA, int TB, int ACC>
__device__ __forceinline__ void wgmma_ss128(float (&d)[64], uint64_t da, uint64_t db) {
  if (ACC)
    asm volatile("wgmma.mma_async.sync.aligned.m64n128k16.f32.bf16.bf16 {" L64 "}, %64, %65, 1, 1, 1, %66, %67;"
                 : R8(d, 0), R8(d, 8), R8(d, 16), R8(d, 24), R8(d, 32), R8(d, 40), R8(d, 48), R8(d, 56)
                 : "l"(da), "l"(db), "n"(TA), "n"(TB));
  else
    asm volatile("wgmma.mma_async.sync.aligned.m64n128k16.f32.bf16.bf16 {" L64 "}, %64, %65, 0, 1, 1, %66, %67;"
                 : W8(d, 0), W8(d, 8), W8(d, 16), W8(d, 24), W8(d, 32), W8(d, 40), W8(d, 48), W8(d, 56)
                 : "l"(da), "l"(db), "n"(TA), "n"(TB));
}
template <int ACC, int TB = 0>
__device__ __forceinline__ void wgmma_rs32(float (&d)[16], uint32_t a0, uint32_t a1, uint32_t a2, uint32_t a3, uint64_t db) {
  if (ACC)
    asm volatile("wgmma.mma_async.sync.aligned.m64n32k16.f32.bf16.bf16 {" L16 "}, {%16,%17,%18,%19}, %20, 1, 1, 1, %21;"
                 : R8(d, 0), R8(d, 8) : "r"(a0), "r"(a1), "r"(a2), "r"(a3), "l"(db), "n"(TB));
  else
    asm volatile("wgmma.mma_async.sync.aligned.m64n32k16.f32.bf16.bf16 {" L16 "}, {%16,%17,%18,%19}, %20, 0, 1, 1, %21;"
                 : W8(d, 0), W8(d, 8) : "r"(a0), "r"(a1), "r"(a2), "r"(a3), "l"(db), "n"(TB));
}
template <int N>
__device__ __forceinline__ void reg_fence(float (&d)[N]) {
#pragma unroll
  for (int i = 0; i < N; i++) asm volatile("" : "+f"(d[i])::"memory");
}
__host__ __device__ __forceinline__ constexpr uint32_t dlo(uint32_t addr, uint32_t lbo) { return (addr >> 4) + ((lbo >> 4) << 16); }
__device__ __forceinline__ uint64_t mkdesc(uint32_t lo, uint32_t sbo, uint32_t mode) {
  uint64_t d;
  asm("mov.b64 %0, {%1, %2};" : "=l"(d) : "r"(lo), "r"((sbo >> 4) | (mode << 30)));
  return d;
}
template <int N>
__device__ __forceinline__ void zero(float (&d)[N]) {
#pragma unroll
  for (int i = 0; i < N; i++) d[i] = 0.f;
}
__device__ __forceinline__ void trap_if(int c) {
  asm volatile("{.reg .pred p; .reg .b64 z; setp.ne.s32 p, %0, 0; mov.b64 z, 0; @p st.global.u32 [z], %0;}" ::"r"(c) : "memory");
}
template <int K>
__device__ __forceinline__ void sched_fence() {
  asm volatile("{.reg .pred p; setp.eq.u32 p, %0, %1; @p exit;}" ::"r"(gridDim.x), "n"(256 + K) : "memory");
}
template <int K>
__device__ __forceinline__ void sched_fence_async() {
  asm volatile("{.reg .pred p; .reg .u32 r; setp.ne.u32 p, %0, %1; @p bra.uni SFE;\n"
               "SFL: nanosleep.u32 1000; mov.u32 r, %%clock; setp.eq.u32 p, r, 0; @p bra.uni SFL;\nSFE: }" ::"r"(gridDim.x), "n"(256 + K) : "memory");
}
__device__ __forceinline__ bool elect_one() {
  uint32_t pred;
  asm volatile("{.reg .pred p; elect.sync _|p, 0xffffffff; selp.u32 %0, 1, 0, p;}" : "=r"(pred));
  return pred;
}
__device__ __forceinline__ void mbar_init(uint32_t bar, uint32_t cnt) {
  asm volatile("mbarrier.init.shared::cta.b64 [%0], %1;" ::"r"(bar), "r"(cnt) : "memory");
}
__device__ __forceinline__ bool mbar_try(uint32_t bar, uint32_t par) {
  uint32_t ok;
  asm volatile("{.reg .pred p; mbarrier.try_wait.parity.shared::cta.b64 p, [%1], %2; selp.u32 %0, 1, 0, p;}"
               : "=r"(ok) : "r"(bar), "r"(par) : "memory");
  return ok;
}
#undef DBGV
#define DBGV ((bar - S_BAR) * 2 + par)
__device__ __forceinline__ void mbar_wait(uint32_t bar, uint32_t par) {
  if (__builtin_expect(!mbar_try(bar, par), 0)) {
    int n = SPIN_LIMIT;
    while (!mbar_try(bar, par) && --n) {}
    trap_if(n == 0);
  }
}
#define full_wait(bar, par, slot) mbar_wait(bar, par)
__device__ __forceinline__ void mbar_wait_long(uint32_t bar, uint32_t par) {
  int n = SPIN_LIMIT;
  while (!mbar_try(bar, par) && --n) __nanosleep(100);
  trap_if(n == 0);
}
#undef DBGV
#define DBGV 0
__device__ __forceinline__ void mbar_arrive(uint32_t bar) {
  asm volatile("mbarrier.arrive.shared::cta.b64 _, [%0];" ::"r"(bar) : "memory");
}
__device__ __forceinline__ void mbar_expect(uint32_t bar, uint32_t bytes) {
  asm volatile("mbarrier.arrive.expect_tx.shared::cta.b64 _, [%0], %1;" ::"r"(bar), "r"(bytes) : "memory");
}
__device__ __forceinline__ void tma2d(uint32_t dst, const CUtensorMap* m, uint32_t bar, int c0, int c1) {
  asm volatile("cp.async.bulk.tensor.2d.shared::cluster.global.mbarrier::complete_tx::bytes [%0], [%1, {%3, %4}], [%2];"
               ::"r"(dst), "l"(m), "r"(bar), "r"(c0), "r"(c1) : "memory");
}
__device__ __forceinline__ void tma3d(uint32_t dst, const CUtensorMap* m, uint32_t bar, int c0, int c1, int c2) {
  asm volatile("cp.async.bulk.tensor.3d.shared::cluster.global.mbarrier::complete_tx::bytes [%0], [%1, {%3, %4, %5}], [%2];"
               ::"r"(dst), "l"(m), "r"(bar), "r"(c0), "r"(c1), "r"(c2) : "memory");
}
__device__ __forceinline__ void tma4d(uint32_t dst, const CUtensorMap* m, uint32_t bar, int c0, int c1, int c2, int c3) {
  asm volatile("cp.async.bulk.tensor.4d.shared::cluster.global.mbarrier::complete_tx::bytes [%0], [%1, {%3, %4, %5, %6}], [%2];"
               ::"r"(dst), "l"(m), "r"(bar), "r"(c0), "r"(c1), "r"(c2), "r"(c3) : "memory");
}
__device__ __forceinline__ void tma5d(uint32_t dst, const CUtensorMap* m, uint32_t bar, int c0, int c1, int c2, int c3, int c4) {
  asm volatile("cp.async.bulk.tensor.5d.shared::cluster.global.mbarrier::complete_tx::bytes [%0], [%1, {%3, %4, %5, %6, %7}], [%2];"
               ::"r"(dst), "l"(m), "r"(bar), "r"(c0), "r"(c1), "r"(c2), "r"(c3), "r"(c4) : "memory");
}
__device__ __forceinline__ void bulk_load(uint32_t dst, const void* src, uint32_t bytes, uint32_t bar) {
  asm volatile("cp.async.bulk.shared::cluster.global.mbarrier::complete_tx::bytes [%0], [%1], %2, [%3];"
               ::"r"(dst), "l"(src), "r"(bytes), "r"(bar) : "memory");
}
__device__ __forceinline__ void l2_prefetch(const void* src, uint32_t bytes) {
  asm volatile("cp.async.bulk.prefetch.L2.global [%0], %1;" ::"l"(src), "r"(bytes) : "memory");
}
__device__ __forceinline__ void bar_sync(int id, int n) { asm volatile("bar.sync %0, %1;" ::"r"(id), "r"(n) : "memory"); }
__device__ __forceinline__ void bar_arrive(int id, int n) { asm volatile("bar.arrive %0, %1;" ::"r"(id), "r"(n) : "memory"); }
__device__ __forceinline__ void fence_async_smem() { asm volatile("fence.proxy.async.shared::cta;" ::: "memory"); }
__device__ __forceinline__ void fence_async_global() { asm volatile("fence.proxy.async.global;" ::: "memory"); }
__device__ __forceinline__ void flag_add(int f) {
  asm volatile("red.relaxed.gpu.global.add.u32 [%0], 1;" ::"l"(g_flag + f * 32) : "memory");
}
__device__ __forceinline__ void flag_release(int f) {
  asm volatile("fence.release.gpu;" ::: "memory");
  flag_add(f);
}
__device__ __forceinline__ unsigned ld_relaxed(const unsigned* p) {
  unsigned v;
  asm volatile("ld.relaxed.gpu.global.u32 %0, [%1];" : "=r"(v) : "l"(p) : "memory");
  return v;
}
__device__ __forceinline__ void wait_clock(unsigned t) {
  int d;
  while ((d = (int)(t - (unsigned)clock())) > 0) __nanosleep(d > 600 ? 200 : 40);
}
__device__ __forceinline__ uint32_t pack2(float lo, float hi) {
  uint32_t r;
  asm("cvt.rn.bf16x2.f32 %0, %1, %2;" : "=r"(r) : "f"(hi), "f"(lo));
  return r;
}
__device__ __forceinline__ float bf_lo(uint32_t v) { return __uint_as_float(v << 16); }
__device__ __forceinline__ float bf_hi(uint32_t v) { return __uint_as_float(v & 0xffff0000u); }
__device__ __forceinline__ float bf_round(float v) { return __bfloat162float(__float2bfloat16_rn(v)); }
__device__ __forceinline__ uint32_t hmul2(uint32_t a, uint32_t b) {
  uint32_t r;
  asm("mul.rn.bf16x2 %0, %1, %2;" : "=r"(r) : "r"(a), "r"(b));
  return r;
}
__device__ __forceinline__ uint32_t hadd2(uint32_t a, uint32_t b) {
  uint32_t r;
  asm("add.rn.bf16x2 %0, %1, %2;" : "=r"(r) : "r"(a), "r"(b));
  return r;
}
__device__ __forceinline__ uint32_t hsub2(uint32_t a, uint32_t b) {
  uint32_t r;
  asm("sub.rn.bf16x2 %0, %1, %2;" : "=r"(r) : "r"(a), "r"(b));
  return r;
}
__device__ __forceinline__ uint32_t hfma2(uint32_t a, uint32_t b, uint32_t c) {
  uint32_t r;
  asm("fma.rn.bf16x2 %0, %1, %2, %3;" : "=r"(r) : "r"(a), "r"(b), "r"(c));
  return r;
}
__device__ __forceinline__ uint32_t hneg2(uint32_t a) {
  uint32_t r;
  asm("neg.bf16x2 %0, %1;" : "=r"(r) : "r"(a));
  return r;
}
__device__ __forceinline__ uint4 ldg128(const void* p) {
  uint4 v;
  asm volatile("ld.global.nc" LDQ ".v4.u32 {%0,%1,%2,%3}, [%4];" : "=r"(v.x), "=r"(v.y), "=r"(v.z), "=r"(v.w) : "l"(p));
  return v;
}
__device__ __forceinline__ uint2 ldg64(const void* p) {
  uint2 v;
  asm volatile("ld.global.nc.v2.u32 {%0,%1}, [%2];" : "=r"(v.x), "=r"(v.y) : "l"(p));
  return v;
}
__device__ __forceinline__ void stg128(void* p, uint32_t a, uint32_t b, uint32_t c, uint32_t d) {
  asm volatile("st.global.v4.u32 [%0], {%1,%2,%3,%4};" ::"l"(p), "r"(a), "r"(b), "r"(c), "r"(d) : "memory");
}
__device__ __forceinline__ void sts128(uint32_t a, uint32_t x, uint32_t y, uint32_t z, uint32_t w) {
  asm volatile("st.shared.v4.u32 [%0], {%1,%2,%3,%4};" ::"r"(a), "r"(x), "r"(y), "r"(z), "r"(w) : "memory");
}
__device__ __forceinline__ uint32_t lds32(uint32_t a) {
  uint32_t v;
  asm volatile("ld.shared.u32 %0, [%1];" : "=r"(v) : "r"(a) : "memory");
  return v;
}
__device__ __forceinline__ uint4 lds128(uint32_t a) {
  uint4 v;
  asm volatile("ld.shared.v4.u32 {%0,%1,%2,%3}, [%4];" : "=r"(v.x), "=r"(v.y), "=r"(v.z), "=r"(v.w) : "r"(a) : "memory");
  return v;
}
__device__ __forceinline__ void stsm4(uint32_t a, uint32_t x, uint32_t y, uint32_t z, uint32_t w) {
  asm volatile("stmatrix.sync.aligned.m8n8.x4.shared.b16 [%0], {%1,%2,%3,%4};" ::"r"(a), "r"(x), "r"(y), "r"(z), "r"(w) : "memory");
}
__device__ __forceinline__ void stsm4t(uint32_t a, uint32_t x, uint32_t y, uint32_t z, uint32_t w) {
  asm volatile("stmatrix.sync.aligned.m8n8.x4.trans.shared.b16 [%0], {%1,%2,%3,%4};" ::"r"(a), "r"(x), "r"(y), "r"(z), "r"(w) : "memory");
}
__device__ __forceinline__ uint4 ldsm4t(uint32_t a) {
  uint4 v;
  asm volatile("ldmatrix.sync.aligned.m8n8.x4.trans.shared.b16 {%0,%1,%2,%3}, [%4];" : "=r"(v.x), "=r"(v.y), "=r"(v.z), "=r"(v.w) : "r"(a) : "memory");
  return v;
}
struct cx { float r, i; };
__device__ __forceinline__ cx cmul(cx a, cx b) { return {a.r * b.r - a.i * b.i, a.r * b.i + a.i * b.r}; }
__device__ __forceinline__ cx cfma(cx a, cx b, cx c) { return {fmaf(a.r, b.r, fmaf(-a.i, b.i, c.r)), fmaf(a.r, b.i, fmaf(a.i, b.r, c.i))}; }
__device__ __forceinline__ cx csq(cx a) { return {a.r * a.r - a.i * a.i, 2.f * a.r * a.i}; }
__device__ __forceinline__ cx unit(int num, int den) {
  int m = num & (den - 1);
  if (m >= den / 2) m -= den;
  float s, c;
  __sincosf((float)m * (-6.283185307179586f / (float)den), &s, &c);
  return {c, s};
}

__device__ __forceinline__ uint2 lds64(uint32_t a) {
  uint2 v;
  asm volatile("ld.shared.v2.u32 {%0,%1}, [%2];" : "=r"(v.x), "=r"(v.y) : "r"(a) : "memory");
  return v;
}
__device__ __forceinline__ void prep_taps(const uint4 (&sh)[2], uint32_t (&s)[2][4]) {
#pragma unroll
  for (int e = 0; e < 2; e++) {
    s[e][0] = __byte_perm(sh[e].x, sh[e].z, 0x5410); s[e][1] = __byte_perm(sh[e].x, sh[e].z, 0x7632);
    s[e][2] = __byte_perm(sh[e].y, sh[e].w, 0x5410); s[e][3] = __byte_perm(sh[e].y, sh[e].w, 0x7632);
  }
}
__device__ __forceinline__ void prep_math(const uint2 (&kk)[11], uint2 (&vv)[8], const uint32_t (&s)[2][4]) {
#pragma unroll
  for (int i = 0; i < 8; i++)
#pragma unroll
    for (int e = 0; e < 2; e++) {
      uint32_t a = hmul2((&kk[i].x)[e], s[e][3]);
      a = hfma2((&kk[i + 1].x)[e], s[e][2], a);
      a = hfma2((&kk[i + 2].x)[e], s[e][1], a);
      a = hfma2((&kk[i + 3].x)[e], s[e][0], a);
      (&vv[i].x)[e] = hmul2(a, (&vv[i].x)[e]);
    }
}
__device__ __forceinline__ void prep_store(const uint2 (&vv)[8], int d, int tb) {
  uint4* dst = g_u + (size_t)((d >> 5) * 32 + (tb >> 3)) * 256 + (d & 31) * 8 + ((tb & 7) ^ ((tb >> 3) & 1));
#pragma unroll
  for (int e = 0; e < 2; e++) {
#define U(i) (&vv[i].x)[e]
    stg128(dst + (2 * e) * 8, __byte_perm(U(0), U(1), 0x5410), __byte_perm(U(2), U(3), 0x5410),
           __byte_perm(U(4), U(5), 0x5410), __byte_perm(U(6), U(7), 0x5410));
    stg128(dst + (2 * e + 1) * 8, __byte_perm(U(0), U(1), 0x7632), __byte_perm(U(2), U(3), 0x7632),
           __byte_perm(U(4), U(5), 0x7632), __byte_perm(U(6), U(7), 0x7632));
#undef U
  }
}
template <int PG>
__device__ __forceinline__ void prep(const Ptrs& p, int ti, int pj, int w, int lane) {
  const int tb = lane & 7, chunk = 2 * w + (lane >> 4), ch = chunk * 8 + ((lane >> 3) & 1) * 4, d = pj * 128 + PG * 64 + ch;
  const uint4 sh[2] = {ldg128(p.shift + d * 4), ldg128(p.shift + d * 4 + 8)};
  uint32_t s[2][4];
  prep_taps(sh, s);
#pragma unroll 1
  for (int th = 0; th < 2; th++) {
    uint2 kk[11], vv[8];
    {
      const uint32_t in = S_STG + th * 16384 + (lane & 8);
      const uint32_t a0 = in + tb * 128 + ((chunk ^ tb) << 4);
      const uint32_t hb = tb ? in + (39 + tb) * 128 + ((chunk ^ (tb - 1)) << 4) : S_T + (PG * 2 + th) * 512 + ch * 2;
      const uint32_t hs = tb ? 1024 : 128;
      mbar_wait_long(B_PIN + 16 * PG + 8 * th, 0);
      if (th) TIM(29 + PG);
#pragma unroll
      for (int i = 0; i < 3; i++) kk[i] = lds64(hb + i * hs);
#pragma unroll
      for (int i = 0; i < 8; i++) { kk[3 + i] = lds64(a0 + i * 1024); vv[i] = lds64(a0 + 8192 + i * 1024); }
      prep_math(kk, vv, s);
      sched_fence<52 + PG>();
    }
    if (!PG) bar_arrive(th ? 11 : 3, 160);
    else if (elect_one()) mbar_arrive(B_SFREE + 8 * th);
    prep_store(vv, d, ti * 16 + th * 8 + tb);
  }
  bar_arrive(4 + PG, 160);
}

__device__ __forceinline__ int gate_step(int pj) { return pj ? 2 * pj : 16; }
__device__ __forceinline__ void gate_partial(const Ptrs& p, uint32_t tag, int ti, int pj, int w, int lane) {
  const int ck = lane & 7, s0 = gate_step(pj);
  const uint4 gw[2] = {ldg128(p.gw + pj * 128 + ck * 8), ldg128(p.gw + pj * 128 + 64 + ck * 8)};
  float s[8];
  mbar_wait_long(B_GATE, 0);
#pragma unroll
  for (int h = 0; h < 2; h++) {
    const int sl = (s0 + h) % NS;
    mbar_wait(B_FULL + 8 * sl, ((s0 + h) / NS) & 1);
#pragma unroll
    for (int i = 0; i < 8; i++) {
      const uint4 x = lds128(sb + sl * STAGE + 16384 + (32 * w + (lane >> 3) * 8 + i) * 128 + ((ck ^ i) << 4));
      const uint32_t q = hfma2(x.x, gw[h].x, hfma2(x.y, gw[h].y, hfma2(x.z, gw[h].z, hmul2(x.w, gw[h].w))));
      s[i] = h ? s[i] + (bf_lo(q) + bf_hi(q)) : bf_lo(q) + bf_hi(q);
    }
  }
  fence_async_smem();
  __syncwarp();
  if (elect_one()) mbar_arrive(B_GATE + 8);
#pragma unroll
  for (int o = 4; o > 0; o >>= 1)
#pragma unroll
    for (int i = 0; i < o; i++) {
      const bool up = ck & o;
      s[i] = (up ? s[i + o] : s[i]) + __shfl_xor_sync(~0u, up ? s[i] : s[i + o], o);
    }
  const int j = 4 * w + (lane >> 3);
  asm volatile("st.relaxed.gpu.global.u32 [%0], %1;" ::"l"(g_gate + pj * SEQ + ti * 128 + 32 * (ck >> 1) + 2 * j + (ck & 1)),
               "r"((__float_as_uint(s[0]) & ~3u) | tag) : "memory");
}
__device__ __forceinline__ void gate_finish(int ti, int tid) {
  const uint32_t tag = (lds32(S_EP) + 1) & 3;
  float l;
  int n = SPIN_LIMIT;
  bool bad;
  do {
    uint32_t v[8], x = 0;
#pragma unroll
    for (int j = 0; j < 8; j++) v[j] = ld_relaxed(g_gate + j * SEQ + ti * 128 + tid);
    l = 0.f;
#pragma unroll
    for (int j = 0; j < 8; j++) { x |= v[j] ^ tag; l += __uint_as_float(v[j]); }
    bad = __any_sync(~0u, x & 3);
  } while (bad && --n);
  trap_if(n == 0);
  const float g = bf_round(__fdividef(1.f, 1.f + __expf(-bf_round(l))));
  asm volatile("st.shared.f32 [%0], %1;" ::"r"(S_G + tid * 4), "f"(g) : "memory");
}

__device__ __forceinline__ void conv_tables(int tid) {
  {
    const int s = tid >> 5, n1 = tid & 31;
    uint32_t re[4], im[4];
#pragma unroll
    for (int e = 0; e < 4; e++) {
      cx a = unit(n1 * (4 * (8 * s + 2 * e) + 1), 128), b = unit(n1 * (4 * (8 * s + 2 * e + 1) + 1), 128);
      re[e] = pack2(a.r * 0.125f, b.r * 0.125f); im[e] = pack2(a.i * 0.125f, b.i * 0.125f);
    }
    sts128(S_M1 + (2 * s) * 512 + n1 * 16, re[0], re[1], re[2], re[3]);
    sts128(S_M1 + (2 * s + 1) * 512 + n1 * 16, im[0], im[1], im[2], im[3]);
  }
  {
    const int kg = tid >> 5, n = tid & 31;
    const int pi = kg >> 1, po = n >> 4, f2 = n & 15;
    uint32_t fw[4];
#pragma unroll
    for (int e = 0; e < 4; e++) {
      int n2 = (kg & 1) * 8 + 2 * e;
      cx a = unit(n2 * f2, 16), b = unit((n2 + 1) * f2, 16);
      float sg = pi ? -1.f : 1.f;
      float x0 = (pi == po) ? a.r : sg * a.i, x1 = (pi == po) ? b.r : sg * b.i;
      fw[e] = pack2(x0, x1);
    }
    sts128(S_M2 + kg * 512 + n * 16, fw[0], fw[1], fw[2], fw[3]);
  }
  fence_async_smem();
}
__device__ __forceinline__ constexpr int jj_of(int o) { return o == 7 ? 3 : o + (o >= 3); }
__device__ __forceinline__ int conv_chan(int ti, int pj, int jj) { return pj * 128 + jj * 16 + ti; }

struct ConvCtx {
  uint32_t buf, inbar;
  int nb, n;
  int ti, pj, j;
  __device__ __forceinline__ int chan(int c) const {
    return j < 0 ? conv_chan(ti, pj, jj_of(c)) : conv_chan((j + 12 * c) >> 3, (j + 12 * c) & 7, 3);
  }
};
__device__ __forceinline__ ConvCtx conv_ctx(int spare, int wg, int ti, int pj) {
  const int j = spare < 0 ? -1 : spare * 3 + wg;
  return {wg == 2 ? S_CIN : sb + wg * 32768, wg == 2 ? B_CINF : (wg ? B_PIN : B_FULL), 4 + 4 * wg, j < 0 ? 7 : (j < 8 ? 11 : 10), ti, pj, j};
}
#define CDESC(a) mkdesc(dlo(a, 512), 128, 0)
struct ConvTw { uint32_t r[2], i[2], n[2]; };

__device__ __forceinline__ void cv_tw1(float (&d)[64], uint32_t (&R)[16], uint32_t (&I)[16], const ConvTw& t, int i) {
#pragma unroll
  for (int j = 8 * (i & 1); j < 8 * (i & 1) + 8; j++) {
    if (i < 2) {
      R[j] = pack2(d[4 * j], d[4 * j + 1]); I[j] = pack2(d[4 * j + 2], d[4 * j + 3]);
    } else {
      const uint32_t xr = R[j], xi = I[j];
      R[j] = hfma2(xr, t.r[j & 1], hmul2(xi, t.n[j & 1]));
      I[j] = hfma2(xr, t.i[j & 1], hmul2(xi, t.r[j & 1]));
    }
  }
}
template <int N>
__device__ __forceinline__ void cv_pack(float (&X)[16], uint32_t (&P)[N][2][2], int q) {
#pragma unroll
  for (int k = 0; k < 2; k++)
#pragma unroll
    for (int j = 0; j < 4; j++) P[2 * q + k][j >> 1][j & 1] = pack2(X[4 * j + 2 * k], X[4 * j + 2 * k + 1]);
}
__device__ __forceinline__ void cv_overlap(uint32_t (&P)[8][2][2]) {
#pragma unroll
  for (int k = 3; k > 0; k--)
#pragma unroll
    for (int hh = 0; hh < 2; hh++) {
      P[k][0][hh] = hsub2(P[k][0][hh], P[k - 1][1][hh]);
      P[k][1][hh] = hadd2(P[k][1][hh], P[k - 1][0][hh]);
    }
}
__device__ __forceinline__ void cv_pw(uint32_t (&P)[8][2][2], uint32_t (&Q)[4][2][2]) {
#pragma unroll
  for (int jh = 0; jh < 8; jh++) {
    const int j = jh >> 1, hh = jh & 1;
    uint32_t qr = hmul2(P[4 + j][0][hh], P[0][0][hh]), qi = hmul2(P[4 + j][0][hh], P[0][1][hh]);
    qr = hfma2(hneg2(P[4 + j][1][hh]), P[0][1][hh], qr);
    qi = hfma2(P[4 + j][1][hh], P[0][0][hh], qi);
#pragma unroll
    for (int k = j - 1; k >= 0; k--) {
      qr = hfma2(P[4 + k][0][hh], P[j - k][0][hh], qr);
      qi = hfma2(P[4 + k][0][hh], P[j - k][1][hh], qi);
      qr = hfma2(hneg2(P[4 + k][1][hh]), P[j - k][1][hh], qr);
      qi = hfma2(P[4 + k][1][hh], P[j - k][0][hh], qi);
    }
    Q[j][0][hh] = qr; Q[j][1][hh] = qi;
  }
}
__device__ __forceinline__ void cv_tw2(uint32_t (&Q)[4][2][2], const ConvTw& t, int k) {
#pragma unroll
  for (int hh = 0; hh < 2; hh++) {
    const uint32_t xr = Q[k][0][hh], xi = Q[k][1][hh];
    Q[k][0][hh] = hfma2(xr, t.r[hh], hmul2(xi, t.i[hh]));
    Q[k][1][hh] = hfma2(xr, t.n[hh], hmul2(xi, t.r[hh]));
  }
}
__device__ __forceinline__ void cv_out0(float (&Y)[16], uint32_t T, int w, int lane) {
  reg_fence(Y);
  const uint32_t za = T + w * 2048 + (lane >> 4) * 256 + (lane & 7) * 32 + ((lane >> 3) & 1) * 16;
#pragma unroll
  for (int jj = 0; jj < 2; jj++)
    stsm4t(za + jj * 512, pack2(Y[8 * jj], Y[8 * jj + 1]), pack2(Y[8 * jj + 2], Y[8 * jj + 3]),
           pack2(Y[8 * jj + 4], Y[8 * jj + 5]), pack2(Y[8 * jj + 6], Y[8 * jj + 7]));
}

__device__ __forceinline__ void cv_out1(const uint4& z0, const uint4& z1, const ConvCtx& cc, uint32_t keep, uint32_t tag, int ch, int w, int lane) {
  uint4* zp = g_z + (size_t)cc.chan(ch) * 256 + w * 64 + lane;
#define TG(v) ((v & keep) | (tag & ~keep))
  asm volatile("st.relaxed.gpu.global.v4.u32 [%0], {%1,%2,%3,%4};" ::"l"(zp), "r"(TG(z0.x)), "r"(TG(z0.y)), "r"(TG(z0.z)), "r"(TG(z0.w)) : "memory");
  asm volatile("st.relaxed.gpu.global.v4.u32 [%0], {%1,%2,%3,%4};" ::"l"(zp + 32), "r"(TG(z1.x)), "r"(TG(z1.y)), "r"(TG(z1.z)), "r"(TG(z1.w)) : "memory");
#undef TG
}
template <bool FW, bool BW, int K>
__device__ __forceinline__ void conv_step(uint32_t (&Q)[4][2][2], const ConvTw& t, const ConvCtx& cc, float dl, uint32_t tag, int ch, int w, int lane) {
#define SF(n) if ((SFM >> (n)) & 1) sched_fence_async<K + (n)>()
  float d[64], X[4][16], Z[2][16], Y[16];
  uint32_t R[16], I[16];
  uint4 a[4];
  const int nx = ch + 1;
  const uint32_t T = cc.buf + 16384;
  float dv;
  TIMC(1);
  if (FW) {
    dv = __shfl_sync(~0u, dl, nx);
    mbar_wait(cc.inbar + 8 * (nx & 1), (nx >> 1) & 1);
  }
  TIMC(2);
  WG_FENCE();
  if (BW) {
#pragma unroll
    for (int q = 0; q < 2; q++) {
      wgmma_rs32<0, 1>(Z[q], Q[2 * q][0][0], Q[2 * q + 1][0][0], Q[2 * q][0][1], Q[2 * q + 1][0][1], mkdesc(dlo(S_M2, 128), 512, 0));
      wgmma_rs32<1, 1>(Z[q], Q[2 * q][1][0], Q[2 * q + 1][1][0], Q[2 * q][1][1], Q[2 * q + 1][1][1], mkdesc(dlo(S_M2 + 256, 128), 512, 0));
    }
    WG_COMMIT();
  }
  if (FW) {
    const uint32_t lo = dlo(0, 1024) + (cc.buf >> 4) + (nx & 1) * 512;
    wgmma_ss128<1, 1, 0>(d, mkdesc(dlo(S_M1, 128), 512, 0), mkdesc(lo, 256, 3));
    wgmma_ss128<1, 1, 1>(d, mkdesc(dlo(S_M1 + 256, 128), 512, 0), mkdesc(lo + 32, 256, 3));
    WG_COMMIT();
  }
  TIMC(3);
  if (BW) {
    TIMC(4);
    WG_WAIT(FW ? 1 : 0);
    TIMC(5);
    reg_fence(Z[0]); reg_fence(Z[1]);
    uint32_t V[4][2][2];
    cv_pack(Z[0], V, 0); cv_pack(Z[1], V, 1);
    SF(0);
#pragma unroll
    for (int k = 0; k < 4; k++) cv_tw2(V, t, k);
    bar_sync(cc.nb, 128);
#pragma unroll
    for (int k = 0; k < 4; k++) stsm4(T + w * 512 + lane * 16 + k * 2048, V[k][0][0], V[k][0][1], V[k][1][0], V[k][1][1]);
    SF(1);
    TIMC(6);
  }
  if (FW) {
    WG_WAIT(0);
    reg_fence(d);
    if (nx + 2 < cc.n) bar_arrive(cc.nb + 2 + (nx & 1), 160);
    cv_tw1(d, R, I, t, 0); cv_tw1(d, R, I, t, 1);
    SF(2);
    TIMC(7);
  }
  if (BW) {
    bar_sync(cc.nb, 128);
#pragma unroll
    for (int s = 0; s < 4; s++) a[s] = ldsm4t(T + (4 * w + s) * 512 + lane * 16);
  }
  if (FW) { cv_tw1(d, R, I, t, 2); cv_tw1(d, R, I, t, 3); }
  sched_fence<K + 3>();
  TIMC(8);
  WG_FENCE();
  if (BW) {
    wgmma_rs32<0>(Y, a[0].x, a[0].y, a[0].z, a[0].w, CDESC(S_M1));
#pragma unroll
    for (int i = 1; i < 4; i++) wgmma_rs32<1>(Y, a[i].x, a[i].y, a[i].z, a[i].w, CDESC(S_M1 + 1024 * i));
  }
  if (FW) {
#pragma unroll
    for (int q = 0; q < 4; q++) {
      if (q == 2) WG_COMMIT();
      wgmma_rs32<0>(X[q], R[4 * q], R[4 * q + 2], R[4 * q + 1], R[4 * q + 3], CDESC(S_M2));
      wgmma_rs32<1>(X[q], I[4 * q], I[4 * q + 2], I[4 * q + 1], I[4 * q + 3], CDESC(S_M2 + 1024));
    }
  }
  WG_COMMIT();
  TIMC(9);
  WG_WAIT(FW ? 1 : 0);
  TIMC(10);
  uint4 z0, z1;
  if (BW) {
    cv_out0(Y, T, w, lane);
    __syncwarp();
    z0 = lds128(T + w * 2048 + lane * 16); z1 = lds128(T + w * 2048 + 512 + lane * 16);
  }
  if (FW) {
    uint32_t P[8][2][2];
    reg_fence(X[0]); reg_fence(X[1]);
    cv_pack(X[0], P, 0); cv_pack(X[1], P, 1);
    cv_overlap(P);
    if (BW) cv_out1(z0, z1, cc, cc.j < 0 ? ~0u : ~1u, tag, ch, w, lane);
    sched_fence_async<K + 7>();
    WG_WAIT(0);
    reg_fence(X[2]); reg_fence(X[3]);
    X[2][0] += dv; X[2][1] += dv; X[2][4] += dv; X[2][5] += dv;
    cv_pack(X[2], P, 2); cv_pack(X[3], P, 3);
    SF(4);
    TIMC(11);
    cv_pw(P, Q);
  } else {
    cv_out1(z0, z1, cc, ~1u, tag, ch, w, lane);
  }
  sched_fence<K + 5>();
  TIMC(13);
#undef SF
}

__device__ __forceinline__ void conv_main(const Ptrs& p, const ConvCtx& cc, int eb, int tid) {
  const int ti = cc.ti, pj = cc.pj;
  const int w = tid >> 5, lane = tid & 31;
  ConvTw t;
#pragma unroll
  for (int hh = 0; hh < 2; hh++) {
    const int n2 = 8 * hh + 2 * (lane & 3), m = 4 * (8 * w + (lane >> 2)) + 1;
    cx a = unit(n2 * m, 2048), b = unit((n2 + 1) * m, 2048);
    t.r[hh] = pack2(a.r, b.r); t.i[hh] = pack2(a.i, b.i); t.n[hh] = pack2(-a.i, -b.i);
  }
  const uint32_t tag = (ld_relaxed(g_epoch + eb) + 1) & 3;
  const float dl = 0.125f * __bfloat162float(p.ssmd[cc.chan(min(lane, cc.n - 1))]);
  if (cc.j < 0) {
    gate_partial(p, tag, ti, pj, w, lane);
    prep<1>(p, ti, pj, w, lane);
  }
  {
    uint32_t P[4][2][2];
    mbar_wait_long(cc.inbar, 0);
    TIM(20);
    conv_step<true, false, 10>(P, t, cc, dl, tag, -1, w, lane);
#pragma unroll 1
    for (int ch = 0; ch < cc.n - 1; ch++) {
      conv_step<true, true, 20>(P, t, cc, dl, tag, ch, w, lane);
      if (cc.j < 0 && (ch == 3 || ch == 5)) bar_arrive(ch == 3 ? 0 : 11, 160);
      if (ch == 0) TIM(21);
    }
    conv_step<false, true, 30>(P, t, cc, dl, tag, cc.n - 1, w, lane);
  }
  TIM(22);
}

__device__ __forceinline__ cx csel(bool k, cx a, cx b) { return {k ? a.r : b.r, k ? a.i : b.i}; }
__device__ __forceinline__ void ld2cx(uint32_t a, cx& x, cx& y) {
  const uint4 v = lds128(a);
  x = {__uint_as_float(v.x), __uint_as_float(v.y)};
  y = {__uint_as_float(v.z), __uint_as_float(v.w)};
}
__device__ __forceinline__ cx ldcx(uint32_t a) {
  cx x;
  asm volatile("ld.shared.v2.f32 {%0,%1}, [%2];" : "=f"(x.r), "=f"(x.i) : "r"(a) : "memory");
  return x;
}

__device__ __forceinline__ void scan_epilogue(float (&aR)[64], float (&aI)[64], uint32_t last_empty, int ph, int ti, int pj, int tid) {
  const int w = tid >> 5, lane = tid & 31, r = lane >> 2, c = lane & 3;
  const uint32_t par = S_PAR + (ph * 64 + 16 * w + r) * 16;
  uint4* agg = g_agg + ph * 16 * 256 + pj * 32 + 8 * w + r;
  const uint32_t tag = (lds32(S_EP) + 1) & 3;
  cx h[2];
  {
    cx lam[2], a[2];
#pragma unroll
    for (int q = 0; q < 2; q++) { lam[q] = ldcx(par + q * 128); h[q] = ldcx(par + 2048 + q * 128); }
    WG_WAIT(0);
    if (elect_one()) mbar_arrive(last_empty);
    asm volatile("setmaxnreg.inc.sync.aligned.u32 168;");
    reg_fence(aR); reg_fence(aI);
    TIM(3 + ph * 2);
#pragma unroll
    for (int q = 0; q < 2; q++) a[q] = {aR[2 * q], aI[2 * q]};
#pragma unroll
    for (int s = 1; s < 32; s++)
#pragma unroll
      for (int q = 0; q < 2; q++) {
        const int i = 4 * (s >> 1) + 2 * q + (s & 1);
        a[q] = cfma(lam[q], a[q], {aR[i], aI[i]});
      }
    sched_fence<1>();
    cx t[2][3];
#pragma unroll
    for (int q = 0; q < 2; q++)
#pragma unroll
      for (int k = 0; k < 3; k++) t[q][k] = {__shfl_up_sync(~0u, a[q].r, k + 1, 4), __shfl_up_sync(~0u, a[q].i, k + 1, 4)};
#pragma unroll
    for (int q = 0; q < 2; q++) {
      const cx z = {0.f, 0.f};
      cx ex = cfma(h[q], csel(c >= 3, t[q][2], z), csel(c >= 2, t[q][1], z));
      ex = cfma(h[q], ex, csel(c >= 1, t[q][0], z));
      a[q] = cfma(h[q], ex, a[q]);
      const cx u = cfma(lam[q], ex, {aR[2 * q], aI[2 * q]});
      aR[2 * q] = u.r; aI[2 * q] = u.i;
    }
    if (c == 3)
      asm volatile("st.relaxed.gpu.global.v4.u32 [%0], {%1,%2,%3,%4};" ::"l"(agg + ti * 256),
                   "r"((__float_as_uint(a[0].r) & ~3u) | tag), "r"((__float_as_uint(a[0].i) & ~3u) | tag),
                   "r"((__float_as_uint(a[1].r) & ~3u) | tag), "r"((__float_as_uint(a[1].i) & ~3u) | tag) : "memory");
    TIM(8 + ph * 4);
  }
  if (ti > 0) {
    const uint2* ap = (const uint2*)(agg + (ti - 1 - (c >> 1)) * 256) + (c & 1);
    const int cnt = ti - (c >> 1);
    const cx one = {1.f, 0.f};
    const cx l128 = ldcx(par + 2048 + 8 + (c & 1) * 128), l256 = csq(l128), fa = csel(c & 2, l128, one);
#pragma unroll
    for (int q = 0; q < 2; q++) h[q] = cmul(csel(c & 1, h[q], one), csel(c & 2, csq(h[q]), one));
    uint2 v[8];
    int n = SPIN_LIMIT;
    bool bad;
    __nanosleep(AGG_NS);
    TIM(27 + ph);
    do {
      uint32_t x = 0;
#pragma unroll
      for (int j = 0; j < 8; j++) {
        v[j] = make_uint2(tag, tag);
        asm volatile("{.reg .pred p; setp.lt.s32 p, %3, %4; @p ld.relaxed.gpu.global.v2.u32 {%0,%1}, [%2];}"
                     : "+r"(v[j].x), "+r"(v[j].y) : "l"(ap - j * 1024), "r"(2 * j), "r"(cnt) : "memory");
      }
#pragma unroll
      for (int j = 0; j < 8; j++) x |= (v[j].x ^ tag) | (v[j].y ^ tag);
      bad = __any_sync(~0u, x & 3);
    } while (bad && --n);
    trap_if(n == 0);
    cx a = {__uint_as_float(v[7].x), __uint_as_float(v[7].y)};
#pragma unroll
    for (int j = 6; j >= 0; j--) a = cfma(l256, a, {__uint_as_float(v[j].x), __uint_as_float(v[j].y)});
    a = cmul(a, fa);
    const cx t1 = {__shfl_xor_sync(~0u, a.r, 1), __shfl_xor_sync(~0u, a.i, 1)};
    const cx t2 = {__shfl_xor_sync(~0u, a.r, 2), __shfl_xor_sync(~0u, a.i, 2)};
    const cx t3 = {__shfl_xor_sync(~0u, a.r, 3), __shfl_xor_sync(~0u, a.i, 3)};
    const cx own = {a.r + t2.r, a.i + t2.i}, oth = {t1.r + t3.r, t1.i + t3.i};
#pragma unroll
    for (int q = 0; q < 2; q++) h[q] = cmul(csel((c & 1) == q, own, oth), h[q]);
  } else {
    h[0] = h[1] = {0.f, 0.f};
  }
  TIM(9 + ph * 4);
  cx lam[2];
  uint32_t cr[2], nci[2];
#pragma unroll
  for (int q = 0; q < 2; q++) {
    const uint4 v = lds128(par + q * 128);
    lam[q] = {__uint_as_float(v.x), __uint_as_float(v.y)};
    cr[q] = v.z; nci[q] = v.w;
  }
  mbar_wait(B_SFREE + 16 * ph, 0);
  const uint32_t hs = S_STG + w * 1024 + r * 64 + ((c ^ (r >> 1)) << 4);
  uint4* hg = g_h + (size_t)(ti * 32 + ph * 16 + pj) * 1024 + w * 64 + r * 4 + (c ^ (r >> 1));
  uint32_t pr[4][2][4], pi[4][2][4];
#pragma unroll
  for (int i = 0; i < 4; i++) {
    uint32_t o[2][4];
#pragma unroll
    for (int s2 = 0; s2 < 4; s2++)
#pragma unroll
      for (int q = 0; q < 2; q++) {
        const int k = 4 * (4 * i + s2) + 2 * q;
        cx h0 = cfma(lam[q], h[q], {aR[k], aI[k]});
        h[q] = cfma(lam[q], h0, {aR[k + 1], aI[k + 1]});
        pr[i][q][s2] = pack2(h0.r, h[q].r);
        pi[i][q][s2] = pack2(h0.i, h[q].i);
        o[q][s2] = hfma2(pr[i][q][s2], cr[q], hmul2(pi[i][q][s2], nci[q]));
      }
#pragma unroll
    for (int q = 0; q < 2; q++) {
      stg128(hg + i * 256 + q * 32, o[q][0], o[q][1], o[q][2], o[q][3]);
      sts128(hs + i * 4096 + q * 512, o[q][0], o[q][1], o[q][2], o[q][3]);
    }
    if (i == 0) sched_fence<7>();
    if (i == 1) sched_fence<8>();
    if (i == 2) sched_fence<6>();
  }
  bar_arrive(9, 160);
  sched_fence<9>();
  TIM(10 + ph * 4);
  if (ph == 0) mbar_wait(B_SFREE + 8, 0);
#pragma unroll
  for (int q = 0; q < 2; q++) {
    const uint32_t ncr = cr[q] ^ 0x80008000u;
#pragma unroll
    for (int i = 0; i < 4; i++) {
      uint32_t o[4];
#pragma unroll
      for (int s2 = 0; s2 < 4; s2++) o[s2] = hfma2(pi[i][q][s2], ncr, hmul2(pr[i][q][s2], nci[q]));
      sts128(hs + 16384 + i * 4096 + q * 512, o[0], o[1], o[2], o[3]);
      if (IM_NS) __nanosleep(IM_NS);
      stg128(hg + 8192 + i * 256 + q * 32, o[0], o[1], o[2], o[3]);
    }
  }
  fence_async_smem();
  __syncwarp();
  if (elect_one()) mbar_arrive(B_LOC + 8 * ph);
  bar_arrive(10, 160);
  bar_sync(1 + ph, 128);
  asm volatile("setmaxnreg.dec.sync.aligned.u32 160;");
}

__device__ __forceinline__ constexpr uint32_t e_addr(int o, int mh) { return S_STG + (o * 2 + mh) * 2048; }
__device__ __forceinline__ void eterm(const Ptrs& p, int ti, int pj, int tid) {
  const int w = tid >> 5, lane = tid & 31, r = lane >> 2, c = lane & 3;
  const int trow = 64 * (w & 1) + 8 * (w >> 1) + r;
  const int rs = 2 * (r & 3) + (r >> 2);
  uint2 xv[2][8][2], ds[8];
#pragma unroll
  for (int jj = 0; jj < 8; jj++) ds[jj] = ldg64(p.dskip + pj * 128 + 16 * jj + 4 * c);
  gate_finish(ti, tid);
#pragma unroll
  for (int g = 0; g < 2; g++) {
    mbar_wait_long(B_XT + 8 * g, 0);
#pragma unroll
    for (int i = 0; i < 4; i++)
#pragma unroll
      for (int jj = 4 * g; jj < 4 * g + 4; jj++)
        xv[i >> 1][jj][i & 1] = lds64(sb + ((48 + g) % NS) * STAGE + (trow - r + rs + 16 * (i >> 1) + 32 * (i & 1)) * 128 + (((2 * (jj & 3) + (c >> 1)) ^ rs) << 4) + (c & 1) * 8);
  }
  fence_async_smem();
  __syncwarp();
  if (elect_one()) mbar_arrive(B_XT + 16);
  bar_sync(2, 128);
  TIM(31);
  uint32_t g2[2][2], og2[2][2];
#pragma unroll
  for (int mh = 0; mh < 2; mh++)
#pragma unroll
    for (int hf = 0; hf < 2; hf++) {
      uint32_t g;
      asm volatile("ld.shared.u32 %0, [%1];" : "=r"(g) : "r"(S_G + (trow + 16 * mh + 32 * hf) * 4) : "memory");
      g2[mh][hf] = __byte_perm(g, g, 0x3232);
      og2[mh][hf] = hsub2(0x3f803f80u, g2[mh][hf]);
    }
  const int dl = lane & 15;
  const uint32_t za = S_STG + (w & 1) * 2048 + dl * 128;
#pragma unroll
  for (int g = 0; g < 3; g++) {
    const int o0 = g ? 2 + 2 * g : 0, o1 = 4 + 2 * g;
    if (g < 2) {
      mbar_wait_long(B_ZT + 8 * g, 0);
    } else {
      const uint32_t tag = (lds32(S_EP) + 1) & 1;
      const int n = tid >> 4, ck = tid & 15;
      const uint4* zp = g_z + (size_t)(pj * 128 + 4 * (n >> 1) + (n & 1)) * 256 + ti * 16 + ck;
      uint4 v[4];
      int it = SPIN_LIMIT;
      bool bad;
      do {
        uint32_t x = 0;
#pragma unroll
        for (int i = 0; i < 4; i++)
          asm volatile("ld.relaxed.gpu.global.v4.u32 {%0,%1,%2,%3}, [%4];" : "=r"(v[i].x), "=r"(v[i].y), "=r"(v[i].z), "=r"(v[i].w)
                       : "l"(zp + (jj_of(6 + (i >> 1)) * 16 + 2 * (i & 1)) * 256) : "memory");
#pragma unroll
        for (int i = 0; i < 4; i++) {
          v[i].x ^= tag; v[i].y ^= tag; v[i].z ^= tag; v[i].w ^= tag;
          x |= v[i].x | v[i].y | v[i].z | v[i].w;
        }
        bad = __any_sync(~0u, x & 1);
        if (bad) __nanosleep(ZL_NS);
      } while (bad && --it);
      trap_if(it == 0);
#pragma unroll
      for (int i = 0; i < 4; i++)
        sts128(S_STG + (6 + (i >> 1)) * 4096 + (ck >> 3) * 2048 + (8 * (i & 1) + n) * 128 + (((ck & 7) ^ n) << 4), v[i].x, v[i].y, v[i].z, v[i].w);
      bar_sync(2, 128);
    }
    if (g == 2) TIM(16);
#pragma unroll
    for (int mh = 0; mh < 2; mh++) {
      const uint32_t zb = za + (((4 * (lane >> 4) + 2 * mh + (w >> 1)) ^ (dl & 7)) << 4);
#pragma unroll
      for (int o = o0; o < o1; o++) {
        const int jj = jj_of(o);
        uint4 z = ldsm4t(zb + o * 4096);
#pragma unroll
        for (int hf = 0; hf < 2; hf++) {
          uint2& x = xv[mh][jj][hf];
          x.x = hmul2(x.x, hfma2(og2[mh][hf], hf ? z.z : z.x, hmul2(g2[mh][hf], ds[jj].x)));
          x.y = hmul2(x.y, hfma2(og2[mh][hf], hf ? z.w : z.y, hmul2(g2[mh][hf], ds[jj].y)));
        }
      }
    }
    bar_sync(2, 128);
#pragma unroll
    for (int o = o0; o < o1; o++)
#pragma unroll
      for (int mh = 0; mh < 2; mh++) {
        const int jj = jj_of(o);
        sts128(e_addr(o, mh) + tid * 16, xv[mh][jj][0].x, xv[mh][jj][0].y, xv[mh][jj][1].x, xv[mh][jj][1].y);
      }
    bar_arrive(5 + g, 256);
    if (g == 0) TIM(1);
    if (g == 1) TIM(23);
  }
  TIM(17);
}

__device__ __forceinline__ void store_piece(float (&a)[64], float* op, int jj, const uint4& e, float g0, float g1) {
  stg128(op + 16 * jj, __float_as_uint(fmaf(g0, a[8 * jj], bf_lo(e.x))), __float_as_uint(fmaf(g0, a[8 * jj + 1], bf_hi(e.x))),
         __float_as_uint(fmaf(g0, a[8 * jj + 4], bf_lo(e.y))), __float_as_uint(fmaf(g0, a[8 * jj + 5], bf_hi(e.y))));
  stg128(op + 32 * DM + 16 * jj, __float_as_uint(fmaf(g1, a[8 * jj + 2], bf_lo(e.z))), __float_as_uint(fmaf(g1, a[8 * jj + 3], bf_hi(e.z))),
         __float_as_uint(fmaf(g1, a[8 * jj + 6], bf_lo(e.w))), __float_as_uint(fmaf(g1, a[8 * jj + 7], bf_hi(e.w))));
}

__device__ __forceinline__ void issue_g1(const Maps& m, int s, int sl, int ti, int pj) {
  const uint32_t bar = B_FULL + 8 * sl, dst = sb + sl * STAGE;
  const int k0 = (s & 15) * 64, ch = (s >> 4) * 512 + pj * 64;
  mbar_expect(bar, STAGE);
  tma4d(dst + 16384, &m.x, bar, k0, 0, 4 * ti, 0);
  tma2d(dst, &m.bre, bar, k0, ch);
  tma2d(dst + 8192, &m.bim, bar, k0, ch);
}
__device__ __forceinline__ void producer(const Maps& m, int ti, int pj) {
#pragma unroll
  for (int s = EARLY; s < NS; s++) issue_g1(m, s, s, ti, pj);
  int sl = 0, par = 0;
  const int gs = gate_step(pj);
  if (gs + 1 < NS) mbar_arrive(B_GATE);
#pragma unroll 1
  for (int s = NS; s < 32; s++) {
    mbar_wait(B_EMPTY + 8 * sl, par);
    if (s == gs + NS) mbar_wait(B_GATE + 8, 0);
    issue_g1(m, s, sl, ti, pj);
    if (s == gs + 1) mbar_arrive(B_GATE);
    if (++sl == NS) { sl = 0; par ^= 1; }
  }
#pragma unroll 1
  for (int q = 0; q < 32; q++) {
    mbar_wait(B_EMPTY + 8 * sl, par);
    const uint32_t bar = B_FULL + 8 * sl, dst = sb + sl * STAGE;
    const int ph = q >> 4, u = q & 15, part = u < 2 ? u : u >= 9, i = u - 2 - 7 * part;
    const int src = u < 2 ? pj : (i < 4 ? (~pj & 4) + i : (pj & 4) + i - 4 + (i - 4 >= (pj & 3)));
    if (q == 16 + NS) mbar_wait(B_XT + 16, 0);
    mbar_expect(bar, u < 2 ? 16384 : STAGE);
    tma5d(dst + 16384, part ? &m.cim : &m.cre, bar, ph * 512 + src * 64, 0, 0, 0, pj * 8);
    if (u < 2) {
      if (ph) {
        mbar_expect(B_XT + 8 * u, 16384);
        tma4d(dst, &m.x2, B_XT + 8 * u, pj * 128 + u * 64, 0, 0, ti * 16);
      }
    } else {
      if (i == 0) {
        mbar_wait(B_FLG + 8 * (2 * ph + part), 0);
        fence_async_global();
        if (part == 0) TIM(24 + ph);
      }
      bulk_load(dst, g_h + (size_t)(ti * 32 + ph * 16 + part * 8 + src) * 1024, 16384, bar);
    }
    if (++sl == NS) { sl = 0; par ^= 1; }
  }
}

__device__ __forceinline__ void poller(int ti, int pj, int lane, unsigned ep) {
  if (lane < 6) {
    const int f = lane < 4 ? F_H + lane * 16 + ti : F_Z + pj * 2 + lane - 4;
    const unsigned need = (ep + 1) * (lane < 4 ? 8 : 16);
    int n = SPIN_LIMIT;
    bool done = false;
    do {
      if (!done && (int)(ld_relaxed(g_flag + f * 32) - need) >= 0) {
        done = true;
        asm volatile("fence.acquire.gpu;" ::: "memory");
        mbar_arrive(B_FLG + 8 * lane);
      }
      if (POLL_NS) __nanosleep(POLL_NS);
    } while (!__all_sync(0x3fu, done) && --n);
    trap_if(n == 0);
  }
}
__device__ __forceinline__ void storer(const Maps& m, int ti, int pj) {
#pragma unroll 1
  for (int job = 0; job < 6; job++) {
    bar_sync(job < 2 ? 4 + job : 9 + (job & 1), 160);
    if (elect_one()) flag_release(job < 2 ? F_U + pj * 2 + job : F_H + (job - 2) * 16 + ti);
    __syncwarp();
    if (job == 2 || job == 4) TIM(7 + job * 2);
  }
  if (elect_one()) {
    mbar_wait_long(B_LOC + 16, 0);
#pragma unroll 1
    for (int o = 0; o < 6; o++) {
      const int g = o >> 2;
      if ((o & 3) == 0) {
        mbar_wait_long(B_FLG + 32 + 8 * g, 0);
        fence_async_global();
        mbar_expect(B_ZT + 8 * g, o ? 8192 : 16384);
      }
      tma5d(S_STG + o * 4096, &m.z, B_ZT + 8 * g, ti * 128, 0, 0, 0, pj * 8 + jj_of(o));
      tma5d(S_STG + o * 4096 + 2048, &m.z, B_ZT + 8 * g, ti * 128 + 64, 0, 0, 0, pj * 8 + jj_of(o));
    }
  }
}

__device__ __forceinline__ void kv_loader(const Maps& m, int ti, int pj, unsigned t_start) {
  unsigned tt = t_start + KV0_AT;
#pragma unroll 1
  for (int st = 0; st < 4; st++) {
    const int d = pj * 128 + (st >> 1) * 64, tb = ti * 16 + (st & 1) * 8;
    const uint32_t bar = B_PIN + 8 * st;
    if (st >= 2) { bar_sync(st == 2 ? 3 : 11, 160); fence_async_smem(); }
    if (elect_one()) {
      mbar_expect(bar, 16384 + 384);
      if ((int)(clock() - tt) > 0) tt = clock();
#pragma unroll 1
      for (int i = 0; i < 4; i++) {
        wait_clock(tt);
        tt += st == 3 ? KV_GAP1 : (st == 0 ? KV_GAP0 : KV_GAP);
        tma3d(S_STG + (st & 1) * 16384 + i * 4096, (i & 2) ? &m.v : &m.k, bar, d, tb, (i & 1) * 4);
        if (i == 0) tma3d(S_T + st * 512, &m.kh, bar, d, tb - 1, 5);
      }
    }
    tt = __shfl_sync(~0u, tt, 0);
  }
}

__device__ __forceinline__ void conv_loader(const Maps& m, const Ptrs& p, const ConvCtx& cc, int eb, int lane, unsigned t_start) {
  const unsigned ep = ld_relaxed(g_epoch + eb);
  wait_clock(t_start + SPF_AT);
  if (cc.j >= 0 && elect_one()) {
#pragma unroll 1
    for (int ch = 2; ch < cc.n; ch++) l2_prefetch(p.f + (size_t)cc.chan(ch) * SEQ, 4096);
  }
  __syncwarp();
#pragma unroll 1
  for (int ch = 0; ch < cc.n; ch++) {
    const int d = cc.chan(ch);
    const uint32_t bar = cc.inbar + 8 * (ch & 1), dst = cc.buf + (ch & 1) * 8192;
    const bool first = ch == 0 || ch == (cc.j < 0 ? 3 : 1);
    if (ch >= 2) bar_sync(cc.nb + 2 + (ch & 1), 160);
    if (elect_one()) {
      mbar_expect(cc.inbar + 16, 4096);
      bulk_load(dst + 4096, p.f + (size_t)d * SEQ, 4096, cc.inbar + 16);
      if (!first) { mbar_expect(bar, 4096); tma3d(dst, &m.u, bar, 0, d & 31, d & ~31); }
    }
    __syncwarp();
    const uint32_t a = dst + 4096 + 128 + (lane >> 3) * 256 + (lane & 7) * 16;
    mbar_wait_long(cc.inbar + 16, ch & 1);
#pragma unroll 1
    for (uint32_t i = a; i < a + 4096; i += 1024) {
      const uint4 x = lds128(i);
      __syncwarp();
      sts128(i ^ 16, x.x, x.y, x.z, x.w);
    }
    fence_async_smem();
    __syncwarp();
    if (elect_one()) {
      mbar_arrive(bar);
      if (first) {
        int n = SPIN_LIMIT;
        while ((int)(ld_relaxed(g_flag + (F_U + (d >> 6)) * 32) - (ep + 1) * 16) < 0 && --n) __nanosleep(POLL_NS);
        trap_if(n == 0);
        asm volatile("fence.acquire.gpu;" ::: "memory");
        fence_async_global();
        mbar_expect(bar, 4096);
        tma3d(dst, &m.u, bar, 0, d & 31, d & ~31);
      }
    }
    __syncwarp();
  }
  if (cc.j >= 0) {
    if (lane == 0) g_epoch[eb] = ep + 1;
  } else {
#pragma unroll 1
    for (int g = 0; g < 2; g++) {
      bar_sync(11 * g, 160);
      if (elect_one()) flag_release(F_Z + cc.pj * 2 + g);
      __syncwarp();
    }
  }
}

struct Ring { uint32_t off, par, rel; };
__device__ __forceinline__ void desc_touch(const uint64_t (&c)[12][NS]) {
  uint32_t x = 0;
#pragma unroll
  for (int i = 0; i < 12 * NS; i += 4) x |= (uint32_t)(&c[0][0])[i];
  trap_if((x | (uint32_t)c[11][NS - 1]) == 0);
}
template <int TA, bool TAB, bool LOC = false>
__device__ __forceinline__ void gemm_steps(float (&a0)[64], float (&a1)[64], Ring& r, int n, const uint64_t (&c)[12][NS], int slot) {
#pragma unroll 1
  do {
    const uint32_t off = r.off, rel = r.rel;
    full_wait(B_FULL + off, r.par, slot);
    r.rel = off;
    r.off += 8;
    if (r.off == 8 * NS) { r.off = 0; r.par ^= 1; }
    WG_FENCE();
#define DESC(i) (*(const uint64_t*)((const char*)c[i] + off))
#pragma unroll
    for (int k = 0; k < 4; k++) {
      const uint64_t db = TAB ? DESC(3 * k) : mkdesc(off * 256 + dlo(sb + 16384 + 32 * k, 16), 1024, 1);
      if (LOC) {
        wgmma_ss128<TA, 0, 1>(a0, mkdesc(dlo(S_STG + 32768 + 1024 * k, 4096) - n * 1024, 512, 2), db);
        wgmma_ss128<TA, 0, 1>(a1, mkdesc(dlo(S_STG + 32768 + 8192 + 1024 * k, 4096) - n * 1024, 512, 2), db);
      } else {
        wgmma_ss128<TA, 0, 1>(a0, TAB ? DESC(3 * k + 1) : mkdesc(off * 256 + dlo(sb + 32 * k, 16), 1024, 1), db);
        wgmma_ss128<TA, 0, 1>(a1, TAB ? DESC(3 * k + 2) : mkdesc(off * 256 + dlo(sb + 8192 + 32 * k, 16), 1024, 1), db);
      }
      if (k == RELK) {
        WG_COMMIT();
        WG_WAIT(1);
        if (elect_one()) mbar_arrive(B_EMPTY + rel);
      }
    }
#undef DESC
    if (RELK < 3) WG_COMMIT();
  } while (--n);
}

__global__ void __launch_bounds__(512, 1) fused_kernel(const __grid_constant__ Maps m, const __grid_constant__ Ptrs p) {
  extern __shared__ __align__(1024) uint8_t smem_raw[];
  int b = blockIdx.x;
  {
    int sm, nsm;
    asm volatile("mov.u32 %0, %%smid;" : "=r"(sm));
    asm volatile("mov.u32 %0, %%nsmid;" : "=r"(nsm));
    const int tp = sm >> 1, q = ((tp - 32) * 37) >> 8;
    const int g = tp < 32 ? tp & 7 : (tp < 60 ? tp - 31 - 7 * q : (tp < 62 ? 8 : 0));
    const int j = tp < 32 ? tp >> 3 : (tp < 60 ? 4 + q : (tp < 62 ? tp - 60 : tp - 58));
    if (nsm == 132) b = g * 16 + j * 2 + (sm & 1);
    b = __shfl_sync(~0u, b, 0);
  }
  const int spare = b - 128;
  const int ti = ((b >> 5) << 2) | (b & 3), pj = (((b >> 4) & 1) << 2) | ((b >> 2) & 3);
  const int wid = __shfl_sync(~0u, threadIdx.x >> 5, 0), wg = wid >> 2, tid = threadIdx.x & 127, lane = threadIdx.x & 31;
  if (wg == 0) TIM(0);
  const unsigned t_start = clock();
  if (wid == 12) {
    if (elect_one()) {
      asm volatile("prefetch.tensormap [%0];" ::"l"(&m.x) : "memory");
      asm volatile("prefetch.tensormap [%0];" ::"l"(&m.bre) : "memory");
      asm volatile("prefetch.tensormap [%0];" ::"l"(&m.bim) : "memory");
#pragma unroll
      for (int i = 0; i < NS; i++) mbar_init(B_FULL + 8 * i, (i < 2 && spare >= 0) ? 2 : 1);
      fence_async_smem();
#pragma unroll
      for (int s = 0; s < EARLY; s++) if (spare < 0) issue_g1(m, s, s, ti, pj);
    }
  } else if (wid == 13) {
    if (elect_one()) {
      trap_if((uint32_t)__cvta_generic_to_shared(smem_raw) != sb);
#pragma unroll
      for (uint32_t bar = B_EMPTY; bar < S_EP; bar += 8) mbar_init(bar, (bar < B_CINF || (bar >= B_SFREE && bar < B_GATE) || bar == B_GATE + 8 || bar == B_XT + 16) ? 4 :
                           (bar < B_CINF + 16 || ((bar == B_PIN || bar == B_PIN + 8) && spare >= 0)) ? 2 : 1);
      fence_async_smem();
    }
  }
  __syncwarp();
  if (wg == 3) {
    asm volatile("setmaxnreg.dec.sync.aligned.u32 %0;" ::"n"(RV == 2 ? 32 : 24));
    bar_sync(1, 128);
    if (spare < 0) {
      if (wid == 13) { bar_arrive(2, 160); bar_arrive(12, 160); }
      bar_arrive(0, 256);
    } else {
      bar_arrive(0, 512);
    }
    if (wid == 13) {
      if (spare < 0) {
        const unsigned ep = ld_relaxed(g_epoch + b);
        kv_loader(m, ti, pj, t_start);
        poller(ti, pj, lane, ep);
      }
    } else if (wid == 15 || spare >= 0) {
      const ConvCtx cc = conv_ctx(spare, wid == 12 ? 0 : wid - 13, ti, pj);
      conv_loader(m, p, cc, spare < 0 ? b : 128 + cc.j, lane, t_start);
    } else if (wid == 12) {
      if (elect_one()) producer(m, ti, pj);
    } else {
      storer(m, ti, pj);
    }
  } else if (wg == 2 || spare >= 0) {
    asm volatile("setmaxnreg.inc.sync.aligned.u32 160;");
    if (wg == 2) conv_tables(tid);
    if (spare < 0) bar_sync(12, 160); else bar_sync(0, 512);
    conv_main(p, conv_ctx(spare, wg, ti, pj), spare < 0 ? b : 128 + spare * 3 + wg, tid);
  } else {
    asm volatile("setmaxnreg.inc.sync.aligned.u32 %0;" ::"n"(RV == 3 ? 168 : 160));
    if (wg == 1) {
      const int ch = (tid >> 6) * 512 + pj * 64 + (tid & 63);
      const unsigned ep = ld_relaxed(g_epoch + b);
      const float lr = __bfloat162float(p.lre[ch]), li = __bfloat162float(p.lim[ch]);
      const float dt = bf_round(expf(__bfloat162float(p.ldt[ch])));
      float sn, cs;
      sincosf(dt * li, &sn, &cs);
      const float ex = expf(dt * lr);
      const float ar = ex * cs, ai = ex * sn;
      const float inv = 2.f / (lr * lr + li * li);
      const float cr = ((ar - 1.f) * lr + ai * li) * inv, ci = (ai * lr - (ar - 1.f) * li) * inv;
      sts128(S_PAR + tid * 16, __float_as_uint(ar), __float_as_uint(ai), pack2(cr, cr), pack2(-ci, -ci));
      const cx l32 = csq(csq(csq(csq(csq({ar, ai}))))), l128 = csq(csq(l32));
      sts128(S_PAR + 2048 + tid * 16, __float_as_uint(l32.r), __float_as_uint(l32.i), __float_as_uint(l128.r), __float_as_uint(l128.i));
      if (tid == 0) asm volatile("st.shared.u32 [%0], %1;" ::"r"(S_EP), "r"(ep) : "memory");
      bar_arrive(6, 256);
      bar_sync(2, 160);
      desc_touch(p.dc1);
      prep<0>(p, ti, pj, wid & 3, lane);
    }
    float a0[64], a1[64];
    Ring ring = {8u * wg * (16 % NS), wg * ((16u / NS) & 1), B_DUMMY - B_EMPTY};
    zero(a0); zero(a1);
    reg_fence(a0); reg_fence(a1);
    sched_fence<61>();
    bar_sync(wg * 7, 256);
    TIM(2 + wg * 2);
    if (wg == 0) gemm_steps<0, false>(a0, a1, ring, 15, p.dc1, 0);
    else gemm_steps<0, true>(a0, a1, ring, 15, p.dc1, 1);
    bar_arrive(7 + wg, 256);
    gemm_steps<0, false>(a0, a1, ring, 1, p.dc1, wg);
    if (wg == 0) bar_sync(6, 256);
    scan_epilogue(a0, a1, B_EMPTY + ring.rel, wg, ti, pj, tid);
    if (wg == 1) {
      eterm(p, ti, pj, tid);
    } else {
      ring = {8 * (32 % NS), (32 / NS) & 1, B_DUMMY - B_EMPTY};
      desc_touch(p.dc2);
      zero(a0); zero(a1);
      reg_fence(a0); reg_fence(a1);
      sched_fence<62>();
      bar_sync(8, 256);
      TIM(6);
#pragma unroll 1
      for (int o = 0; o < 4; o++) {
        if (!(o & 1)) {
          if (o) TIM(18);
          full_wait(B_LOC + 4 * o, 0, 2 + 2 * o);
          gemm_steps<1, true, true>(a0, a1, ring, 2, p.dc2, 3 + 2 * o);
        }
        gemm_steps<1, true>(a0, a1, ring, (o & 1) ? (o == 1 ? 13 : 13 - RES) : 1, p.dc2, 4 + 2 * o - (o & 1));
        if (!(o & 1) && elect_one()) {
          mbar_arrive(o ? B_LOC + 16 : B_SFREE + 16);
        }
      }
#pragma unroll
      for (int i = 0; i < RES; i++) {
        const int sl = (64 - RES + i) % NS;
        full_wait(B_FULL + 8 * sl, ((64 - RES + i) / NS) & 1, 10);
        WG_FENCE();
#pragma unroll
        for (int k = 0; k < 4; k++) wgmma_ss128<1, 0, 1>(a0, p.dc2[3 * k + 1][sl], p.dc2[3 * k][sl]);
        WG_COMMIT();
        if (i == 0 && RES == NS) { WG_WAIT(1); if (elect_one()) mbar_arrive(B_EMPTY + ring.rel); }
      }
      const int w = tid >> 5, trow = 16 * 0 + 64 * (w & 1) + 8 * (w >> 1) + (lane >> 2);
      float* op = p.out + (size_t)(ti * 128 + trow) * DM + pj * 128 + 4 * (lane & 3);
      float g[4];
      uint4 e;
#pragma unroll
      for (int i = 0; i < RES; i++) {
        const int sl = (64 - RES + i) % NS;
        if (i == 0) WG_FENCE();
#pragma unroll
        for (int k = 0; k < 4; k++) wgmma_ss128<1, 0, 1>(a1, p.dc2[3 * k + 2][sl], p.dc2[3 * k][sl]);
        WG_COMMIT();
        if (i == 0) {
          bar_sync(5, 256);
#pragma unroll
          for (int q = 0; q < 4; q++) g[q] = __uint_as_float(lds32(S_G + (trow + 16 * (q >> 1) + 32 * (q & 1)) * 4));
          e = lds128(e_addr(0, 0) + tid * 16);
          WG_WAIT(1);
          reg_fence(a0);
        }
        if (i < 4) {
          const uint4 e0 = e;
          e = lds128(e_addr((i + 1) & 3, i == 3) + tid * 16);
          store_piece(a0, op, jj_of(i), e0, g[0], g[1]);
        }
        if (i == 0) sched_fence_async<70>(); if (i == 1) sched_fence_async<71>(); if (i == 2) sched_fence_async<72>(); if (i == 3) sched_fence_async<73>();
      }
      TIM(26);
      WG_WAIT(0);
      reg_fence(a1);
      TIM(7);
#pragma unroll
      for (int o = 0; o < 8; o++) {
        if (o == 4 || o == 6) bar_sync(4 + (o >> 1), 256);
        if (o >= 4) store_piece(a0, op, jj_of(o), lds128(e_addr(o, 0) + tid * 16), g[0], g[1]);
        store_piece(a1, op + 16 * DM, jj_of(o), o ? lds128(e_addr(o, 1) + tid * 16) : e, g[2], g[3]);
      }
      if (tid == 0) g_epoch[b] = lds32(S_EP) + 1;
      TIM(19);
    }
  }
}

typedef CUresult (*EncFn)(CUtensorMap*, CUtensorMapDataType, cuuint32_t, void*, const cuuint64_t*, const cuuint64_t*,
                          const cuuint32_t*, const cuuint32_t*, CUtensorMapInterleave, CUtensorMapSwizzle,
                          CUtensorMapL2promotion, CUtensorMapFloatOOBfill);

void encode(EncFn enc, CUtensorMap* m, const void* ptr, int rank, const cuuint64_t* dims, const cuuint64_t* strides,
            const cuuint32_t* box, CUtensorMapSwizzle sw) {
  cuuint32_t es[5] = {1, 1, 1, 1, 1};
  enc(m, CU_TENSOR_MAP_DATA_TYPE_BFLOAT16, rank, const_cast<void*>(ptr), dims, strides, box, es, CU_TENSOR_MAP_INTERLEAVE_NONE,
      sw, PROMO, CU_TENSOR_MAP_FLOAT_OOB_FILL_NONE);
}

}

extern "C" void kernel_launch(void* const* d_in, const int* in_sizes, int n_in, void* d_out, int out_size) {
  typedef const __nv_bfloat16* bp;
  Ptrs p;
  p.x = (bp)d_in[0]; p.lre = (bp)d_in[1]; p.lim = (bp)d_in[2]; p.bre = (bp)d_in[3]; p.bim = (bp)d_in[4];
  p.cre = (bp)d_in[5]; p.cim = (bp)d_in[6]; p.ldt = (bp)d_in[7]; p.dskip = (bp)d_in[8];
  p.k = (bp)d_in[10]; p.v = (bp)d_in[11]; p.shift = (bp)d_in[12]; p.f = (bp)d_in[13]; p.ssmd = (bp)d_in[14];
  p.gw = (bp)d_in[15]; p.out = (float*)d_out;

  for (int sl = 0; sl < NS; sl++)
    for (int k = 0; k < 4; k++) {
      const uint64_t h128 = (uint64_t)(64u | (1u << 30)) << 32, h64 = (uint64_t)(32u | (2u << 30)) << 32;
      const uint32_t st = sb + sl * STAGE;
      p.dc1[3 * k][sl] = p.dc2[3 * k][sl] = h128 | dlo(st + 16384 + 32 * k, 16);
      p.dc1[3 * k + 1][sl] = h128 | dlo(st + 32 * k, 16);
      p.dc1[3 * k + 2][sl] = h128 | dlo(st + 8192 + 32 * k, 16);
      p.dc2[3 * k + 1][sl] = h64 | dlo(st + 1024 * k, 4096);
      p.dc2[3 * k + 2][sl] = h64 | dlo(st + 8192 + 1024 * k, 4096);
    }
  EncFn enc = nullptr;
  cudaDriverEntryPointQueryResult qr;
  cudaGetDriverEntryPoint("cuTensorMapEncodeTiled", (void**)&enc, cudaEnableDefault, &qr);
  void *zptr = nullptr, *uptr = nullptr;
  cudaGetSymbolAddress(&zptr, g_z);
  cudaGetSymbolAddress(&uptr, g_u);

  Maps m;
  {
    cuuint64_t d[4] = {1024, 2, 64, 16}, s[3] = {2048, 65536, 4096};
    cuuint32_t bx[4] = {64, 2, 4, 16};
    encode(enc, &m.x, p.x, 4, d, s, bx, CU_TENSOR_MAP_SWIZZLE_128B);
  }
  {
    cuuint64_t d[2] = {1024, 1024}, s[1] = {2048};
    cuuint32_t bx[2] = {64, 64};
    encode(enc, &m.bre, p.bre, 2, d, s, bx, CU_TENSOR_MAP_SWIZZLE_128B);
    encode(enc, &m.bim, p.bim, 2, d, s, bx, CU_TENSOR_MAP_SWIZZLE_128B);
  }
  {
    cuuint64_t d[5] = {1024, 2, 4, 2, 64}, s[4] = {2048, 8192, 4096, 32768};
    cuuint32_t bx[5] = {64, 2, 4, 2, 8};
    encode(enc, &m.cre, p.cre, 5, d, s, bx, CU_TENSOR_MAP_SWIZZLE_128B);
    encode(enc, &m.cim, p.cim, 5, d, s, bx, CU_TENSOR_MAP_SWIZZLE_128B);
  }
  {
    cuuint64_t d[3] = {64, 32, 1024}, s[2] = {128, 4096};
    cuuint32_t bx[3] = {64, 1, 32};
    encode(enc, &m.u, uptr, 3, d, s, bx, CU_TENSOR_MAP_SWIZZLE_NONE);
  }
  {
    cuuint64_t d[3] = {1024, 256, 8}, s[2] = {16384, 2048};
    cuuint32_t bx[3] = {64, 8, 4}, bh[3] = {64, 1, 3};
    encode(enc, &m.k, p.k, 3, d, s, bx, CU_TENSOR_MAP_SWIZZLE_128B);
    encode(enc, &m.kh, p.k, 3, d, s, bh, CU_TENSOR_MAP_SWIZZLE_NONE);
    encode(enc, &m.v, p.v, 3, d, s, bx, CU_TENSOR_MAP_SWIZZLE_128B);
  }
  {
    cuuint64_t d[5] = {2048, 2, 4, 2, 64}, s[4] = {4096, 16384, 8192, 65536};
    cuuint32_t bx[5] = {64, 2, 4, 2, 1};
    encode(enc, &m.z, zptr, 5, d, s, bx, CU_TENSOR_MAP_SWIZZLE_128B);
  }
  {
    cuuint64_t d[4] = {1024, 2, 4, 256}, s[3] = {8192, 2048, 16384};
    cuuint32_t bx[4] = {64, 2, 4, 16};
    encode(enc, &m.x2, p.x, 4, d, s, bx, CU_TENSOR_MAP_SWIZZLE_128B);
  }
  cudaFuncSetAttribute(fused_kernel, cudaFuncAttributeMaxDynamicSharedMemorySize, SMEM_BYTES);
  fused_kernel<<<132, 512, SMEM_BYTES, cudaStreamPerThread>>>(m, p);
}
```

```cpp
#include <cuda_runtime.h>
#include <cuda_bf16.h>
#include <cuda.h>
#include <stdint.h>

namespace {

constexpr int SEQ = 2048, DM = 1024;
#define NSV 5
constexpr int NS = NSV;
constexpr int STAGE = 32768;
#define KV0_AT 300
#define KV_GAP0 750
#define KV1_AT 8000
#define KV_GAP1 550
#define EARLY 2
#define SFM 2
#define RV 1
#define POLL_NS 60
#define IM_NS 100
#define SPF_AT 9000
#define RELK 0
#define RES 4
#define AGG_NS 200
#define ZL_NS 100
#define P2F 3
#define LD_GAP 400
#define LDQ ""
#define PROMO CU_TENSOR_MAP_L2_PROMOTION_L2_128B
constexpr uint32_t sb = 1024;
constexpr uint32_t S_STG = sb + NS * STAGE;
constexpr uint32_t S_CIN = S_STG + 32768;
constexpr uint32_t S_T = S_CIN + 16384;
constexpr uint32_t S_M1 = S_T + 8192;
constexpr uint32_t S_M2 = S_M1 + 4096;
constexpr uint32_t S_PAR = S_M2 + 2048;
constexpr uint32_t S_G = S_PAR + 4096;
constexpr uint32_t S_BAR = S_G + 512;
constexpr int SMEM_BYTES = S_BAR + 512 - sb;
constexpr uint32_t B_FULL = S_BAR, B_EMPTY = B_FULL + 8 * NS, B_CINF = B_EMPTY + 8 * NS,
                   B_FLG = B_CINF + 24, B_SFREE = B_FLG + 40, B_LOC = B_SFREE + 24, B_GATE = B_LOC + 24, B_ZT = B_GATE + 16,
                   B_XT = B_ZT + 8, B_PIN = B_XT + 24, B_DUMMY = B_PIN + 32, S_EP = B_DUMMY + 8;
constexpr int SPIN_LIMIT = 1 << 21;
constexpr int F_H = 0, F_U = 64, F_Z = 80;

struct alignas(64) Maps { CUtensorMap x, bre, bim, cre, cim, u, z, x2, k, kh, v; };
struct Ptrs {
  const __nv_bfloat16 *x, *lre, *lim, *ldt, *dskip, *k, *v, *shift, *f, *ssmd, *gw, *bre, *bim, *cre, *cim;
  float* out;
  uint64_t dc1[12][NS], dc2[12][NS];
};

__device__ uint4 g_h[16 * 32 * 1024];
__device__ uint4 g_u[1024 * 256];
__device__ uint4 g_z[1024 * 256];
__device__ uint4 g_agg[2 * 16 * 256];
__device__ unsigned g_gate[8 * SEQ];
__device__ unsigned g_flag[88 * 32];
__device__ unsigned g_epoch[140];
#define TIM(i)
#define TIMC(i)

#define WG_FENCE() asm volatile("wgmma.fence.sync.aligned;" ::: "memory")
#define WG_COMMIT() asm volatile("wgmma.commit_group.sync.aligned;" ::: "memory")
#define WG_WAIT(n) asm volatile("wgmma.wait_group.sync.aligned %0;" ::"n"(n) : "memory")
#define R8(d, o) "+f"(d[o + 0]), "+f"(d[o + 1]), "+f"(d[o + 2]), "+f"(d[o + 3]), "+f"(d[o + 4]), "+f"(d[o + 5]), "+f"(d[o + 6]), "+f"(d[o + 7])
#define W8(d, o) "=f"(d[o + 0]), "=f"(d[o + 1]), "=f"(d[o + 2]), "=f"(d[o + 3]), "=f"(d[o + 4]), "=f"(d[o + 5]), "=f"(d[o + 6]), "=f"(d[o + 7])
#define L16 "%0,%1,%2,%3,%4,%5,%6,%7,%8,%9,%10,%11,%12,%13,%14,%15"
#define L64 L16 ",%16,%17,%18,%19,%20,%21,%22,%23,%24,%25,%26,%27,%28,%29,%30,%31," \
  "%32,%33,%34,%35,%36,%37,%38,%39,%40,%41,%42,%43,%44,%45,%46,%47,%48,%49,%50,%51,%52,%53,%54,%55,%56,%57,%58,%59,%60,%61,%62,%63"

template <int TA, int TB, int ACC>
__device__ __forceinline__ void wgmma_ss128(float (&d)[64], uint64_t da, uint64_t db) {
  if (ACC)
    asm volatile("wgmma.mma_async.sync.aligned.m64n128k16.f32.bf16.bf16 {" L64 "}, %64, %65, 1, 1, 1, %66, %67;"
                 : R8(d, 0), R8(d, 8), R8(d, 16), R8(d, 24), R8(d, 32), R8(d, 40), R8(d, 48), R8(d, 56)
                 : "l"(da), "l"(db), "n"(TA), "n"(TB));
  else
    asm volatile("wgmma.mma_async.sync.aligned.m64n128k16.f32.bf16.bf16 {" L64 "}, %64, %65, 0, 1, 1, %66, %67;"
                 : W8(d, 0), W8(d, 8), W8(d, 16), W8(d, 24), W8(d, 32), W8(d, 40), W8(d, 48), W8(d, 56)
                 : "l"(da), "l"(db), "n"(TA), "n"(TB));
}
template <int ACC, int TB = 0>
__device__ __forceinline__ void wgmma_rs32(float (&d)[16], uint32_t a0, uint32_t a1, uint32_t a2, uint32_t a3, uint64_t db) {
  if (ACC)
    asm volatile("wgmma.mma_async.sync.aligned.m64n32k16.f32.bf16.bf16 {" L16 "}, {%16,%17,%18,%19}, %20, 1, 1, 1, %21;"
                 : R8(d, 0), R8(d, 8) : "r"(a0), "r"(a1), "r"(a2), "r"(a3), "l"(db), "n"(TB));
  else
    asm volatile("wgmma.mma_async.sync.aligned.m64n32k16.f32.bf16.bf16 {" L16 "}, {%16,%17,%18,%19}, %20, 0, 1, 1, %21;"
                 : W8(d, 0), W8(d, 8) : "r"(a0), "r"(a1), "r"(a2), "r"(a3), "l"(db), "n"(TB));
}
template <int N>
__device__ __forceinline__ void reg_fence(float (&d)[N]) {
#pragma unroll
  for (int i = 0; i < N; i++) asm volatile("" : "+f"(d[i])::"memory");
}
__host__ __device__ __forceinline__ constexpr uint32_t dlo(uint32_t addr, uint32_t lbo) { return (addr >> 4) + ((lbo >> 4) << 16); }
__device__ __forceinline__ uint64_t mkdesc(uint32_t lo, uint32_t sbo, uint32_t mode) {
  uint64_t d;
  asm("mov.b64 %0, {%1, %2};" : "=l"(d) : "r"(lo), "r"((sbo >> 4) | (mode << 30)));
  return d;
}
template <int N>
__device__ __forceinline__ void zero(float (&d)[N]) {
#pragma unroll
  for (int i = 0; i < N; i++) d[i] = 0.f;
}
__device__ __forceinline__ void trap_if(int c) {
  asm volatile("{.reg .pred p; .reg .b64 z; setp.ne.s32 p, %0, 0; mov.b64 z, 0; @p st.global.u32 [z], %0;}" ::"r"(c) : "memory");
}
template <int K>
__device__ __forceinline__ void sched_fence() {
  asm volatile("{.reg .pred p; setp.eq.u32 p, %0, %1; @p exit;}" ::"r"(gridDim.x), "n"(256 + K) : "memory");
}
template <int K>
__device__ __forceinline__ void sched_fence_async() {
  asm volatile("{.reg .pred p; .reg .u32 r; setp.ne.u32 p, %0, %1; @p bra.uni SFE;\n"
               "SFL: nanosleep.u32 1000; mov.u32 r, %%clock; setp.eq.u32 p, r, 0; @p bra.uni SFL;\nSFE: }" ::"r"(gridDim.x), "n"(256 + K) : "memory");
}
__device__ __forceinline__ bool elect_one() {
  uint32_t pred;
  asm volatile("{.reg .pred p; elect.sync _|p, 0xffffffff; selp.u32 %0, 1, 0, p;}" : "=r"(pred));
  return pred;
}
__device__ __forceinline__ void mbar_init(uint32_t bar, uint32_t cnt) {
  asm volatile("mbarrier.init.shared::cta.b64 [%0], %1;" ::"r"(bar), "r"(cnt) : "memory");
}
__device__ __forceinline__ bool mbar_try(uint32_t bar, uint32_t par) {
  uint32_t ok;
  asm volatile("{.reg .pred p; mbarrier.try_wait.parity.shared::cta.b64 p, [%1], %2; selp.u32 %0, 1, 0, p;}"
               : "=r"(ok) : "r"(bar), "r"(par) : "memory");
  return ok;
}
#undef DBGV
#define DBGV ((bar - S_BAR) * 2 + par)
__device__ __forceinline__ void mbar_wait(uint32_t bar, uint32_t par) {
  if (__builtin_expect(!mbar_try(bar, par), 0)) {
    int n = SPIN_LIMIT;
    while (!mbar_try(bar, par) && --n) {}
    trap_if(n == 0);
  }
}
#define full_wait(bar, par, slot) mbar_wait(bar, par)
__device__ __forceinline__ void mbar_wait_long(uint32_t bar, uint32_t par) {
  int n = SPIN_LIMIT;
  while (!mbar_try(bar, par) && --n) __nanosleep(100);
  trap_if(n == 0);
}
#undef DBGV
#define DBGV 0
__device__ __forceinline__ void mbar_arrive(uint32_t bar) {
  asm volatile("mbarrier.arrive.shared::cta.b64 _, [%0];" ::"r"(bar) : "memory");
}
__device__ __forceinline__ void mbar_expect(uint32_t bar, uint32_t bytes) {
  asm volatile("mbarrier.arrive.expect_tx.shared::cta.b64 _, [%0], %1;" ::"r"(bar), "r"(bytes) : "memory");
}
__device__ __forceinline__ void tma2d(uint32_t dst, const CUtensorMap* m, uint32_t bar, int c0, int c1) {
  asm volatile("cp.async.bulk.tensor.2d.shared::cluster.global.mbarrier::complete_tx::bytes [%0], [%1, {%3, %4}], [%2];"
               ::"r"(dst), "l"(m), "r"(bar), "r"(c0), "r"(c1) : "memory");
}
__device__ __forceinline__ void tma3d(uint32_t dst, const CUtensorMap* m, uint32_t bar, int c0, int c1, int c2) {
  asm volatile("cp.async.bulk.tensor.3d.shared::cluster.global.mbarrier::complete_tx::bytes [%0], [%1, {%3, %4, %5}], [%2];"
               ::"r"(dst), "l"(m), "r"(bar), "r"(c0), "r"(c1), "r"(c2) : "memory");
}
__device__ __forceinline__ void tma4d(uint32_t dst, const CUtensorMap* m, uint32_t bar, int c0, int c1, int c2, int c3) {
  asm volatile("cp.async.bulk.tensor.4d.shared::cluster.global.mbarrier::complete_tx::bytes [%0], [%1, {%3, %4, %5, %6}], [%2];"
               ::"r"(dst), "l"(m), "r"(bar), "r"(c0), "r"(c1), "r"(c2), "r"(c3) : "memory");
}
__device__ __forceinline__ void tma5d(uint32_t dst, const CUtensorMap* m, uint32_t bar, int c0, int c1, int c2, int c3, int c4) {
  asm volatile("cp.async.bulk.tensor.5d.shared::cluster.global.mbarrier::complete_tx::bytes [%0], [%1, {%3, %4, %5, %6, %7}], [%2];"
               ::"r"(dst), "l"(m), "r"(bar), "r"(c0), "r"(c1), "r"(c2), "r"(c3), "r"(c4) : "memory");
}
__device__ __forceinline__ void bulk_load(uint32_t dst, const void* src, uint32_t bytes, uint32_t bar) {
  asm volatile("cp.async.bulk.shared::cluster.global.mbarrier::complete_tx::bytes [%0], [%1], %2, [%3];"
               ::"r"(dst), "l"(src), "r"(bytes), "r"(bar) : "memory");
}
__device__ __forceinline__ void l2_prefetch(const void* src, uint32_t bytes) {
  asm volatile("cp.async.bulk.prefetch.L2.global [%0], %1;" ::"l"(src), "r"(bytes) : "memory");
}
__device__ __forceinline__ void bar_sync(int id, int n) { asm volatile("bar.sync %0, %1;" ::"r"(id), "r"(n) : "memory"); }
__device__ __forceinline__ void bar_arrive(int id, int n) { asm volatile("bar.arrive %0, %1;" ::"r"(id), "r"(n) : "memory"); }
__device__ __forceinline__ void fence_async_smem() { asm volatile("fence.proxy.async.shared::cta;" ::: "memory"); }
__device__ __forceinline__ void fence_async_global() { asm volatile("fence.proxy.async.global;" ::: "memory"); }
__device__ __forceinline__ void flag_add(int f) {
  asm volatile("red.relaxed.gpu.global.add.u32 [%0], 1;" ::"l"(g_flag + f * 32) : "memory");
}
__device__ __forceinline__ void flag_release(int f) {
  asm volatile("fence.release.gpu;" ::: "memory");
  flag_add(f);
}
__device__ __forceinline__ unsigned ld_relaxed(const unsigned* p) {
  unsigned v;
  asm volatile("ld.relaxed.gpu.global.u32 %0, [%1];" : "=r"(v) : "l"(p) : "memory");
  return v;
}
__device__ __forceinline__ void wait_clock(unsigned t) {
  int d;
  while ((d = (int)(t - (unsigned)clock())) > 0) __nanosleep(d > 600 ? 200 : 40);
}
__device__ __forceinline__ uint32_t pack2(float lo, float hi) {
  uint32_t r;
  asm("cvt.rn.bf16x2.f32 %0, %1, %2;" : "=r"(r) : "f"(hi), "f"(lo));
  return r;
}
__device__ __forceinline__ float bf_lo(uint32_t v) { return __uint_as_float(v << 16); }
__device__ __forceinline__ float bf_hi(uint32_t v) { return __uint_as_float(v & 0xffff0000u); }
__device__ __forceinline__ float bf_round(float v) { return __bfloat162float(__float2bfloat16_rn(v)); }
__device__ __forceinline__ uint32_t hmul2(uint32_t a, uint32_t b) {
  uint32_t r;
  asm("mul.rn.bf16x2 %0, %1, %2;" : "=r"(r) : "r"(a), "r"(b));
  return r;
}
__device__ __forceinline__ uint32_t hadd2(uint32_t a, uint32_t b) {
  uint32_t r;
  asm("add.rn.bf16x2 %0, %1, %2;" : "=r"(r) : "r"(a), "r"(b));
  return r;
}
__device__ __forceinline__ uint32_t hsub2(uint32_t a, uint32_t b) {
  uint32_t r;
  asm("sub.rn.bf16x2 %0, %1, %2;" : "=r"(r) : "r"(a), "r"(b));
  return r;
}
__device__ __forceinline__ uint32_t hfma2(uint32_t a, uint32_t b, uint32_t c) {
  uint32_t r;
  asm("fma.rn.bf16x2 %0, %1, %2, %3;" : "=r"(r) : "r"(a), "r"(b), "r"(c));
  return r;
}
__device__ __forceinline__ uint32_t hneg2(uint32_t a) {
  uint32_t r;
  asm("neg.bf16x2 %0, %1;" : "=r"(r) : "r"(a));
  return r;
}
__device__ __forceinline__ uint4 ldg128(const void* p) {
  uint4 v;
  asm volatile("ld.global.nc" LDQ ".v4.u32 {%0,%1,%2,%3}, [%4];" : "=r"(v.x), "=r"(v.y), "=r"(v.z), "=r"(v.w) : "l"(p));
  return v;
}
__device__ __forceinline__ uint2 ldg64(const void* p) {
  uint2 v;
  asm volatile("ld.global.nc.v2.u32 {%0,%1}, [%2];" : "=r"(v.x), "=r"(v.y) : "l"(p));
  return v;
}
__device__ __forceinline__ void stg128(void* p, uint32_t a, uint32_t b, uint32_t c, uint32_t d) {
  asm volatile("st.global.v4.u32 [%0], {%1,%2,%3,%4};" ::"l"(p), "r"(a), "r"(b), "r"(c), "r"(d) : "memory");
}
__device__ __forceinline__ void sts128(uint32_t a, uint32_t x, uint32_t y, uint32_t z, uint32_t w) {
  asm volatile("st.shared.v4.u32 [%0], {%1,%2,%3,%4};" ::"r"(a), "r"(x), "r"(y), "r"(z), "r"(w) : "memory");
}
__device__ __forceinline__ uint32_t lds32(uint32_t a) {
  uint32_t v;
  asm volatile("ld.shared.u32 %0, [%1];" : "=r"(v) : "r"(a) : "memory");
  return v;
}
__device__ __forceinline__ uint4 lds128(uint32_t a) {
  uint4 v;
  asm volatile("ld.shared.v4.u32 {%0,%1,%2,%3}, [%4];" : "=r"(v.x), "=r"(v.y), "=r"(v.z), "=r"(v.w) : "r"(a) : "memory");
  return v;
}
__device__ __forceinline__ void stsm4(uint32_t a, uint32_t x, uint32_t y, uint32_t z, uint32_t w) {
  asm volatile("stmatrix.sync.aligned.m8n8.x4.shared.b16 [%0], {%1,%2,%3,%4};" ::"r"(a), "r"(x), "r"(y), "r"(z), "r"(w) : "memory");
}
__device__ __forceinline__ void stsm4t(uint32_t a, uint32_t x, uint32_t y, uint32_t z, uint32_t w) {
  asm volatile("stmatrix.sync.aligned.m8n8.x4.trans.shared.b16 [%0], {%1,%2,%3,%4};" ::"r"(a), "r"(x), "r"(y), "r"(z), "r"(w) : "memory");
}
__device__ __forceinline__ uint4 ldsm4t(uint32_t a) {
  uint4 v;
  asm volatile("ldmatrix.sync.aligned.m8n8.x4.trans.shared.b16 {%0,%1,%2,%3}, [%4];" : "=r"(v.x), "=r"(v.y), "=r"(v.z), "=r"(v.w) : "r"(a) : "memory");
  return v;
}
struct cx { float r, i; };
__device__ __forceinline__ cx cmul(cx a, cx b) { return {a.r * b.r - a.i * b.i, a.r * b.i + a.i * b.r}; }
__device__ __forceinline__ cx cfma(cx a, cx b, cx c) { return {fmaf(a.r, b.r, fmaf(-a.i, b.i, c.r)), fmaf(a.r, b.i, fmaf(a.i, b.r, c.i))}; }
__device__ __forceinline__ cx csq(cx a) { return {a.r * a.r - a.i * a.i, 2.f * a.r * a.i}; }
__device__ __forceinline__ cx unit(int num, int den) {
  int m = num & (den - 1);
  if (m >= den / 2) m -= den;
  float s, c;
  __sincosf((float)m * (-6.283185307179586f / (float)den), &s, &c);
  return {c, s};
}

__device__ __forceinline__ uint2 lds64(uint32_t a) {
  uint2 v;
  asm volatile("ld.shared.v2.u32 {%0,%1}, [%2];" : "=r"(v.x), "=r"(v.y) : "r"(a) : "memory");
  return v;
}
__device__ __forceinline__ void prep_taps(const uint4 (&sh)[2], uint32_t (&s)[2][4]) {
#pragma unroll
  for (int e = 0; e < 2; e++) {
    s[e][0] = __byte_perm(sh[e].x, sh[e].z, 0x5410); s[e][1] = __byte_perm(sh[e].x, sh[e].z, 0x7632);
    s[e][2] = __byte_perm(sh[e].y, sh[e].w, 0x5410); s[e][3] = __byte_perm(sh[e].y, sh[e].w, 0x7632);
  }
}
__device__ __forceinline__ void prep_math(const uint2 (&kk)[11], uint2 (&vv)[8], const uint32_t (&s)[2][4]) {
#pragma unroll
  for (int i = 0; i < 8; i++)
#pragma unroll
    for (int e = 0; e < 2; e++) {
      uint32_t a = hmul2((&kk[i].x)[e], s[e][3]);
      a = hfma2((&kk[i + 1].x)[e], s[e][2], a);
      a = hfma2((&kk[i + 2].x)[e], s[e][1], a);
      a = hfma2((&kk[i + 3].x)[e], s[e][0], a);
      (&vv[i].x)[e] = hmul2(a, (&vv[i].x)[e]);
    }
}
__device__ __forceinline__ void prep_store(const uint2 (&vv)[8], int d, int tb) {
  uint4* dst = g_u + (size_t)((d >> 5) * 32 + (tb >> 3)) * 256 + (d & 31) * 8 + ((tb & 7) ^ ((tb >> 3) & 1));
#pragma unroll
  for (int e = 0; e < 2; e++) {
#define U(i) (&vv[i].x)[e]
    stg128(dst + (2 * e) * 8, __byte_perm(U(0), U(1), 0x5410), __byte_perm(U(2), U(3), 0x5410),
           __byte_perm(U(4), U(5), 0x5410), __byte_perm(U(6), U(7), 0x5410));
    stg128(dst + (2 * e + 1) * 8, __byte_perm(U(0), U(1), 0x7632), __byte_perm(U(2), U(3), 0x7632),
           __byte_perm(U(4), U(5), 0x7632), __byte_perm(U(6), U(7), 0x7632));
#undef U
  }
}
template <int PG>
__device__ __forceinline__ void prep(const Ptrs& p, int ti, int pj, int w, int lane) {
  const int tb = lane & 7, chunk = 2 * w + (lane >> 4), ch = chunk * 8 + ((lane >> 3) & 1) * 4, d = pj * 128 + PG * 64 + ch;
  const uint4 sh[2] = {ldg128(p.shift + d * 4), ldg128(p.shift + d * 4 + 8)};
  uint32_t s[2][4];
  prep_taps(sh, s);
#pragma unroll 1
  for (int th = 0; th < 2; th++) {
    uint2 kk[11], vv[8];
    {
      const uint32_t in = S_STG + th * 16384 + (lane & 8);
      const uint32_t a0 = in + tb * 128 + ((chunk ^ tb) << 4);
      const uint32_t hb = tb ? in + (39 + tb) * 128 + ((chunk ^ (tb - 1)) << 4) : S_T + (PG * 2 + th) * 512 + ch * 2;
      const uint32_t hs = tb ? 1024 : 128;
      mbar_wait_long(B_PIN + 16 * PG + 8 * th, 0);
      if (th) TIM(29 + PG);
#pragma unroll
      for (int i = 0; i < 3; i++) kk[i] = lds64(hb + i * hs);
#pragma unroll
      for (int i = 0; i < 8; i++) { kk[3 + i] = lds64(a0 + i * 1024); vv[i] = lds64(a0 + 8192 + i * 1024); }
      prep_math(kk, vv, s);
      sched_fence<52 + PG>();
    }
    if (!PG) bar_arrive(th ? 11 : 3, 160);
    else if (elect_one()) mbar_arrive(B_SFREE + 8 * th);
    prep_store(vv, d, ti * 16 + th * 8 + tb);
  }
  bar_arrive(4 + PG, 160);
}

__device__ __forceinline__ int gate_step(int pj) { return pj ? 2 * pj : 16; }
__device__ __forceinline__ void gate_partial(const Ptrs& p, uint32_t tag, int ti, int pj, int w, int lane) {
  const int ck = lane & 7, s0 = gate_step(pj);
  const uint4 gw[2] = {ldg128(p.gw + pj * 128 + ck * 8), ldg128(p.gw + pj * 128 + 64 + ck * 8)};
  float s[8];
  mbar_wait_long(B_GATE, 0);
#pragma unroll
  for (int h = 0; h < 2; h++) {
    const int sl = (s0 + h) % NS;
    mbar_wait(B_FULL + 8 * sl, ((s0 + h) / NS) & 1);
#pragma unroll
    for (int i = 0; i < 8; i++) {
      const uint4 x = lds128(sb + sl * STAGE + 16384 + (32 * w + (lane >> 3) * 8 + i) * 128 + ((ck ^ i) << 4));
      const uint32_t q = hfma2(x.x, gw[h].x, hfma2(x.y, gw[h].y, hfma2(x.z, gw[h].z, hmul2(x.w, gw[h].w))));
      s[i] = h ? s[i] + (bf_lo(q) + bf_hi(q)) : bf_lo(q) + bf_hi(q);
    }
  }
  fence_async_smem();
  __syncwarp();
  if (elect_one()) mbar_arrive(B_GATE + 8);
#pragma unroll
  for (int o = 4; o > 0; o >>= 1)
#pragma unroll
    for (int i = 0; i < o; i++) {
      const bool up = ck & o;
      s[i] = (up ? s[i + o] : s[i]) + __shfl_xor_sync(~0u, up ? s[i] : s[i + o], o);
    }
  const int j = 4 * w + (lane >> 3);
  asm volatile("st.relaxed.gpu.global.u32 [%0], %1;" ::"l"(g_gate + pj * SEQ + ti * 128 + 32 * (ck >> 1) + 2 * j + (ck & 1)),
               "r"((__float_as_uint(s[0]) & ~3u) | tag) : "memory");
}
__device__ __forceinline__ void gate_finish(int ti, int tid) {
  const uint32_t tag = (lds32(S_EP) + 1) & 3;
  float l;
  int n = SPIN_LIMIT;
  bool bad;
  do {
    uint32_t v[8], x = 0;
#pragma unroll
    for (int j = 0; j < 8; j++) v[j] = ld_relaxed(g_gate + j * SEQ + ti * 128 + tid);
    l = 0.f;
#pragma unroll
    for (int j = 0; j < 8; j++) { x |= v[j] ^ tag; l += __uint_as_float(v[j]); }
    bad = __any_sync(~0u, x & 3);
  } while (bad && --n);
  trap_if(n == 0);
  const float g = bf_round(__fdividef(1.f, 1.f + __expf(-bf_round(l))));
  asm volatile("st.shared.f32 [%0], %1;" ::"r"(S_G + tid * 4), "f"(g) : "memory");
}

__device__ __forceinline__ void conv_tables(int tid) {
  {
    const int s = tid >> 5, n1 = tid & 31;
    uint32_t re[4], im[4];
#pragma unroll
    for (int e = 0; e < 4; e++) {
      cx a = unit(n1 * (4 * (8 * s + 2 * e) + 1), 128), b = unit(n1 * (4 * (8 * s + 2 * e + 1) + 1), 128);
      re[e] = pack2(a.r * 0.125f, b.r * 0.125f); im[e] = pack2(a.i * 0.125f, b.i * 0.125f);
    }
    sts128(S_M1 + (2 * s) * 512 + n1 * 16, re[0], re[1], re[2], re[3]);
    sts128(S_M1 + (2 * s + 1) * 512 + n1 * 16, im[0], im[1], im[2], im[3]);
  }
  {
    const int kg = tid >> 5, n = tid & 31;
    const int pi = kg >> 1, po = n >> 4, f2 = n & 15;
    uint32_t fw[4];
#pragma unroll
    for (int e = 0; e < 4; e++) {
      int n2 = (kg & 1) * 8 + 2 * e;
      cx a = unit(n2 * f2, 16), b = unit((n2 + 1) * f2, 16);
      float sg = pi ? -1.f : 1.f;
      float x0 = (pi == po) ? a.r : sg * a.i, x1 = (pi == po) ? b.r : sg * b.i;
      fw[e] = pack2(x0, x1);
    }
    sts128(S_M2 + kg * 512 + n * 16, fw[0], fw[1], fw[2], fw[3]);
  }
  fence_async_smem();
}
__device__ __forceinline__ constexpr int jj_of(int o) { return o == 7 ? 3 : o + (o >= 3); }
__device__ __forceinline__ int conv_chan(int ti, int pj, int jj) { return pj * 128 + jj * 16 + ti; }

struct ConvCtx {
  uint32_t buf, inbar;
  int nb, n;
  int ti, pj, j;
  __device__ __forceinline__ int chan(int c) const {
    return j < 0 ? conv_chan(ti, pj, jj_of(c)) : conv_chan((j + 12 * c) >> 3, (j + 12 * c) & 7, 3);
  }
};
__device__ __forceinline__ ConvCtx conv_ctx(int spare, int wg, int ti, int pj) {
  const int j = spare < 0 ? -1 : spare * 3 + wg;
  return {wg == 2 ? S_CIN : sb + wg * 32768, wg == 2 ? B_CINF : (wg ? B_PIN : B_FULL), 4 + 4 * wg, j < 0 ? 7 : (j < 8 ? 11 : 10), ti, pj, j};
}
#define CDESC(a) mkdesc(dlo(a, 512), 128, 0)
struct ConvTw { uint32_t r[2], i[2], n[2]; };

__device__ __forceinline__ void cv_tw1(float (&d)[64], uint32_t (&R)[16], uint32_t (&I)[16], const ConvTw& t, int i) {
#pragma unroll
  for (int j = 8 * (i & 1); j < 8 * (i & 1) + 8; j++) {
    if (i < 2) {
      R[j] = pack2(d[4 * j], d[4 * j + 1]); I[j] = pack2(d[4 * j + 2], d[4 * j + 3]);
    } else {
      const uint32_t xr = R[j], xi = I[j];
      R[j] = hfma2(xr, t.r[j & 1], hmul2(xi, t.n[j & 1]));
      I[j] = hfma2(xr, t.i[j & 1], hmul2(xi, t.r[j & 1]));
    }
  }
}
template <int N>
__device__ __forceinline__ void cv_pack(float (&X)[16], uint32_t (&P)[N][2][2], int q) {
#pragma unroll
  for (int k = 0; k < 2; k++)
#pragma unroll
    for (int j = 0; j < 4; j++) P[2 * q + k][j >> 1][j & 1] = pack2(X[4 * j + 2 * k], X[4 * j + 2 * k + 1]);
}
__device__ __forceinline__ void cv_overlap(uint32_t (&P)[8][2][2]) {
#pragma unroll
  for (int k = 3; k > 0; k--)
#pragma unroll
    for (int hh = 0; hh < 2; hh++) {
      P[k][0][hh] = hsub2(P[k][0][hh], P[k - 1][1][hh]);
      P[k][1][hh] = hadd2(P[k][1][hh], P[k - 1][0][hh]);
    }
}
__device__ __forceinline__ void cv_pw(uint32_t (&P)[8][2][2], uint32_t (&Q)[4][2][2]) {
#pragma unroll
  for (int jh = 0; jh < 8; jh++) {
    const int j = jh >> 1, hh = jh & 1;
    uint32_t qr = hmul2(P[4 + j][0][hh], P[0][0][hh]), qi = hmul2(P[4 + j][0][hh], P[0][1][hh]);
    qr = hfma2(hneg2(P[4 + j][1][hh]), P[0][1][hh], qr);
    qi = hfma2(P[4 + j][1][hh], P[0][0][hh], qi);
#pragma unroll
    for (int k = j - 1; k >= 0; k--) {
      qr = hfma2(P[4 + k][0][hh], P[j - k][0][hh], qr);
      qi = hfma2(P[4 + k][0][hh], P[j - k][1][hh], qi);
      qr = hfma2(hneg2(P[4 + k][1][hh]), P[j - k][1][hh], qr);
      qi = hfma2(P[4 + k][1][hh], P[j - k][0][hh], qi);
    }
    Q[j][0][hh] = qr; Q[j][1][hh] = qi;
  }
}
__device__ __forceinline__ void cv_tw2(uint32_t (&Q)[4][2][2], const ConvTw& t, int k) {
#pragma unroll
  for (int hh = 0; hh < 2; hh++) {
    const uint32_t xr = Q[k][0][hh], xi = Q[k][1][hh];
    Q[k][0][hh] = hfma2(xr, t.r[hh], hmul2(xi, t.i[hh]));
    Q[k][1][hh] = hfma2(xr, t.n[hh], hmul2(xi, t.r[hh]));
  }
}
__device__ __forceinline__ void cv_out0(float (&Y)[16], uint32_t T, int w, int lane) {
  reg_fence(Y);
  const uint32_t za = T + w * 2048 + (lane >> 4) * 256 + (lane & 7) * 32 + (((lane >> 3) ^ (lane >> 2)) & 1) * 16;
#pragma unroll
  for (int jj = 0; jj < 2; jj++)
    stsm4t(za + jj * 512, pack2(Y[8 * jj], Y[8 * jj + 1]), pack2(Y[8 * jj + 2], Y[8 * jj + 3]),
           pack2(Y[8 * jj + 4], Y[8 * jj + 5]), pack2(Y[8 * jj + 6], Y[8 * jj + 7]));
}

__device__ __forceinline__ void cv_out1(const uint4& z0, const uint4& z1, const ConvCtx& cc, uint32_t keep, uint32_t tag, int ch, int w, int lane) {
  uint4* zp = g_z + (size_t)cc.chan(ch) * 256 + w * 64 + lane;
#define TG(v) ((v & keep) | (tag & ~keep))
  asm volatile("st.relaxed.gpu.global.v4.u32 [%0], {%1,%2,%3,%4};" ::"l"(zp), "r"(TG(z0.x)), "r"(TG(z0.y)), "r"(TG(z0.z)), "r"(TG(z0.w)) : "memory");
  asm volatile("st.relaxed.gpu.global.v4.u32 [%0], {%1,%2,%3,%4};" ::"l"(zp + 32), "r"(TG(z1.x)), "r"(TG(z1.y)), "r"(TG(z1.z)), "r"(TG(z1.w)) : "memory");
#undef TG
}
template <bool FW, bool BW, int K>
__device__ __forceinline__ void conv_step(uint32_t (&Q)[4][2][2], const ConvTw& t, const ConvCtx& cc, float dl, uint32_t tag, int ch, int w, int lane) {
#define SF(n) if ((SFM >> (n)) & 1) sched_fence_async<K + (n)>()
  float d[64], X[4][16], Z[2][16], Y[16];
  uint32_t R[16], I[16];
  uint4 a[4];
  const int nx = ch + 1;
  const uint32_t T = cc.buf + 16384;
  float dv;
  TIMC(1);
  if (FW) {
    dv = __shfl_sync(~0u, dl, nx);
    mbar_wait(cc.inbar + 8 * (nx & 1), (nx >> 1) & 1);
  }
  TIMC(2);
  WG_FENCE();
  if (BW) {
#pragma unroll
    for (int q = 0; q < 2; q++) {
      wgmma_rs32<0, 1>(Z[q], Q[2 * q][0][0], Q[2 * q + 1][0][0], Q[2 * q][0][1], Q[2 * q + 1][0][1], mkdesc(dlo(S_M2, 128), 512, 0));
      wgmma_rs32<1, 1>(Z[q], Q[2 * q][1][0], Q[2 * q + 1][1][0], Q[2 * q][1][1], Q[2 * q + 1][1][1], mkdesc(dlo(S_M2 + 256, 128), 512, 0));
    }
    WG_COMMIT();
  }
  if (FW) {
    const uint32_t lo = dlo(0, 1024) + (cc.buf >> 4) + (nx & 1) * 512;
    wgmma_ss128<1, 1, 0>(d, mkdesc(dlo(S_M1, 128), 512, 0), mkdesc(lo, 256, 3));
    wgmma_ss128<1, 1, 1>(d, mkdesc(dlo(S_M1 + 256, 128), 512, 0), mkdesc(lo + 32, 256, 3));
    WG_COMMIT();
  }
  TIMC(3);
  if (BW) {
    TIMC(4);
    WG_WAIT(FW ? 1 : 0);
    TIMC(5);
    reg_fence(Z[0]); reg_fence(Z[1]);
    uint32_t V[4][2][2];
    cv_pack(Z[0], V, 0); cv_pack(Z[1], V, 1);
    SF(0);
#pragma unroll
    for (int k = 0; k < 4; k++) cv_tw2(V, t, k);
    bar_sync(cc.nb, 128);
#pragma unroll
    for (int k = 0; k < 4; k++) stsm4(T + w * 512 + lane * 16 + k * 2048, V[k][0][0], V[k][0][1], V[k][1][0], V[k][1][1]);
    SF(1);
    TIMC(6);
  }
  if (FW) {
    WG_WAIT(0);
    reg_fence(d);
    if (nx + 2 < cc.n) bar_arrive(cc.nb + 2 + (nx & 1), 160);
    cv_tw1(d, R, I, t, 0); cv_tw1(d, R, I, t, 1);
    SF(2);
    TIMC(7);
  }
  if (BW) {
    bar_sync(cc.nb, 128);
#pragma unroll
    for (int s = 0; s < 4; s++) a[s] = ldsm4t(T + (4 * w + s) * 512 + lane * 16);
  }
  if (FW) { cv_tw1(d, R, I, t, 2); cv_tw1(d, R, I, t, 3); }
  sched_fence<K + 3>();
  TIMC(8);
  WG_FENCE();
  if (BW) {
    wgmma_rs32<0>(Y, a[0].x, a[0].y, a[0].z, a[0].w, CDESC(S_M1));
#pragma unroll
    for (int i = 1; i < 4; i++) wgmma_rs32<1>(Y, a[i].x, a[i].y, a[i].z, a[i].w, CDESC(S_M1 + 1024 * i));
  }
  if (FW) {
#pragma unroll
    for (int q = 0; q < 4; q++) {
      if (q == 2) WG_COMMIT();
      wgmma_rs32<0>(X[q], R[4 * q], R[4 * q + 2], R[4 * q + 1], R[4 * q + 3], CDESC(S_M2));
      wgmma_rs32<1>(X[q], I[4 * q], I[4 * q + 2], I[4 * q + 1], I[4 * q + 3], CDESC(S_M2 + 1024));
    }
  }
  WG_COMMIT();
  TIMC(9);
  WG_WAIT(FW ? 1 : 0);
  TIMC(10);
  uint4 z0, z1;
  const uint32_t zr = T + w * 2048 + (lane ^ ((lane >> 3) & 1)) * 16;
  if (BW) {
    cv_out0(Y, T, w, lane);
    __syncwarp();
  }
  if (FW) {
    uint32_t P[8][2][2];
    reg_fence(X[0]); reg_fence(X[1]);
    cv_pack(X[0], P, 0); cv_pack(X[1], P, 1);
    cv_overlap(P);
    if (BW) { z0 = lds128(zr); z1 = lds128(zr + 512); }
    sched_fence_async<K + 7>();
    WG_WAIT(0);
    reg_fence(X[2]); reg_fence(X[3]);
    X[2][0] += dv; X[2][1] += dv; X[2][4] += dv; X[2][5] += dv;
    cv_pack(X[2], P, 2); cv_pack(X[3], P, 3);
    SF(4);
    TIMC(11);
    cv_pw(P, Q);
    SF(8);
  } else {
    z0 = lds128(zr); z1 = lds128(zr + 512);
  }
  if (BW) cv_out1(z0, z1, cc, FW && cc.j < 0 && ch < 4 ? ~0u : ~1u, tag, ch, w, lane);
  sched_fence<K + 5>();
  TIMC(13);
#undef SF
}

__device__ __forceinline__ void conv_main(const Ptrs& p, const ConvCtx& cc, int eb, int tid) {
  const int ti = cc.ti, pj = cc.pj;
  const int w = tid >> 5, lane = tid & 31;
  ConvTw t;
#pragma unroll
  for (int hh = 0; hh < 2; hh++) {
    const int n2 = 8 * hh + 2 * (lane & 3), m = 4 * (8 * w + (lane >> 2)) + 1;
    cx a = unit(n2 * m, 2048), b = unit((n2 + 1) * m, 2048);
    t.r[hh] = pack2(a.r, b.r); t.i[hh] = pack2(a.i, b.i); t.n[hh] = pack2(-a.i, -b.i);
  }
  const uint32_t tag = (ld_relaxed(g_epoch + eb) + 1) & 3;
  const float dl = 0.125f * __bfloat162float(p.ssmd[cc.chan(min(lane, cc.n - 1))]);
  if (cc.j < 0) {
    gate_partial(p, tag, ti, pj, w, lane);
    prep<1>(p, ti, pj, w, lane);
  }
  {
    uint32_t P[4][2][2];
    mbar_wait_long(cc.inbar, 0);
    TIM(20);
    conv_step<true, false, 10>(P, t, cc, dl, tag, -1, w, lane);
#pragma unroll 1
    for (int ch = 0; ch < cc.n - 1; ch++) {
      conv_step<true, true, 20>(P, t, cc, dl, tag, ch, w, lane);
      if (cc.j < 0 && (ch == 3 || ch == 5)) bar_arrive(ch == 3 ? 0 : 11, ch == 3 ? 160 : 256);
      if (ch == 0) TIM(21);
    }
    conv_step<false, true, 30>(P, t, cc, dl, tag, cc.n - 1, w, lane);
    if (cc.j < 0) bar_arrive(13, 256);
  }
  TIM(22);
}

__device__ __forceinline__ cx csel(bool k, cx a, cx b) { return {k ? a.r : b.r, k ? a.i : b.i}; }
__device__ __forceinline__ void ld2cx(uint32_t a, cx& x, cx& y) {
  const uint4 v = lds128(a);
  x = {__uint_as_float(v.x), __uint_as_float(v.y)};
  y = {__uint_as_float(v.z), __uint_as_float(v.w)};
}
__device__ __forceinline__ cx ldcx(uint32_t a) {
  cx x;
  asm volatile("ld.shared.v2.f32 {%0,%1}, [%2];" : "=f"(x.r), "=f"(x.i) : "r"(a) : "memory");
  return x;
}

__device__ __forceinline__ void scan_epilogue(float (&aR)[64], float (&aI)[64], uint32_t last_empty, int ph, int ti, int pj, int tid) {
  const int w = tid >> 5, lane = tid & 31, r = lane >> 2, c = lane & 3;
  const uint32_t par = S_PAR + (ph * 64 + 16 * w + r) * 16;
  uint4* agg = g_agg + ph * 16 * 256 + pj * 32 + 8 * w + r;
  const uint32_t tag = (lds32(S_EP) + 1) & 3;
  cx h[2];
  {
    cx lam[2], a[2];
#pragma unroll
    for (int q = 0; q < 2; q++) { lam[q] = ldcx(par + q * 128); h[q] = ldcx(par + 2048 + q * 128); }
    WG_WAIT(0);
    if (elect_one()) mbar_arrive(last_empty);
    asm volatile("setmaxnreg.inc.sync.aligned.u32 168;");
    reg_fence(aR); reg_fence(aI);
    TIM(3 + ph * 2);
#pragma unroll
    for (int q = 0; q < 2; q++) a[q] = {aR[2 * q], aI[2 * q]};
#pragma unroll
    for (int s = 1; s < 32; s++)
#pragma unroll
      for (int q = 0; q < 2; q++) {
        const int i = 4 * (s >> 1) + 2 * q + (s & 1);
        a[q] = cfma(lam[q], a[q], {aR[i], aI[i]});
      }
    sched_fence<1>();
    cx t[2][3];
#pragma unroll
    for (int q = 0; q < 2; q++)
#pragma unroll
      for (int k = 0; k < 3; k++) t[q][k] = {__shfl_up_sync(~0u, a[q].r, k + 1, 4), __shfl_up_sync(~0u, a[q].i, k + 1, 4)};
#pragma unroll
    for (int q = 0; q < 2; q++) {
      const cx z = {0.f, 0.f};
      cx ex = cfma(h[q], csel(c >= 3, t[q][2], z), csel(c >= 2, t[q][1], z));
      ex = cfma(h[q], ex, csel(c >= 1, t[q][0], z));
      a[q] = cfma(h[q], ex, a[q]);
      const cx u = cfma(lam[q], ex, {aR[2 * q], aI[2 * q]});
      aR[2 * q] = u.r; aI[2 * q] = u.i;
    }
    if (c == 3)
      asm volatile("st.relaxed.gpu.global.v4.u32 [%0], {%1,%2,%3,%4};" ::"l"(agg + ti * 256),
                   "r"((__float_as_uint(a[0].r) & ~3u) | tag), "r"((__float_as_uint(a[0].i) & ~3u) | tag),
                   "r"((__float_as_uint(a[1].r) & ~3u) | tag), "r"((__float_as_uint(a[1].i) & ~3u) | tag) : "memory");
    TIM(8 + ph * 4);
  }
  if (ti > 0) {
    const uint2* ap = (const uint2*)(agg + (ti - 1 - (c >> 1)) * 256) + (c & 1);
    const int cnt = ti - (c >> 1);
    const cx one = {1.f, 0.f};
    const cx l128 = ldcx(par + 2048 + 8 + (c & 1) * 128), l256 = csq(l128), fa = csel(c & 2, l128, one);
#pragma unroll
    for (int q = 0; q < 2; q++) h[q] = cmul(csel(c & 1, h[q], one), csel(c & 2, csq(h[q]), one));
    uint2 v[8];
    int n = SPIN_LIMIT;
    bool bad;
    __nanosleep(AGG_NS);
    do {
      uint32_t x = 0;
#pragma unroll
      for (int j = 0; j < 8; j++) {
        v[j] = make_uint2(tag, tag);
        asm volatile("{.reg .pred p; setp.lt.s32 p, %3, %4; @p ld.relaxed.gpu.global.v2.u32 {%0,%1}, [%2];}"
                     : "+r"(v[j].x), "+r"(v[j].y) : "l"(ap - j * 1024), "r"(2 * j), "r"(cnt) : "memory");
      }
#pragma unroll
      for (int j = 0; j < 8; j++) x |= (v[j].x ^ tag) | (v[j].y ^ tag);
      bad = __any_sync(~0u, x & 3);
    } while (bad && --n);
    trap_if(n == 0);
    cx a = {__uint_as_float(v[7].x), __uint_as_float(v[7].y)};
#pragma unroll
    for (int j = 6; j >= 0; j--) a = cfma(l256, a, {__uint_as_float(v[j].x), __uint_as_float(v[j].y)});
    a = cmul(a, fa);
    const cx t1 = {__shfl_xor_sync(~0u, a.r, 1), __shfl_xor_sync(~0u, a.i, 1)};
    const cx t2 = {__shfl_xor_sync(~0u, a.r, 2), __shfl_xor_sync(~0u, a.i, 2)};
    const cx t3 = {__shfl_xor_sync(~0u, a.r, 3), __shfl_xor_sync(~0u, a.i, 3)};
    const cx own = {a.r + t2.r, a.i + t2.i}, oth = {t1.r + t3.r, t1.i + t3.i};
#pragma unroll
    for (int q = 0; q < 2; q++) h[q] = cmul(csel((c & 1) == q, own, oth), h[q]);
  } else {
    h[0] = h[1] = {0.f, 0.f};
  }
  TIM(9 + ph * 4);
  cx lam[2];
  uint32_t cr[2], nci[2];
#pragma unroll
  for (int q = 0; q < 2; q++) {
    const uint4 v = lds128(par + q * 128);
    lam[q] = {__uint_as_float(v.x), __uint_as_float(v.y)};
    cr[q] = v.z; nci[q] = v.w;
  }
  uint4* hg = g_h + (size_t)(ti * 32 + ph * 16 + pj) * 1024 + w * 64 + r * 4 + (c ^ (r >> 1));
  uint32_t pr[4][2][4], pi[4][2][4], re[4][2][4];
#pragma unroll
  for (int i = 0; i < 4; i++) {
#pragma unroll
    for (int s2 = 0; s2 < 4; s2++)
#pragma unroll
      for (int q = 0; q < 2; q++) {
        const int k = 4 * (4 * i + s2) + 2 * q;
        cx h0 = cfma(lam[q], h[q], {aR[k], aI[k]});
        h[q] = cfma(lam[q], h0, {aR[k + 1], aI[k + 1]});
        pr[i][q][s2] = pack2(h0.r, h[q].r);
        pi[i][q][s2] = pack2(h0.i, h[q].i);
        re[i][q][s2] = hfma2(pr[i][q][s2], cr[q], hmul2(pi[i][q][s2], nci[q]));
      }
#pragma unroll
    for (int q = 0; q < 2; q++) stg128(hg + i * 256 + q * 32, re[i][q][0], re[i][q][1], re[i][q][2], re[i][q][3]);
    if (i == 0 && (P2F & 1)) sched_fence<7>();
    if (i == 1 && (P2F & 2)) sched_fence<8>();
    if (i == 2 && (P2F & 1)) sched_fence<6>();
  }
  bar_arrive(9, 160);
  sched_fence<9>();
  TIM(10 + ph * 4);
  mbar_wait(B_SFREE + 16 * ph, 0);
  if (ph == 0) mbar_wait(B_SFREE + 8, 0);
  const uint32_t hs = S_STG + w * 1024 + r * 64 + ((c ^ (r >> 1)) << 4);
#pragma unroll
  for (int q = 0; q < 2; q++) {
    const uint32_t ncr = cr[q] ^ 0x80008000u;
#pragma unroll
    for (int i = 0; i < 4; i++) {
      uint32_t o[4];
#pragma unroll
      for (int s2 = 0; s2 < 4; s2++) o[s2] = hfma2(pi[i][q][s2], ncr, hmul2(pr[i][q][s2], nci[q]));
      sts128(hs + i * 4096 + q * 512, re[i][q][0], re[i][q][1], re[i][q][2], re[i][q][3]);
      sts128(hs + 16384 + i * 4096 + q * 512, o[0], o[1], o[2], o[3]);
      if (IM_NS) __nanosleep(IM_NS);
      stg128(hg + 8192 + i * 256 + q * 32, o[0], o[1], o[2], o[3]);
    }
  }
  fence_async_smem();
  __syncwarp();
  if (elect_one()) mbar_arrive(B_LOC + 8 * ph);
  bar_arrive(10, 160);
  bar_sync(1 + ph, 128);
  asm volatile("setmaxnreg.dec.sync.aligned.u32 160;");
}

__device__ __forceinline__ constexpr uint32_t e_addr(int o, int mh) { return S_STG + (o * 2 + mh) * 2048; }
__device__ __forceinline__ void eterm(const Ptrs& p, int ti, int pj, int tid) {
  const int w = tid >> 5, lane = tid & 31, r = lane >> 2, c = lane & 3;
  const int trow = 64 * (w & 1) + 8 * (w >> 1) + r;
  const int rs = 2 * (r & 3) + (r >> 2);
  uint2 xv[2][8][2], ds[8];
#pragma unroll
  for (int jj = 0; jj < 8; jj++) ds[jj] = ldg64(p.dskip + pj * 128 + 16 * jj + 4 * c);
  gate_finish(ti, tid);
#pragma unroll
  for (int g = 0; g < 2; g++) {
    mbar_wait_long(B_XT + 8 * g, 0);
#pragma unroll
    for (int i = 0; i < 4; i++)
#pragma unroll
      for (int jj = 4 * g; jj < 4 * g + 4; jj++)
        xv[i >> 1][jj][i & 1] = lds64(sb + ((48 + g) % NS) * STAGE + (trow - r + rs + 16 * (i >> 1) + 32 * (i & 1)) * 128 + (((2 * (jj & 3) + (c >> 1)) ^ rs) << 4) + (c & 1) * 8);
  }
  fence_async_smem();
  __syncwarp();
  if (elect_one()) mbar_arrive(B_XT + 16);
  bar_sync(2, 128);
  TIM(31);
  uint32_t g2[2][2], og2[2][2];
#pragma unroll
  for (int mh = 0; mh < 2; mh++)
#pragma unroll
    for (int hf = 0; hf < 2; hf++) {
      uint32_t g;
      asm volatile("ld.shared.u32 %0, [%1];" : "=r"(g) : "r"(S_G + (trow + 16 * mh + 32 * hf) * 4) : "memory");
      g2[mh][hf] = __byte_perm(g, g, 0x3232);
      og2[mh][hf] = hsub2(0x3f803f80u, g2[mh][hf]);
    }
  const int dl = lane & 15;
  const uint32_t za = S_STG + (w & 1) * 2048 + dl * 128;
#pragma unroll
  for (int g = 0; g < 3; g++) {
    const int o0 = g ? 2 + 2 * g : 0, o1 = 4 + 2 * g;
    if (g == 0) {
      mbar_wait_long(B_ZT, 0);
    } else {
      bar_sync(9 + 2 * g, 256);
      const uint32_t tag = (lds32(S_EP) + 1) & 1;
      const int n = tid >> 4, ck = tid & 15;
      const uint4* zp = g_z + (size_t)(pj * 128 + 4 * (n >> 1) + (n & 1)) * 256 + ti * 16 + ck;
      uint4 v[4];
      int it = SPIN_LIMIT;
      bool bad;
      do {
        uint32_t x = 0;
#pragma unroll
        for (int i = 0; i < 4; i++)
          asm volatile("ld.relaxed.gpu.global.v4.u32 {%0,%1,%2,%3}, [%4];" : "=r"(v[i].x), "=r"(v[i].y), "=r"(v[i].z), "=r"(v[i].w)
                       : "l"(zp + (jj_of(o0 + (i >> 1)) * 16 + 2 * (i & 1)) * 256) : "memory");
#pragma unroll
        for (int i = 0; i < 4; i++) {
          v[i].x ^= tag; v[i].y ^= tag; v[i].z ^= tag; v[i].w ^= tag;
          x |= v[i].x | v[i].y | v[i].z | v[i].w;
        }
        bad = __any_sync(~0u, x & 1);
        if (bad) __nanosleep(ZL_NS);
      } while (bad && --it);
      trap_if(it == 0);
#pragma unroll
      for (int i = 0; i < 4; i++)
        sts128(S_STG + (o0 + (i >> 1)) * 4096 + (ck >> 3) * 2048 + (8 * (i & 1) + n) * 128 + (((ck & 7) ^ n) << 4), v[i].x, v[i].y, v[i].z, v[i].w);
      bar_sync(2, 128);
    }
    if (g == 2) TIM(16);
#pragma unroll
    for (int mh = 0; mh < 2; mh++) {
      const uint32_t zb = za + (((4 * (lane >> 4) + 2 * mh + (w >> 1)) ^ (dl & 7)) << 4);
#pragma unroll
      for (int o = o0; o < o1; o++) {
        const int jj = jj_of(o);
        uint4 z = ldsm4t(zb + o * 4096);
#pragma unroll
        for (int hf = 0; hf < 2; hf++) {
          uint2& x = xv[mh][jj][hf];
          x.x = hmul2(x.x, hfma2(og2[mh][hf], hf ? z.z : z.x, hmul2(g2[mh][hf], ds[jj].x)));
          x.y = hmul2(x.y, hfma2(og2[mh][hf], hf ? z.w : z.y, hmul2(g2[mh][hf], ds[jj].y)));
        }
      }
    }
    bar_sync(2, 128);
#pragma unroll
    for (int o = o0; o < o1; o++)
#pragma unroll
      for (int mh = 0; mh < 2; mh++) {
        const int jj = jj_of(o);
        sts128(e_addr(o, mh) + tid * 16, xv[mh][jj][0].x, xv[mh][jj][0].y, xv[mh][jj][1].x, xv[mh][jj][1].y);
      }
    bar_arrive(5 + g, 256);
    if (g == 0) TIM(1);
    if (g == 1) TIM(23);
  }
  TIM(17);
}

__device__ __forceinline__ void store_piece(float (&a)[64], float* op, int jj, const uint4& e, float g0, float g1) {
  stg128(op + 16 * jj, __float_as_uint(fmaf(g0, a[8 * jj], bf_lo(e.x))), __float_as_uint(fmaf(g0, a[8 * jj + 1], bf_hi(e.x))),
         __float_as_uint(fmaf(g0, a[8 * jj + 4], bf_lo(e.y))), __float_as_uint(fmaf(g0, a[8 * jj + 5], bf_hi(e.y))));
  stg128(op + 32 * DM + 16 * jj, __float_as_uint(fmaf(g1, a[8 * jj + 2], bf_lo(e.z))), __float_as_uint(fmaf(g1, a[8 * jj + 3], bf_hi(e.z))),
         __float_as_uint(fmaf(g1, a[8 * jj + 6], bf_lo(e.w))), __float_as_uint(fmaf(g1, a[8 * jj + 7], bf_hi(e.w))));
}

__device__ __forceinline__ void issue_g1(const Maps& m, int s, int sl, int ti, int pj) {
  const uint32_t bar = B_FULL + 8 * sl, dst = sb + sl * STAGE;
  const int k0 = (s & 15) * 64, ch = (s >> 4) * 512 + pj * 64;
  mbar_expect(bar, STAGE);
  tma4d(dst + 16384, &m.x, bar, k0, 0, 4 * ti, 0);
  tma2d(dst, &m.bre, bar, k0, ch);
  tma2d(dst + 8192, &m.bim, bar, k0, ch);
}
__device__ __forceinline__ void producer(const Maps& m, int ti, int pj) {
#pragma unroll
  for (int s = EARLY; s < NS; s++) issue_g1(m, s, s, ti, pj);
  int sl = 0, par = 0;
  const int gs = gate_step(pj);
  if (gs + 1 < NS) mbar_arrive(B_GATE);
#pragma unroll 1
  for (int s = NS; s < 32; s++) {
    mbar_wait(B_EMPTY + 8 * sl, par);
    if (s == gs + NS) mbar_wait(B_GATE + 8, 0);
    issue_g1(m, s, sl, ti, pj);
    if (s == gs + 1) mbar_arrive(B_GATE);
    if (++sl == NS) { sl = 0; par ^= 1; }
  }
#pragma unroll 1
  for (int q = 0; q < 32; q++) {
    mbar_wait(B_EMPTY + 8 * sl, par);
    const uint32_t bar = B_FULL + 8 * sl, dst = sb + sl * STAGE;
    const int ph = q >> 4, u = q & 15, part = u < 2 ? u : u >= 9, i = u - 2 - 7 * part;
    const int src = u < 2 ? pj : (i < 4 ? (~pj & 4) + i : (pj & 4) + i - 4 + (i - 4 >= (pj & 3)));
    if (q == 16 + NS) mbar_wait(B_XT + 16, 0);
    mbar_expect(bar, u < 2 ? 16384 : STAGE);
    tma5d(dst + 16384, part ? &m.cim : &m.cre, bar, ph * 512 + src * 64, 0, 0, 0, pj * 8);
    if (u < 2) {
      if (ph) {
        mbar_expect(B_XT + 8 * u, 16384);
        tma4d(dst, &m.x2, B_XT + 8 * u, pj * 128 + u * 64, 0, 0, ti * 16);
      }
    } else {
      if (i == 0) {
        mbar_wait(B_FLG + 8 * (2 * ph + part), 0);
        fence_async_global();
        if (part == 0) TIM(24 + ph);
      }
      bulk_load(dst, g_h + (size_t)(ti * 32 + ph * 16 + part * 8 + src) * 1024, 16384, bar);
    }
    if (++sl == NS) { sl = 0; par ^= 1; }
  }
}

__device__ __forceinline__ void poller(int ti, int pj, int lane, unsigned ep) {
  if (lane < 5) {
    const int f = lane < 4 ? F_H + lane * 16 + ti : F_Z + pj;
    const unsigned need = (ep + 1) * (lane < 4 ? 8 : 16);
    int n = SPIN_LIMIT;
    bool done = false;
    do {
      if (!done && (int)(ld_relaxed(g_flag + f * 32) - need) >= 0) {
        done = true;
        asm volatile("fence.acquire.gpu;" ::: "memory");
        mbar_arrive(B_FLG + 8 * lane);
      }
      if (POLL_NS) __nanosleep(POLL_NS);
    } while (!__all_sync(0x1fu, done) && --n);
    trap_if(n == 0);
  }
}
__device__ __forceinline__ void storer(const Maps& m, int ti, int pj) {
#pragma unroll 1
  for (int job = 0; job < 6; job++) {
    bar_sync(job < 2 ? 4 + job : 9 + (job & 1), 160);
    if (elect_one()) flag_release(job < 2 ? F_U + pj * 2 + job : F_H + (job - 2) * 16 + ti);
    __syncwarp();
    if (job == 2 || job == 4) TIM(7 + job * 2);
  }
  if (elect_one()) {
    mbar_wait_long(B_LOC + 16, 0);
    mbar_wait_long(B_FLG + 32, 0);
    fence_async_global();
    mbar_expect(B_ZT, 16384);
#pragma unroll 1
    for (int o = 0; o < 4; o++) {
      tma5d(S_STG + o * 4096, &m.z, B_ZT, ti * 128, 0, 0, 0, pj * 8 + jj_of(o));
      tma5d(S_STG + o * 4096 + 2048, &m.z, B_ZT, ti * 128 + 64, 0, 0, 0, pj * 8 + jj_of(o));
    }
  }
}

__device__ __forceinline__ void kv_loader(const Maps& m, int ti, int pj, unsigned t_start) {
  unsigned tt = t_start + KV0_AT;
#pragma unroll 1
  for (int st = 0; st < 4; st++) {
    const int d = pj * 128 + (st >> 1) * 64, tb = ti * 16 + (st & 1) * 8;
    const uint32_t bar = B_PIN + 8 * st;
    if (st >= 2) { bar_sync(st == 2 ? 3 : 11, 160); fence_async_smem(); }
    if (elect_one()) {
      mbar_expect(bar, 16384 + 384);
      if (st == 2) tt = t_start + KV1_AT;
      if ((int)(clock() - tt) > 0) tt = clock();
#pragma unroll 1
      for (int i = 0; i < 4; i++) {
        wait_clock(tt);
        tt += st >= 2 ? KV_GAP1 : KV_GAP0;
        tma3d(S_STG + (st & 1) * 16384 + i * 4096, (i & 2) ? &m.v : &m.k, bar, d, tb, (i & 1) * 4);
        if (i == 0) tma3d(S_T + st * 512, &m.kh, bar, d, tb - 1, 5);
      }
    }
    tt = __shfl_sync(~0u, tt, 0);
  }
}

__device__ __forceinline__ void conv_loader(const Maps& m, const Ptrs& p, const ConvCtx& cc, int eb, int lane, unsigned t_start) {
  const unsigned ep = ld_relaxed(g_epoch + eb);
  wait_clock(t_start + SPF_AT);
#pragma unroll 1
  for (int ch = 0; ch < cc.n; ch++) {
    const int d = cc.chan(ch);
    const uint32_t bar = cc.inbar + 8 * (ch & 1), dst = cc.buf + (ch & 1) * 8192;
    const bool first = ch == 0 || ch == (cc.j < 0 ? 3 : 1);
    if (ch >= 2) bar_sync(cc.nb + 2 + (ch & 1), 160);
    if (elect_one()) {
      mbar_expect(cc.inbar + 16, 4096);
      bulk_load(dst + 4096, p.f + (size_t)d * SEQ, 4096, cc.inbar + 16);
      if (!first) { mbar_expect(bar, 4096); tma3d(dst, &m.u, bar, 0, d & 31, d & ~31); }
      if (ch + 1 < cc.n) l2_prefetch(p.f + (size_t)cc.chan(ch + 1) * SEQ, 4096);
    }
    __syncwarp();
    const uint32_t a = dst + 4096 + 128 + (lane >> 3) * 256 + (lane & 7) * 16;
    mbar_wait(cc.inbar + 16, ch & 1);
#pragma unroll 1
    for (uint32_t i = a; i < a + 4096; i += 2048) {
      const uint4 x = lds128(i), y = lds128(i + 1024);
      __syncwarp();
      sts128(i ^ 16, x.x, x.y, x.z, x.w);
      sts128((i ^ 16) + 1024, y.x, y.y, y.z, y.w);
    }
    fence_async_smem();
    __syncwarp();
    if (elect_one()) {
      mbar_arrive(bar);
      if (first) {
        int n = SPIN_LIMIT;
        while ((int)(ld_relaxed(g_flag + (F_U + (d >> 6)) * 32) - (ep + 1) * 16) < 0 && --n) __nanosleep(POLL_NS);
        trap_if(n == 0);
        asm volatile("fence.acquire.gpu;" ::: "memory");
        fence_async_global();
        mbar_expect(bar, 4096);
        tma3d(dst, &m.u, bar, 0, d & 31, d & ~31);
      }
    }
    __syncwarp();
  }
  if (cc.j >= 0) {
    if (lane == 0) g_epoch[eb] = ep + 1;
  } else {
    bar_sync(0, 160);
    if (elect_one()) flag_release(F_Z + cc.pj);
  }
}

struct Ring { uint32_t off, par, rel; };
__device__ __forceinline__ void desc_touch(const uint64_t (&c)[12][NS]) {
  uint32_t x = 0;
#pragma unroll
  for (int i = 0; i < 12 * NS; i += 4) x |= (uint32_t)(&c[0][0])[i];
  trap_if((x | (uint32_t)c[11][NS - 1]) == 0);
}
template <int TA, bool TAB, bool LOC = false>
__device__ __forceinline__ void gemm_steps(float (&a0)[64], float (&a1)[64], Ring& r, int n, const uint64_t (&c)[12][NS], int slot) {
#pragma unroll 1
  do {
    const uint32_t off = r.off, rel = r.rel;
    full_wait(B_FULL + off, r.par, slot);
    r.rel = off;
    r.off += 8;
    if (r.off == 8 * NS) { r.off = 0; r.par ^= 1; }
    WG_FENCE();
#define DESC(i) (*(const uint64_t*)((const char*)c[i] + off))
#pragma unroll
    for (int k = 0; k < 4; k++) {
      const uint64_t db = TAB ? DESC(3 * k) : mkdesc(off * 256 + dlo(sb + 16384 + 32 * k, 16), 1024, 1);
      if (LOC) {
        wgmma_ss128<TA, 0, 1>(a0, mkdesc(dlo(S_STG + 32768 + 1024 * k, 4096) - n * 1024, 512, 2), db);
        wgmma_ss128<TA, 0, 1>(a1, mkdesc(dlo(S_STG + 32768 + 8192 + 1024 * k, 4096) - n * 1024, 512, 2), db);
      } else {
        wgmma_ss128<TA, 0, 1>(a0, TAB ? DESC(3 * k + 1) : mkdesc(off * 256 + dlo(sb + 32 * k, 16), 1024, 1), db);
        wgmma_ss128<TA, 0, 1>(a1, TAB ? DESC(3 * k + 2) : mkdesc(off * 256 + dlo(sb + 8192 + 32 * k, 16), 1024, 1), db);
      }
      if (k == RELK) {
        WG_COMMIT();
        WG_WAIT(1);
        if (elect_one()) mbar_arrive(B_EMPTY + rel);
      }
    }
#undef DESC
    if (RELK < 3) WG_COMMIT();
  } while (--n);
}

__global__ void __launch_bounds__(512, 1) fused_kernel(const __grid_constant__ Maps m, const __grid_constant__ Ptrs p) {
  extern __shared__ __align__(1024) uint8_t smem_raw[];
  int b = blockIdx.x;
  {
    int sm, nsm;
    asm volatile("mov.u32 %0, %%smid;" : "=r"(sm));
    asm volatile("mov.u32 %0, %%nsmid;" : "=r"(nsm));
    const int tp = sm >> 1, q = ((tp - 32) * 37) >> 8;
    const int g = tp < 32 ? tp & 7 : (tp < 60 ? tp - 31 - 7 * q : (tp < 62 ? 8 : 0));
    const int j = tp < 32 ? tp >> 3 : (tp < 60 ? 4 + q : (tp < 62 ? tp - 60 : tp - 58));
    if (nsm == 132) b = g * 16 + j * 2 + (sm & 1);
    b = __shfl_sync(~0u, b, 0);
  }
  const int spare = b - 128;
  const int ti = ((b >> 5) << 2) | (b & 3), pj = (((b >> 4) & 1) << 2) | ((b >> 2) & 3);
  const int wid = __shfl_sync(~0u, threadIdx.x >> 5, 0), wg = wid >> 2, tid = threadIdx.x & 127, lane = threadIdx.x & 31;
  if (wg == 0) TIM(0);
  const unsigned t_start = clock();
  if (wid == 12) {
    if (elect_one()) {
      asm volatile("prefetch.tensormap [%0];" ::"l"(&m.x) : "memory");
      asm volatile("prefetch.tensormap [%0];" ::"l"(&m.bre) : "memory");
      asm volatile("prefetch.tensormap [%0];" ::"l"(&m.bim) : "memory");
#pragma unroll
      for (int i = 0; i < NS; i++) mbar_init(B_FULL + 8 * i, (i < 2 && spare >= 0) ? 2 : 1);
      fence_async_smem();
#pragma unroll
      for (int s = 0; s < EARLY; s++) if (spare < 0) issue_g1(m, s, s, ti, pj);
    }
  } else if (wid == 13) {
    if (elect_one()) {
      trap_if((uint32_t)__cvta_generic_to_shared(smem_raw) != sb);
#pragma unroll
      for (uint32_t bar = B_EMPTY; bar < S_EP; bar += 8) mbar_init(bar, (bar < B_CINF || (bar >= B_SFREE && bar < B_GATE) || bar == B_GATE + 8 || bar == B_XT + 16) ? 4 :
                           (bar < B_CINF + 16 || ((bar == B_PIN || bar == B_PIN + 8) && spare >= 0)) ? 2 : 1);
      fence_async_smem();
    }
  }
  __syncwarp();
  if (wg == 3) {
    asm volatile("setmaxnreg.dec.sync.aligned.u32 %0;" ::"n"(RV == 2 ? 32 : 24));
    bar_sync(1, 128);
    if (spare < 0) {
      if (wid == 13) { bar_arrive(2, 160); bar_arrive(12, 160); }
      bar_arrive(0, 256);
    } else {
      bar_arrive(0, 512);
    }
    if (wid == 13) {
      if (spare < 0) {
        const unsigned ep = ld_relaxed(g_epoch + b);
        kv_loader(m, ti, pj, t_start);
        poller(ti, pj, lane, ep);
      }
    } else if (wid == 15 || spare >= 0) {
      const ConvCtx cc = conv_ctx(spare, wid == 12 ? 0 : wid - 13, ti, pj);
      conv_loader(m, p, cc, spare < 0 ? b : 128 + cc.j, lane, t_start);
    } else if (wid == 12) {
      if (elect_one()) producer(m, ti, pj);
    } else {
      storer(m, ti, pj);
    }
  } else if (wg == 2 || spare >= 0) {
    asm volatile("setmaxnreg.inc.sync.aligned.u32 160;");
    if (wg == 2) conv_tables(tid);
    if (spare < 0) bar_sync(12, 160); else bar_sync(0, 512);
    conv_main(p, conv_ctx(spare, wg, ti, pj), spare < 0 ? b : 128 + spare * 3 + wg, tid);
  } else {
    asm volatile("setmaxnreg.inc.sync.aligned.u32 %0;" ::"n"(RV == 3 ? 168 : 160));
    if (wg == 1) {
      const int ch = (tid >> 6) * 512 + pj * 64 + (tid & 63);
      const unsigned ep = ld_relaxed(g_epoch + b);
      const float lr = __bfloat162float(p.lre[ch]), li = __bfloat162float(p.lim[ch]);
      const float dt = bf_round(expf(__bfloat162float(p.ldt[ch])));
      float sn, cs;
      sincosf(dt * li, &sn, &cs);
      const float ex = expf(dt * lr);
      const float ar = ex * cs, ai = ex * sn;
      const float inv = 2.f / (lr * lr + li * li);
      const float cr = ((ar - 1.f) * lr + ai * li) * inv, ci = (ai * lr - (ar - 1.f) * li) * inv;
      sts128(S_PAR + tid * 16, __float_as_uint(ar), __float_as_uint(ai), pack2(cr, cr), pack2(-ci, -ci));
      const cx l32 = csq(csq(csq(csq(csq({ar, ai}))))), l128 = csq(csq(l32));
      sts128(S_PAR + 2048 + tid * 16, __float_as_uint(l32.r), __float_as_uint(l32.i), __float_as_uint(l128.r), __float_as_uint(l128.i));
      if (tid == 0) asm volatile("st.shared.u32 [%0], %1;" ::"r"(S_EP), "r"(ep) : "memory");
      bar_arrive(6, 256);
      bar_sync(2, 160);
      desc_touch(p.dc1);
      prep<0>(p, ti, pj, wid & 3, lane);
    }
    float a0[64], a1[64];
    Ring ring = {8u * wg * (16 % NS), wg * ((16u / NS) & 1), B_DUMMY - B_EMPTY};
    zero(a0); zero(a1);
    reg_fence(a0); reg_fence(a1);
    sched_fence<61>();
    bar_sync(wg * 7, 256);
    TIM(2 + wg * 2);
    if (wg == 0) gemm_steps<0, false>(a0, a1, ring, 15, p.dc1, 0);
    else gemm_steps<0, true>(a0, a1, ring, 15, p.dc1, 1);
    bar_arrive(7 + wg, 256);
    gemm_steps<0, false>(a0, a1, ring, 1, p.dc1, wg);
    if (wg == 0) bar_sync(6, 256);
    scan_epilogue(a0, a1, B_EMPTY + ring.rel, wg, ti, pj, tid);
    if (wg == 1) {
      eterm(p, ti, pj, tid);
    } else {
      ring = {8 * (32 % NS), (32 / NS) & 1, B_DUMMY - B_EMPTY};
      desc_touch(p.dc2);
      zero(a0); zero(a1);
      reg_fence(a0); reg_fence(a1);
      sched_fence<62>();
      bar_sync(8, 256);
      TIM(6);
#pragma unroll 1
      for (int o = 0; o < 4; o++) {
        if (!(o & 1)) {
          if (o) TIM(18);
          full_wait(B_LOC + 4 * o, 0, 2 + 2 * o);
          gemm_steps<1, true, true>(a0, a1, ring, 2, p.dc2, 3 + 2 * o);
        }
        gemm_steps<1, true>(a0, a1, ring, (o & 1) ? (o == 1 ? 13 : 13 - RES) : 1, p.dc2, 4 + 2 * o - (o & 1));
        if (!(o & 1) && elect_one()) {
          mbar_arrive(o ? B_LOC + 16 : B_SFREE + 16);
        }
      }
#pragma unroll
      for (int i = 0; i < RES; i++) {
        const int sl = (64 - RES + i) % NS;
        full_wait(B_FULL + 8 * sl, ((64 - RES + i) / NS) & 1, 10);
        WG_FENCE();
#pragma unroll
        for (int k = 0; k < 4; k++) wgmma_ss128<1, 0, 1>(a0, p.dc2[3 * k + 1][sl], p.dc2[3 * k][sl]);
        WG_COMMIT();
        if (i == 0 && RES == NS) { WG_WAIT(1); if (elect_one()) mbar_arrive(B_EMPTY + ring.rel); }
      }
      const int w = tid >> 5, trow = 16 * 0 + 64 * (w & 1) + 8 * (w >> 1) + (lane >> 2);
      float* op = p.out + (size_t)(ti * 128 + trow) * DM + pj * 128 + 4 * (lane & 3);
      float g[4];
      uint4 e;
#pragma unroll
      for (int i = 0; i < RES; i++) {
        const int sl = (64 - RES + i) % NS;
        if (i == 0) WG_FENCE();
#pragma unroll
        for (int k = 0; k < 4; k++) wgmma_ss128<1, 0, 1>(a1, p.dc2[3 * k + 2][sl], p.dc2[3 * k][sl]);
        WG_COMMIT();
        if (i == 0) {
          bar_sync(5, 256);
#pragma unroll
          for (int q = 0; q < 4; q++) g[q] = __uint_as_float(lds32(S_G + (trow + 16 * (q >> 1) + 32 * (q & 1)) * 4));
          e = lds128(e_addr(0, 0) + tid * 16);
          WG_WAIT(1);
          reg_fence(a0);
        }
        if (i < 4) {
          const uint4 e0 = e;
          e = lds128(e_addr((i + 1) & 3, i == 3) + tid * 16);
          store_piece(a0, op, jj_of(i), e0, g[0], g[1]);
        }
        if (i == 0) sched_fence_async<70>(); if (i == 1) sched_fence_async<71>(); if (i == 2) sched_fence_async<72>(); if (i == 3) sched_fence_async<73>();
      }
      TIM(26);
      WG_WAIT(0);
      reg_fence(a1);
      TIM(7);
#pragma unroll
      for (int o = 0; o < 8; o++) {
        if (o == 4 || o == 6) bar_sync(4 + (o >> 1), 256);
        if (o >= 4) store_piece(a0, op, jj_of(o), lds128(e_addr(o, 0) + tid * 16), g[0], g[1]);
        store_piece(a1, op + 16 * DM, jj_of(o), o ? lds128(e_addr(o, 1) + tid * 16) : e, g[2], g[3]);
      }
      if (tid == 0) g_epoch[b] = lds32(S_EP) + 1;
      TIM(19);
    }
  }
}

typedef CUresult (*EncFn)(CUtensorMap*, CUtensorMapDataType, cuuint32_t, void*, const cuuint64_t*, const cuuint64_t*,
                          const cuuint32_t*, const cuuint32_t*, CUtensorMapInterleave, CUtensorMapSwizzle,
                          CUtensorMapL2promotion, CUtensorMapFloatOOBfill);

void encode(EncFn enc, CUtensorMap* m, const void* ptr, int rank, const cuuint64_t* dims, const cuuint64_t* strides,
            const cuuint32_t* box, CUtensorMapSwizzle sw) {
  cuuint32_t es[5] = {1, 1, 1, 1, 1};
  enc(m, CU_TENSOR_MAP_DATA_TYPE_BFLOAT16, rank, const_cast<void*>(ptr), dims, strides, box, es, CU_TENSOR_MAP_INTERLEAVE_NONE,
      sw, PROMO, CU_TENSOR_MAP_FLOAT_OOB_FILL_NONE);
}

}

extern "C" void kernel_launch(void* const* d_in, const int* in_sizes, int n_in, void* d_out, int out_size) {
  typedef const __nv_bfloat16* bp;
  Ptrs p;
  p.x = (bp)d_in[0]; p.lre = (bp)d_in[1]; p.lim = (bp)d_in[2]; p.bre = (bp)d_in[3]; p.bim = (bp)d_in[4];
  p.cre = (bp)d_in[5]; p.cim = (bp)d_in[6]; p.ldt = (bp)d_in[7]; p.dskip = (bp)d_in[8];
  p.k = (bp)d_in[10]; p.v = (bp)d_in[11]; p.shift = (bp)d_in[12]; p.f = (bp)d_in[13]; p.ssmd = (bp)d_in[14];
  p.gw = (bp)d_in[15]; p.out = (float*)d_out;

  for (int sl = 0; sl < NS; sl++)
    for (int k = 0; k < 4; k++) {
      const uint64_t h128 = (uint64_t)(64u | (1u << 30)) << 32, h64 = (uint64_t)(32u | (2u << 30)) << 32;
      const uint32_t st = sb + sl * STAGE;
      p.dc1[3 * k][sl] = p.dc2[3 * k][sl] = h128 | dlo(st + 16384 + 32 * k, 16);
      p.dc1[3 * k + 1][sl] = h128 | dlo(st + 32 * k, 16);
      p.dc1[3 * k + 2][sl] = h128 | dlo(st + 8192 + 32 * k, 16);
      p.dc2[3 * k + 1][sl] = h64 | dlo(st + 1024 * k, 4096);
      p.dc2[3 * k + 2][sl] = h64 | dlo(st + 8192 + 1024 * k, 4096);
    }
  EncFn enc = nullptr;
  cudaDriverEntryPointQueryResult qr;
  cudaGetDriverEntryPoint("cuTensorMapEncodeTiled", (void**)&enc, cudaEnableDefault, &qr);
  void *zptr = nullptr, *uptr = nullptr;
  cudaGetSymbolAddress(&zptr, g_z);
  cudaGetSymbolAddress(&uptr, g_u);

  Maps m;
  {
    cuuint64_t d[4] = {1024, 2, 64, 16}, s[3] = {2048, 65536, 4096};
    cuuint32_t bx[4] = {64, 2, 4, 16};
    encode(enc, &m.x, p.x, 4, d, s, bx, CU_TENSOR_MAP_SWIZZLE_128B);
  }
  {
    cuuint64_t d[2] = {1024, 1024}, s[1] = {2048};
    cuuint32_t bx[2] = {64, 64};
    encode(enc, &m.bre, p.bre, 2, d, s, bx, CU_TENSOR_MAP_SWIZZLE_128B);
    encode(enc, &m.bim, p.bim, 2, d, s, bx, CU_TENSOR_MAP_SWIZZLE_128B);
  }
  {
    cuuint64_t d[5] = {1024, 2, 4, 2, 64}, s[4] = {2048, 8192, 4096, 32768};
    cuuint32_t bx[5] = {64, 2, 4, 2, 8};
    encode(enc, &m.cre, p.cre, 5, d, s, bx, CU_TENSOR_MAP_SWIZZLE_128B);
    encode(enc, &m.cim, p.cim, 5, d, s, bx, CU_TENSOR_MAP_SWIZZLE_128B);
  }
  {
    cuuint64_t d[3] = {64, 32, 1024}, s[2] = {128, 4096};
    cuuint32_t bx[3] = {64, 1, 32};
    encode(enc, &m.u, uptr, 3, d, s, bx, CU_TENSOR_MAP_SWIZZLE_NONE);
  }
  {
    cuuint64_t d[3] = {1024, 256, 8}, s[2] = {16384, 2048};
    cuuint32_t bx[3] = {64, 8, 4}, bh[3] = {64, 1, 3};
    encode(enc, &m.k, p.k, 3, d, s, bx, CU_TENSOR_MAP_SWIZZLE_128B);
    encode(enc, &m.kh, p.k, 3, d, s, bh, CU_TENSOR_MAP_SWIZZLE_NONE);
    encode(enc, &m.v, p.v, 3, d, s, bx, CU_TENSOR_MAP_SWIZZLE_128B);
  }
  {
    cuuint64_t d[5] = {2048, 2, 4, 2, 64}, s[4] = {4096, 16384, 8192, 65536};
    cuuint32_t bx[5] = {64, 2, 4, 2, 1};
    encode(enc, &m.z, zptr, 5, d, s, bx, CU_TENSOR_MAP_SWIZZLE_128B);
  }
  {
    cuuint64_t d[4] = {1024, 2, 4, 256}, s[3] = {8192, 2048, 16384};
    cuuint32_t bx[4] = {64, 2, 4, 16};
    encode(enc, &m.x2, p.x, 4, d, s, bx, CU_TENSOR_MAP_SWIZZLE_128B);
  }
  cudaFuncSetAttribute(fused_kernel, cudaFuncAttributeMaxDynamicSharedMemorySize, SMEM_BYTES);
  fused_kernel<<<132, 512, SMEM_BYTES, cudaStreamPerThread>>>(m, p);
}
```

```cpp
#include <cuda_runtime.h>
#include <cuda_bf16.h>
#include <cuda.h>
#include <stdint.h>

namespace {

constexpr int SEQ = 2048, DM = 1024;
#define NSV 5
constexpr int NS = NSV;
constexpr int STAGE = 32768;
#define KV0_AT 300
#define KV_GAP0 750
#define KV1_AT 8000
#define KV_GAP1 550
#define EARLY 2
#define SFM 2
#define RV 1
#define POLL_NS 60
#define IM_NS 100
#define SPF_AT 9000
#define RELK 0
#define RES 4
#define AGG_NS 200
#define ZL_NS 60
#define P2F 3
#define KEEP 8
#define LD_GAP 400
#define LDQ ""
#define PROMO CU_TENSOR_MAP_L2_PROMOTION_L2_128B
constexpr uint32_t sb = 1024;
constexpr uint32_t S_STG = sb + NS * STAGE;
constexpr uint32_t S_CIN = S_STG + 32768;
constexpr uint32_t S_T = S_CIN + 16384;
constexpr uint32_t S_M1 = S_T + 8192;
constexpr uint32_t S_M2 = S_M1 + 4096;
constexpr uint32_t S_PAR = S_M2 + 2048;
constexpr uint32_t S_G = S_PAR + 4096;
constexpr uint32_t S_BAR = S_G + 512;
constexpr int SMEM_BYTES = S_BAR + 512 - sb;
constexpr uint32_t B_FULL = S_BAR, B_EMPTY = B_FULL + 8 * NS, B_CINF = B_EMPTY + 8 * NS,
                   B_FLG = B_CINF + 24, B_SFREE = B_FLG + 40, B_LOC = B_SFREE + 24, B_ZT = B_LOC + 24,
                   B_XT = B_ZT + 8, B_PIN = B_XT + 32, B_DUMMY = B_PIN + 32, S_EP = B_DUMMY + 8;
constexpr int SPIN_LIMIT = 1 << 21;
constexpr int F_H = 0, F_U = 64, F_Z = 80;

struct alignas(64) Maps { CUtensorMap x, bre, bim, cre, cim, u, z, x2, k, kh, v; };
struct Ptrs {
  const __nv_bfloat16 *x, *lre, *lim, *ldt, *dskip, *k, *v, *shift, *f, *ssmd, *gw, *bre, *bim, *cre, *cim;
  float* out;
  uint64_t dc1[12][NS], dc2[12][NS];
};

__device__ uint4 g_h[16 * 32 * 1024];
__device__ uint4 g_u[1024 * 256];
__device__ uint4 g_z[1024 * 256];
__device__ uint4 g_agg[2 * 16 * 256];
__device__ unsigned g_gate[8 * SEQ];
__device__ unsigned g_flag[88 * 32];
__device__ unsigned g_epoch[140];
#define TIM(i)
#define TIMC(i)

#define WG_FENCE() asm volatile("wgmma.fence.sync.aligned;" ::: "memory")
#define WG_COMMIT() asm volatile("wgmma.commit_group.sync.aligned;" ::: "memory")
#define WG_WAIT(n) asm volatile("wgmma.wait_group.sync.aligned %0;" ::"n"(n) : "memory")
#define R8(d, o) "+f"(d[o + 0]), "+f"(d[o + 1]), "+f"(d[o + 2]), "+f"(d[o + 3]), "+f"(d[o + 4]), "+f"(d[o + 5]), "+f"(d[o + 6]), "+f"(d[o + 7])
#define W8(d, o) "=f"(d[o + 0]), "=f"(d[o + 1]), "=f"(d[o + 2]), "=f"(d[o + 3]), "=f"(d[o + 4]), "=f"(d[o + 5]), "=f"(d[o + 6]), "=f"(d[o + 7])
#define L16 "%0,%1,%2,%3,%4,%5,%6,%7,%8,%9,%10,%11,%12,%13,%14,%15"
#define L64 L16 ",%16,%17,%18,%19,%20,%21,%22,%23,%24,%25,%26,%27,%28,%29,%30,%31," \
  "%32,%33,%34,%35,%36,%37,%38,%39,%40,%41,%42,%43,%44,%45,%46,%47,%48,%49,%50,%51,%52,%53,%54,%55,%56,%57,%58,%59,%60,%61,%62,%63"

template <int TA, int TB, int ACC>
__device__ __forceinline__ void wgmma_ss128(float (&d)[64], uint64_t da, uint64_t db) {
  if (ACC)
    asm volatile("wgmma.mma_async.sync.aligned.m64n128k16.f32.bf16.bf16 {" L64 "}, %64, %65, 1, 1, 1, %66, %67;"
                 : R8(d, 0), R8(d, 8), R8(d, 16), R8(d, 24), R8(d, 32), R8(d, 40), R8(d, 48), R8(d, 56)
                 : "l"(da), "l"(db), "n"(TA), "n"(TB));
  else
    asm volatile("wgmma.mma_async.sync.aligned.m64n128k16.f32.bf16.bf16 {" L64 "}, %64, %65, 0, 1, 1, %66, %67;"
                 : W8(d, 0), W8(d, 8), W8(d, 16), W8(d, 24), W8(d, 32), W8(d, 40), W8(d, 48), W8(d, 56)
                 : "l"(da), "l"(db), "n"(TA), "n"(TB));
}
template <int ACC, int TB = 0>
__device__ __forceinline__ void wgmma_rs32(float (&d)[16], uint32_t a0, uint32_t a1, uint32_t a2, uint32_t a3, uint64_t db) {
  if (ACC)
    asm volatile("wgmma.mma_async.sync.aligned.m64n32k16.f32.bf16.bf16 {" L16 "}, {%16,%17,%18,%19}, %20, 1, 1, 1, %21;"
                 : R8(d, 0), R8(d, 8) : "r"(a0), "r"(a1), "r"(a2), "r"(a3), "l"(db), "n"(TB));
  else
    asm volatile("wgmma.mma_async.sync.aligned.m64n32k16.f32.bf16.bf16 {" L16 "}, {%16,%17,%18,%19}, %20, 0, 1, 1, %21;"
                 : W8(d, 0), W8(d, 8) : "r"(a0), "r"(a1), "r"(a2), "r"(a3), "l"(db), "n"(TB));
}
template <int N>
__device__ __forceinline__ void reg_fence(float (&d)[N]) {
#pragma unroll
  for (int i = 0; i < N; i++) asm volatile("" : "+f"(d[i])::"memory");
}
__host__ __device__ __forceinline__ constexpr uint32_t dlo(uint32_t addr, uint32_t lbo) { return (addr >> 4) + ((lbo >> 4) << 16); }
__device__ __forceinline__ uint64_t mkdesc(uint32_t lo, uint32_t sbo, uint32_t mode) {
  uint64_t d;
  asm("mov.b64 %0, {%1, %2};" : "=l"(d) : "r"(lo), "r"((sbo >> 4) | (mode << 30)));
  return d;
}
template <int N>
__device__ __forceinline__ void zero(float (&d)[N]) {
#pragma unroll
  for (int i = 0; i < N; i++) d[i] = 0.f;
}
__device__ __forceinline__ void trap_if(int c) {
  asm volatile("{.reg .pred p; .reg .b64 z; setp.ne.s32 p, %0, 0; mov.b64 z, 0; @p st.global.u32 [z], %0;}" ::"r"(c) : "memory");
}
template <int K>
__device__ __forceinline__ void sched_fence() {
  asm volatile("{.reg .pred p; setp.eq.u32 p, %0, %1; @p exit;}" ::"r"(gridDim.x), "n"(256 + K) : "memory");
}
template <int K>
__device__ __forceinline__ void sched_fence_async() {
  asm volatile("{.reg .pred p; .reg .u32 r; setp.ne.u32 p, %0, %1; @p bra.uni SFE;\n"
               "SFL: nanosleep.u32 1000; mov.u32 r, %%clock; setp.eq.u32 p, r, 0; @p bra.uni SFL;\nSFE: }" ::"r"(gridDim.x), "n"(256 + K) : "memory");
}
__device__ __forceinline__ bool elect_one() {
  uint32_t pred;
  asm volatile("{.reg .pred p; elect.sync _|p, 0xffffffff; selp.u32 %0, 1, 0, p;}" : "=r"(pred));
  return pred;
}
__device__ __forceinline__ void mbar_init(uint32_t bar, uint32_t cnt) {
  asm volatile("mbarrier.init.shared::cta.b64 [%0], %1;" ::"r"(bar), "r"(cnt) : "memory");
}
__device__ __forceinline__ bool mbar_try(uint32_t bar, uint32_t par) {
  uint32_t ok;
  asm volatile("{.reg .pred p; mbarrier.try_wait.parity.shared::cta.b64 p, [%1], %2; selp.u32 %0, 1, 0, p;}"
               : "=r"(ok) : "r"(bar), "r"(par) : "memory");
  return ok;
}
#undef DBGV
#define DBGV ((bar - S_BAR) * 2 + par)
__device__ __forceinline__ void mbar_wait(uint32_t bar, uint32_t par) {
  if (__builtin_expect(!mbar_try(bar, par), 0)) {
    int n = SPIN_LIMIT;
    while (!mbar_try(bar, par) && --n) {}
    trap_if(n == 0);
  }
}
#define full_wait(bar, par, slot) mbar_wait(bar, par)
__device__ __forceinline__ void mbar_wait_long(uint32_t bar, uint32_t par) {
  int n = SPIN_LIMIT;
  while (!mbar_try(bar, par) && --n) __nanosleep(100);
  trap_if(n == 0);
}
#undef DBGV
#define DBGV 0
__device__ __forceinline__ void mbar_arrive(uint32_t bar) {
  asm volatile("mbarrier.arrive.shared::cta.b64 _, [%0];" ::"r"(bar) : "memory");
}
__device__ __forceinline__ void mbar_expect(uint32_t bar, uint32_t bytes) {
  asm volatile("mbarrier.arrive.expect_tx.shared::cta.b64 _, [%0], %1;" ::"r"(bar), "r"(bytes) : "memory");
}
__device__ __forceinline__ void tma2d(uint32_t dst, const CUtensorMap* m, uint32_t bar, int c0, int c1) {
  asm volatile("cp.async.bulk.tensor.2d.shared::cluster.global.mbarrier::complete_tx::bytes [%0], [%1, {%3, %4}], [%2];"
               ::"r"(dst), "l"(m), "r"(bar), "r"(c0), "r"(c1) : "memory");
}
__device__ __forceinline__ void tma3d(uint32_t dst, const CUtensorMap* m, uint32_t bar, int c0, int c1, int c2) {
  asm volatile("cp.async.bulk.tensor.3d.shared::cluster.global.mbarrier::complete_tx::bytes [%0], [%1, {%3, %4, %5}], [%2];"
               ::"r"(dst), "l"(m), "r"(bar), "r"(c0), "r"(c1), "r"(c2) : "memory");
}
__device__ __forceinline__ void tma4d(uint32_t dst, const CUtensorMap* m, uint32_t bar, int c0, int c1, int c2, int c3) {
  asm volatile("cp.async.bulk.tensor.4d.shared::cluster.global.mbarrier::complete_tx::bytes [%0], [%1, {%3, %4, %5, %6}], [%2];"
               ::"r"(dst), "l"(m), "r"(bar), "r"(c0), "r"(c1), "r"(c2), "r"(c3) : "memory");
}
__device__ __forceinline__ void tma5d(uint32_t dst, const CUtensorMap* m, uint32_t bar, int c0, int c1, int c2, int c3, int c4) {
  asm volatile("cp.async.bulk.tensor.5d.shared::cluster.global.mbarrier::complete_tx::bytes [%0], [%1, {%3, %4, %5, %6, %7}], [%2];"
               ::"r"(dst), "l"(m), "r"(bar), "r"(c0), "r"(c1), "r"(c2), "r"(c3), "r"(c4) : "memory");
}
__device__ __forceinline__ void bulk_load(uint32_t dst, const void* src, uint32_t bytes, uint32_t bar) {
  asm volatile("cp.async.bulk.shared::cluster.global.mbarrier::complete_tx::bytes [%0], [%1], %2, [%3];"
               ::"r"(dst), "l"(src), "r"(bytes), "r"(bar) : "memory");
}
__device__ __forceinline__ void l2_prefetch(const void* src, uint32_t bytes) {
  asm volatile("cp.async.bulk.prefetch.L2.global [%0], %1;" ::"l"(src), "r"(bytes) : "memory");
}
__device__ __forceinline__ void bar_sync(int id, int n) { asm volatile("bar.sync %0, %1;" ::"r"(id), "r"(n) : "memory"); }
__device__ __forceinline__ void bar_arrive(int id, int n) { asm volatile("bar.arrive %0, %1;" ::"r"(id), "r"(n) : "memory"); }
__device__ __forceinline__ void fence_async_smem() { asm volatile("fence.proxy.async.shared::cta;" ::: "memory"); }
__device__ __forceinline__ void fence_async_global() { asm volatile("fence.proxy.async.global;" ::: "memory"); }
__device__ __forceinline__ void flag_add(int f) {
  asm volatile("red.relaxed.gpu.global.add.u32 [%0], 1;" ::"l"(g_flag + f * 32) : "memory");
}
__device__ __forceinline__ void flag_release(int f) {
  asm volatile("fence.release.gpu;" ::: "memory");
  flag_add(f);
}
__device__ __forceinline__ unsigned ld_relaxed(const unsigned* p) {
  unsigned v;
  asm volatile("ld.relaxed.gpu.global.u32 %0, [%1];" : "=r"(v) : "l"(p) : "memory");
  return v;
}
__device__ __forceinline__ void wait_clock(unsigned t) {
  int d;
  while ((d = (int)(t - (unsigned)clock())) > 0) __nanosleep(d > 600 ? 200 : 40);
}
__device__ __forceinline__ uint32_t pack2(float lo, float hi) {
  uint32_t r;
  asm("cvt.rn.bf16x2.f32 %0, %1, %2;" : "=r"(r) : "f"(hi), "f"(lo));
  return r;
}
__device__ __forceinline__ float bf_lo(uint32_t v) { return __uint_as_float(v << 16); }
__device__ __forceinline__ float bf_hi(uint32_t v) { return __uint_as_float(v & 0xffff0000u); }
__device__ __forceinline__ float bf_round(float v) { return __bfloat162float(__float2bfloat16_rn(v)); }
__device__ __forceinline__ uint32_t hmul2(uint32_t a, uint32_t b) {
  uint32_t r;
  asm("mul.rn.bf16x2 %0, %1, %2;" : "=r"(r) : "r"(a), "r"(b));
  return r;
}
__device__ __forceinline__ uint32_t hadd2(uint32_t a, uint32_t b) {
  uint32_t r;
  asm("add.rn.bf16x2 %0, %1, %2;" : "=r"(r) : "r"(a), "r"(b));
  return r;
}
__device__ __forceinline__ uint32_t hsub2(uint32_t a, uint32_t b) {
  uint32_t r;
  asm("sub.rn.bf16x2 %0, %1, %2;" : "=r"(r) : "r"(a), "r"(b));
  return r;
}
__device__ __forceinline__ uint32_t hfma2(uint32_t a, uint32_t b, uint32_t c) {
  uint32_t r;
  asm("fma.rn.bf16x2 %0, %1, %2, %3;" : "=r"(r) : "r"(a), "r"(b), "r"(c));
  return r;
}
__device__ __forceinline__ uint32_t hneg2(uint32_t a) {
  uint32_t r;
  asm("neg.bf16x2 %0, %1;" : "=r"(r) : "r"(a));
  return r;
}
__device__ __forceinline__ uint4 ldg128(const void* p) {
  uint4 v;
  asm volatile("ld.global.nc" LDQ ".v4.u32 {%0,%1,%2,%3}, [%4];" : "=r"(v.x), "=r"(v.y), "=r"(v.z), "=r"(v.w) : "l"(p));
  return v;
}
__device__ __forceinline__ uint2 ldg64(const void* p) {
  uint2 v;
  asm volatile("ld.global.nc.v2.u32 {%0,%1}, [%2];" : "=r"(v.x), "=r"(v.y) : "l"(p));
  return v;
}
__device__ __forceinline__ void stg128(void* p, uint32_t a, uint32_t b, uint32_t c, uint32_t d) {
  asm volatile("st.global.v4.u32 [%0], {%1,%2,%3,%4};" ::"l"(p), "r"(a), "r"(b), "r"(c), "r"(d) : "memory");
}
__device__ __forceinline__ void sts128(uint32_t a, uint32_t x, uint32_t y, uint32_t z, uint32_t w) {
  asm volatile("st.shared.v4.u32 [%0], {%1,%2,%3,%4};" ::"r"(a), "r"(x), "r"(y), "r"(z), "r"(w) : "memory");
}
__device__ __forceinline__ uint32_t lds32(uint32_t a) {
  uint32_t v;
  asm volatile("ld.shared.u32 %0, [%1];" : "=r"(v) : "r"(a) : "memory");
  return v;
}
__device__ __forceinline__ uint4 lds128(uint32_t a) {
  uint4 v;
  asm volatile("ld.shared.v4.u32 {%0,%1,%2,%3}, [%4];" : "=r"(v.x), "=r"(v.y), "=r"(v.z), "=r"(v.w) : "r"(a) : "memory");
  return v;
}
__device__ __forceinline__ void stsm4(uint32_t a, uint32_t x, uint32_t y, uint32_t z, uint32_t w) {
  asm volatile("stmatrix.sync.aligned.m8n8.x4.shared.b16 [%0], {%1,%2,%3,%4};" ::"r"(a), "r"(x), "r"(y), "r"(z), "r"(w) : "memory");
}
__device__ __forceinline__ void stsm4t(uint32_t a, uint32_t x, uint32_t y, uint32_t z, uint32_t w) {
  asm volatile("stmatrix.sync.aligned.m8n8.x4.trans.shared.b16 [%0], {%1,%2,%3,%4};" ::"r"(a), "r"(x), "r"(y), "r"(z), "r"(w) : "memory");
}
__device__ __forceinline__ uint4 ldsm4t(uint32_t a) {
  uint4 v;
  asm volatile("ldmatrix.sync.aligned.m8n8.x4.trans.shared.b16 {%0,%1,%2,%3}, [%4];" : "=r"(v.x), "=r"(v.y), "=r"(v.z), "=r"(v.w) : "r"(a) : "memory");
  return v;
}
struct cx { float r, i; };
__device__ __forceinline__ cx cmul(cx a, cx b) { return {a.r * b.r - a.i * b.i, a.r * b.i + a.i * b.r}; }
__device__ __forceinline__ cx cfma(cx a, cx b, cx c) { return {fmaf(a.r, b.r, fmaf(-a.i, b.i, c.r)), fmaf(a.r, b.i, fmaf(a.i, b.r, c.i))}; }
__device__ __forceinline__ cx csq(cx a) { return {a.r * a.r - a.i * a.i, 2.f * a.r * a.i}; }
__device__ __forceinline__ cx unit(int num, int den) {
  int m = num & (den - 1);
  if (m >= den / 2) m -= den;
  float s, c;
  __sincosf((float)m * (-6.283185307179586f / (float)den), &s, &c);
  return {c, s};
}

__device__ __forceinline__ uint2 lds64(uint32_t a) {
  uint2 v;
  asm volatile("ld.shared.v2.u32 {%0,%1}, [%2];" : "=r"(v.x), "=r"(v.y) : "r"(a) : "memory");
  return v;
}
__device__ __forceinline__ void prep_taps(const uint4 (&sh)[2], uint32_t (&s)[2][4]) {
#pragma unroll
  for (int e = 0; e < 2; e++) {
    s[e][0] = __byte_perm(sh[e].x, sh[e].z, 0x5410); s[e][1] = __byte_perm(sh[e].x, sh[e].z, 0x7632);
    s[e][2] = __byte_perm(sh[e].y, sh[e].w, 0x5410); s[e][3] = __byte_perm(sh[e].y, sh[e].w, 0x7632);
  }
}
__device__ __forceinline__ void prep_math(const uint2 (&kk)[11], uint2 (&vv)[8], const uint32_t (&s)[2][4]) {
#pragma unroll
  for (int i = 0; i < 8; i++)
#pragma unroll
    for (int e = 0; e < 2; e++) {
      uint32_t a = hmul2((&kk[i].x)[e], s[e][3]);
      a = hfma2((&kk[i + 1].x)[e], s[e][2], a);
      a = hfma2((&kk[i + 2].x)[e], s[e][1], a);
      a = hfma2((&kk[i + 3].x)[e], s[e][0], a);
      (&vv[i].x)[e] = hmul2(a, (&vv[i].x)[e]);
    }
}
__device__ __forceinline__ void prep_store(const uint2 (&vv)[8], int d, int tb) {
  uint4* dst = g_u + (size_t)((d >> 5) * 32 + (tb >> 3)) * 256 + (d & 31) * 8 + ((tb & 7) ^ ((tb >> 3) & 1));
#pragma unroll
  for (int e = 0; e < 2; e++) {
#define U(i) (&vv[i].x)[e]
    stg128(dst + (2 * e) * 8, __byte_perm(U(0), U(1), 0x5410), __byte_perm(U(2), U(3), 0x5410),
           __byte_perm(U(4), U(5), 0x5410), __byte_perm(U(6), U(7), 0x5410));
    stg128(dst + (2 * e + 1) * 8, __byte_perm(U(0), U(1), 0x7632), __byte_perm(U(2), U(3), 0x7632),
           __byte_perm(U(4), U(5), 0x7632), __byte_perm(U(6), U(7), 0x7632));
#undef U
  }
}
template <int PG>
__device__ __forceinline__ void prep(const Ptrs& p, int ti, int pj, int w, int lane) {
  const int tb = lane & 7, chunk = 2 * w + (lane >> 4), ch = chunk * 8 + ((lane >> 3) & 1) * 4, d = pj * 128 + PG * 64 + ch;
  const uint4 sh[2] = {ldg128(p.shift + d * 4), ldg128(p.shift + d * 4 + 8)};
  uint32_t s[2][4];
  prep_taps(sh, s);
#pragma unroll 1
  for (int th = 0; th < 2; th++) {
    uint2 kk[11], vv[8];
    {
      const uint32_t in = S_STG + th * 16384 + (lane & 8);
      const uint32_t a0 = in + tb * 128 + ((chunk ^ tb) << 4);
      const uint32_t hb = tb ? in + (39 + tb) * 128 + ((chunk ^ (tb - 1)) << 4) : S_T + (PG * 2 + th) * 512 + ch * 2;
      const uint32_t hs = tb ? 1024 : 128;
      mbar_wait_long(B_PIN + 16 * PG + 8 * th, 0);
      if (th) TIM(29 + PG);
#pragma unroll
      for (int i = 0; i < 3; i++) kk[i] = lds64(hb + i * hs);
#pragma unroll
      for (int i = 0; i < 8; i++) { kk[3 + i] = lds64(a0 + i * 1024); vv[i] = lds64(a0 + 8192 + i * 1024); }
      prep_math(kk, vv, s);
      sched_fence<52 + PG>();
    }
    if (!PG) bar_arrive(th ? 11 : 3, 160);
    else if (elect_one()) mbar_arrive(B_SFREE + 8 * th);
    prep_store(vv, d, ti * 16 + th * 8 + tb);
  }
  bar_arrive(4 + PG, 160);
}

__device__ __forceinline__ void gate_finish(int ti, int tid, uint32_t tag) {
  float l;
  int n = SPIN_LIMIT;
  bool bad;
  do {
    __nanosleep(250);
    uint32_t v[8], x = 0;
#pragma unroll
    for (int j = 0; j < 8; j++) v[j] = ld_relaxed(g_gate + j * SEQ + ti * 128 + tid) ^ tag;
    l = 0.f;
#pragma unroll
    for (int j = 0; j < 8; j++) { x |= v[j]; l += __uint_as_float(v[j]); }
    bad = __any_sync(~0u, x & 3);
  } while (bad && --n);
  trap_if(n == 0);
  const float g = bf_round(__fdividef(1.f, 1.f + __expf(-bf_round(l))));
  asm volatile("st.shared.f32 [%0], %1;" ::"r"(S_G + tid * 4), "f"(g) : "memory");
}

__device__ __forceinline__ void conv_tables(int tid) {
  {
    const int s = tid >> 5, n1 = tid & 31;
    uint32_t re[4], im[4];
#pragma unroll
    for (int e = 0; e < 4; e++) {
      cx a = unit(n1 * (4 * (8 * s + 2 * e) + 1), 128), b = unit(n1 * (4 * (8 * s + 2 * e + 1) + 1), 128);
      re[e] = pack2(a.r * 0.125f, b.r * 0.125f); im[e] = pack2(a.i * 0.125f, b.i * 0.125f);
    }
    sts128(S_M1 + (2 * s) * 512 + n1 * 16, re[0], re[1], re[2], re[3]);
    sts128(S_M1 + (2 * s + 1) * 512 + n1 * 16, im[0], im[1], im[2], im[3]);
  }
  {
    const int kg = tid >> 5, n = tid & 31;
    const int pi = kg >> 1, po = n >> 4, f2 = n & 15;
    uint32_t fw[4];
#pragma unroll
    for (int e = 0; e < 4; e++) {
      int n2 = (kg & 1) * 8 + 2 * e;
      cx a = unit(n2 * f2, 16), b = unit((n2 + 1) * f2, 16);
      float sg = pi ? -1.f : 1.f;
      float x0 = (pi == po) ? a.r : sg * a.i, x1 = (pi == po) ? b.r : sg * b.i;
      fw[e] = pack2(x0, x1);
    }
    sts128(S_M2 + kg * 512 + n * 16, fw[0], fw[1], fw[2], fw[3]);
  }
  fence_async_smem();
}
__device__ __forceinline__ constexpr int jj_of(int o) { return o == 7 ? 3 : o + (o >= 3); }
__device__ __forceinline__ int conv_chan(int ti, int pj, int jj) { return pj * 128 + jj * 16 + ti; }

struct ConvCtx {
  uint32_t buf, inbar;
  int nb, n;
  int ti, pj, j;
  __device__ __forceinline__ int chan(int c) const {
    return j < 0 ? conv_chan(ti, pj, jj_of(c)) : conv_chan(((j + 12 * c) >> 3) + (((j + 12 * c) >> 3) >= KEEP), (j + 12 * c) & 7, 3);
  }
};
__device__ __forceinline__ ConvCtx conv_ctx(int spare, int wg, int ti, int pj) {
  const int j = spare < 0 ? -1 : spare * 3 + wg;
  return {wg == 2 ? S_CIN : sb + wg * 32768, wg == 2 ? B_CINF : (wg ? B_PIN : B_FULL), 4 + 4 * wg, j < 0 ? 7 + (ti == KEEP) : (j < 8 && KEEP > 15 ? 11 : 10), ti, pj, j};
}
#define CDESC(a) mkdesc(dlo(a, 512), 128, 0)
struct ConvTw { uint32_t r[2], i[2], n[2]; };

__device__ __forceinline__ void cv_tw1(float (&d)[64], uint32_t (&R)[16], uint32_t (&I)[16], const ConvTw& t, int i) {
#pragma unroll
  for (int j = 8 * (i & 1); j < 8 * (i & 1) + 8; j++) {
    if (i < 2) {
      R[j] = pack2(d[4 * j], d[4 * j + 1]); I[j] = pack2(d[4 * j + 2], d[4 * j + 3]);
    } else {
      const uint32_t xr = R[j], xi = I[j];
      R[j] = hfma2(xr, t.r[j & 1], hmul2(xi, t.n[j & 1]));
      I[j] = hfma2(xr, t.i[j & 1], hmul2(xi, t.r[j & 1]));
    }
  }
}
template <int N>
__device__ __forceinline__ void cv_pack(float (&X)[16], uint32_t (&P)[N][2][2], int q) {
#pragma unroll
  for (int k = 0; k < 2; k++)
#pragma unroll
    for (int j = 0; j < 4; j++) P[2 * q + k][j >> 1][j & 1] = pack2(X[4 * j + 2 * k], X[4 * j + 2 * k + 1]);
}
__device__ __forceinline__ void cv_overlap(uint32_t (&P)[8][2][2]) {
#pragma unroll
  for (int k = 3; k > 0; k--)
#pragma unroll
    for (int hh = 0; hh < 2; hh++) {
      P[k][0][hh] = hsub2(P[k][0][hh], P[k - 1][1][hh]);
      P[k][1][hh] = hadd2(P[k][1][hh], P[k - 1][0][hh]);
    }
}
__device__ __forceinline__ void cv_pw(uint32_t (&P)[8][2][2], uint32_t (&Q)[4][2][2]) {
#pragma unroll
  for (int jh = 0; jh < 8; jh++) {
    const int j = jh >> 1, hh = jh & 1;
    uint32_t qr = hmul2(P[4 + j][0][hh], P[0][0][hh]), qi = hmul2(P[4 + j][0][hh], P[0][1][hh]);
    qr = hfma2(hneg2(P[4 + j][1][hh]), P[0][1][hh], qr);
    qi = hfma2(P[4 + j][1][hh], P[0][0][hh], qi);
#pragma unroll
    for (int k = j - 1; k >= 0; k--) {
      qr = hfma2(P[4 + k][0][hh], P[j - k][0][hh], qr);
      qi = hfma2(P[4 + k][0][hh], P[j - k][1][hh], qi);
      qr = hfma2(hneg2(P[4 + k][1][hh]), P[j - k][1][hh], qr);
      qi = hfma2(P[4 + k][1][hh], P[j - k][0][hh], qi);
    }
    Q[j][0][hh] = qr; Q[j][1][hh] = qi;
  }
}
__device__ __forceinline__ void cv_tw2(uint32_t (&Q)[4][2][2], const ConvTw& t, int k) {
#pragma unroll
  for (int hh = 0; hh < 2; hh++) {
    const uint32_t xr = Q[k][0][hh], xi = Q[k][1][hh];
    Q[k][0][hh] = hfma2(xr, t.r[hh], hmul2(xi, t.i[hh]));
    Q[k][1][hh] = hfma2(xr, t.n[hh], hmul2(xi, t.r[hh]));
  }
}
__device__ __forceinline__ void cv_out0(float (&Y)[16], uint32_t T, int w, int lane) {
  reg_fence(Y);
  const uint32_t za = T + w * 2048 + (lane >> 4) * 256 + (lane & 7) * 32 + (((lane >> 3) ^ (lane >> 2)) & 1) * 16;
#pragma unroll
  for (int jj = 0; jj < 2; jj++)
    stsm4t(za + jj * 512, pack2(Y[8 * jj], Y[8 * jj + 1]), pack2(Y[8 * jj + 2], Y[8 * jj + 3]),
           pack2(Y[8 * jj + 4], Y[8 * jj + 5]), pack2(Y[8 * jj + 6], Y[8 * jj + 7]));
}

__device__ __forceinline__ void cv_out1(const uint4& z0, const uint4& z1, const ConvCtx& cc, uint32_t keep, uint32_t tag, int ch, int w, int lane) {
  uint4* zp = g_z + (size_t)cc.chan(ch) * 256 + w * 64 + lane;
#define TG(v) ((v & keep) | (tag & ~keep))
  asm volatile("st.relaxed.gpu.global.v4.u32 [%0], {%1,%2,%3,%4};" ::"l"(zp), "r"(TG(z0.x)), "r"(TG(z0.y)), "r"(TG(z0.z)), "r"(TG(z0.w)) : "memory");
  asm volatile("st.relaxed.gpu.global.v4.u32 [%0], {%1,%2,%3,%4};" ::"l"(zp + 32), "r"(TG(z1.x)), "r"(TG(z1.y)), "r"(TG(z1.z)), "r"(TG(z1.w)) : "memory");
#undef TG
}
template <bool FW, bool BW, int K>
__device__ __forceinline__ void conv_step(uint32_t (&Q)[4][2][2], const ConvTw& t, const ConvCtx& cc, float dl, uint32_t tag, int ch, int w, int lane) {
#define SF(n) if ((SFM >> (n)) & 1) sched_fence_async<K + (n)>()
  float d[64], X[4][16], Z[2][16], Y[16];
  uint32_t R[16], I[16];
  uint4 a[4];
  const int nx = ch + 1;
  const uint32_t T = cc.buf + 16384;
  float dv;
  TIMC(1);
  if (FW) {
    dv = __shfl_sync(~0u, dl, nx);
    mbar_wait(cc.inbar + 8 * (nx & 1), (nx >> 1) & 1);
  }
  TIMC(2);
  WG_FENCE();
  if (BW) {
#pragma unroll
    for (int q = 0; q < 2; q++) {
      wgmma_rs32<0, 1>(Z[q], Q[2 * q][0][0], Q[2 * q + 1][0][0], Q[2 * q][0][1], Q[2 * q + 1][0][1], mkdesc(dlo(S_M2, 128), 512, 0));
      wgmma_rs32<1, 1>(Z[q], Q[2 * q][1][0], Q[2 * q + 1][1][0], Q[2 * q][1][1], Q[2 * q + 1][1][1], mkdesc(dlo(S_M2 + 256, 128), 512, 0));
    }
    WG_COMMIT();
  }
  if (FW) {
    const uint32_t lo = dlo(0, 1024) + (cc.buf >> 4) + (nx & 1) * 512;
    wgmma_ss128<1, 1, 0>(d, mkdesc(dlo(S_M1, 128), 512, 0), mkdesc(lo, 256, 3));
    wgmma_ss128<1, 1, 1>(d, mkdesc(dlo(S_M1 + 256, 128), 512, 0), mkdesc(lo + 32, 256, 3));
    WG_COMMIT();
  }
  TIMC(3);
  if (BW) {
    TIMC(4);
    WG_WAIT(FW ? 1 : 0);
    TIMC(5);
    reg_fence(Z[0]); reg_fence(Z[1]);
    uint32_t V[4][2][2];
    cv_pack(Z[0], V, 0); cv_pack(Z[1], V, 1);
    SF(0);
#pragma unroll
    for (int k = 0; k < 4; k++) cv_tw2(V, t, k);
    bar_sync(cc.nb, 128);
#pragma unroll
    for (int k = 0; k < 4; k++) stsm4(T + w * 512 + lane * 16 + k * 2048, V[k][0][0], V[k][0][1], V[k][1][0], V[k][1][1]);
    SF(1);
    TIMC(6);
  }
  if (FW) {
    WG_WAIT(0);
    reg_fence(d);
    if (nx + 2 < cc.n) bar_arrive(cc.nb + 2 + (nx & 1), 160);
    cv_tw1(d, R, I, t, 0); cv_tw1(d, R, I, t, 1);
    SF(2);
    TIMC(7);
  }
  if (BW) {
    bar_sync(cc.nb, 128);
#pragma unroll
    for (int s = 0; s < 4; s++) a[s] = ldsm4t(T + (4 * w + s) * 512 + lane * 16);
  }
  if (FW) { cv_tw1(d, R, I, t, 2); cv_tw1(d, R, I, t, 3); }
  sched_fence<K + 3>();
  TIMC(8);
  WG_FENCE();
  if (BW) {
    wgmma_rs32<0>(Y, a[0].x, a[0].y, a[0].z, a[0].w, CDESC(S_M1));
#pragma unroll
    for (int i = 1; i < 4; i++) wgmma_rs32<1>(Y, a[i].x, a[i].y, a[i].z, a[i].w, CDESC(S_M1 + 1024 * i));
  }
  if (FW) {
#pragma unroll
    for (int q = 0; q < 4; q++) {
      if (q == 2) WG_COMMIT();
      wgmma_rs32<0>(X[q], R[4 * q], R[4 * q + 2], R[4 * q + 1], R[4 * q + 3], CDESC(S_M2));
      wgmma_rs32<1>(X[q], I[4 * q], I[4 * q + 2], I[4 * q + 1], I[4 * q + 3], CDESC(S_M2 + 1024));
    }
  }
  WG_COMMIT();
  TIMC(9);
  WG_WAIT(FW ? 1 : 0);
  TIMC(10);
  uint4 z0, z1;
  const uint32_t zr = T + w * 2048 + (lane ^ ((lane >> 3) & 1)) * 16;
  if (BW) {
    cv_out0(Y, T, w, lane);
    __syncwarp();
  }
  if (FW) {
    uint32_t P[8][2][2];
    reg_fence(X[0]); reg_fence(X[1]);
    cv_pack(X[0], P, 0); cv_pack(X[1], P, 1);
    cv_overlap(P);
    if (BW) { z0 = lds128(zr); z1 = lds128(zr + 512); }
    sched_fence_async<K + 7>();
    WG_WAIT(0);
    reg_fence(X[2]); reg_fence(X[3]);
    X[2][0] += dv; X[2][1] += dv; X[2][4] += dv; X[2][5] += dv;
    cv_pack(X[2], P, 2); cv_pack(X[3], P, 3);
    SF(4);
    TIMC(11);
    cv_pw(P, Q);
    SF(8);
  } else {
    z0 = lds128(zr); z1 = lds128(zr + 512);
  }
  if (BW) cv_out1(z0, z1, cc, FW && cc.j < 0 && ch < 4 ? ~0u : ~1u, tag, ch, w, lane);
  sched_fence<K + 5>();
  TIMC(13);
#undef SF
}

__device__ __forceinline__ void conv_main(const Ptrs& p, const ConvCtx& cc, int eb, int tid) {
  const int ti = cc.ti, pj = cc.pj;
  const int w = tid >> 5, lane = tid & 31;
  const unsigned ep = ld_relaxed(g_epoch + eb);
  const __nv_bfloat16 dsk = p.ssmd[cc.chan(min(lane, cc.n - 1))];
  if (cc.nb == 12) conv_tables(tid);
  if (cc.j < 0) bar_sync(12, 160); else bar_sync(0, 512);
  ConvTw t;
#pragma unroll
  for (int hh = 0; hh < 2; hh++) {
    const int n2 = 8 * hh + 2 * (lane & 3), m = 4 * (8 * w + (lane >> 2)) + 1;
    cx a = unit(n2 * m, 2048), b = unit((n2 + 1) * m, 2048);
    t.r[hh] = pack2(a.r, b.r); t.i[hh] = pack2(a.i, b.i); t.n[hh] = pack2(-a.i, -b.i);
  }
  const uint32_t tag = (ep + 1) & 3;
  const float dl = 0.125f * __bfloat162float(dsk);
  if (cc.j < 0) prep<1>(p, ti, pj, w, lane);
  {
    uint32_t P[4][2][2];
    mbar_wait_long(cc.inbar, 0);
    TIM(20);
    conv_step<true, false, 10>(P, t, cc, dl, tag, -1, w, lane);
#pragma unroll 1
    for (int ch = 0; ch < cc.n - 1; ch++) {
      conv_step<true, true, 20>(P, t, cc, dl, tag, ch, w, lane);
      if (cc.j < 0 && ch == 3) bar_arrive(0, 160);
      if (ch == 0) TIM(21);
    }
    conv_step<false, true, 30>(P, t, cc, dl, tag, cc.n - 1, w, lane);
  }
  TIM(22);
}

__device__ __forceinline__ cx csel(bool k, cx a, cx b) { return {k ? a.r : b.r, k ? a.i : b.i}; }
__device__ __forceinline__ void ld2cx(uint32_t a, cx& x, cx& y) {
  const uint4 v = lds128(a);
  x = {__uint_as_float(v.x), __uint_as_float(v.y)};
  y = {__uint_as_float(v.z), __uint_as_float(v.w)};
}
__device__ __forceinline__ cx ldcx(uint32_t a) {
  cx x;
  asm volatile("ld.shared.v2.f32 {%0,%1}, [%2];" : "=f"(x.r), "=f"(x.i) : "r"(a) : "memory");
  return x;
}

__device__ __forceinline__ void scan_epilogue(float (&aR)[64], float (&aI)[64], uint32_t last_empty, int ph, int ti, int pj, int tid) {
  const int w = tid >> 5, lane = tid & 31, r = lane >> 2, c = lane & 3;
  const uint32_t par = S_PAR + (ph * 64 + 16 * w + r) * 16;
  uint4* agg = g_agg + ph * 16 * 256 + pj * 32 + 8 * w + r;
  const uint32_t tag = (lds32(S_EP) + 1) & 3;
  cx h[2];
  {
    cx lam[2], a[2];
#pragma unroll
    for (int q = 0; q < 2; q++) { lam[q] = ldcx(par + q * 128); h[q] = ldcx(par + 2048 + q * 128); }
    WG_WAIT(0);
    if (elect_one()) mbar_arrive(last_empty);
    asm volatile("setmaxnreg.inc.sync.aligned.u32 168;");
    reg_fence(aR); reg_fence(aI);
    TIM(3 + ph * 2);
#pragma unroll
    for (int q = 0; q < 2; q++) a[q] = {aR[2 * q], aI[2 * q]};
#pragma unroll
    for (int s = 1; s < 32; s++)
#pragma unroll
      for (int q = 0; q < 2; q++) {
        const int i = 4 * (s >> 1) + 2 * q + (s & 1);
        a[q] = cfma(lam[q], a[q], {aR[i], aI[i]});
      }
    sched_fence<1>();
    cx t[2][3];
#pragma unroll
    for (int q = 0; q < 2; q++)
#pragma unroll
      for (int k = 0; k < 3; k++) t[q][k] = {__shfl_up_sync(~0u, a[q].r, k + 1, 4), __shfl_up_sync(~0u, a[q].i, k + 1, 4)};
#pragma unroll
    for (int q = 0; q < 2; q++) {
      const cx z = {0.f, 0.f};
      cx ex = cfma(h[q], csel(c >= 3, t[q][2], z), csel(c >= 2, t[q][1], z));
      ex = cfma(h[q], ex, csel(c >= 1, t[q][0], z));
      a[q] = cfma(h[q], ex, a[q]);
      const cx u = cfma(lam[q], ex, {aR[2 * q], aI[2 * q]});
      aR[2 * q] = u.r; aI[2 * q] = u.i;
    }
    if (c == 3)
      asm volatile("st.relaxed.gpu.global.v4.u32 [%0], {%1,%2,%3,%4};" ::"l"(agg + ti * 256),
                   "r"((__float_as_uint(a[0].r) & ~3u) | tag), "r"((__float_as_uint(a[0].i) & ~3u) | tag),
                   "r"((__float_as_uint(a[1].r) & ~3u) | tag), "r"((__float_as_uint(a[1].i) & ~3u) | tag) : "memory");
    TIM(8 + ph * 4);
  }
  if (ti > 0) {
    const uint2* ap = (const uint2*)(agg + (ti - 1 - (c >> 1)) * 256) + (c & 1);
    const int cnt = ti - (c >> 1);
    const cx one = {1.f, 0.f};
    const cx l128 = ldcx(par + 2048 + 8 + (c & 1) * 128), l256 = csq(l128), fa = csel(c & 2, l128, one);
#pragma unroll
    for (int q = 0; q < 2; q++) h[q] = cmul(csel(c & 1, h[q], one), csel(c & 2, csq(h[q]), one));
    uint2 v[8];
    int n = SPIN_LIMIT;
    bool bad;
    __nanosleep(AGG_NS);
    do {
      uint32_t x = 0;
#pragma unroll
      for (int j = 0; j < 8; j++) {
        v[j] = make_uint2(tag, tag);
        asm volatile("{.reg .pred p; setp.lt.s32 p, %3, %4; @p ld.relaxed.gpu.global.v2.u32 {%0,%1}, [%2];}"
                     : "+r"(v[j].x), "+r"(v[j].y) : "l"(ap - j * 1024), "r"(2 * j), "r"(cnt) : "memory");
      }
#pragma unroll
      for (int j = 0; j < 8; j++) { v[j].x ^= tag; v[j].y ^= tag; x |= v[j].x | v[j].y; }
      bad = __any_sync(~0u, x & 3);
    } while (bad && --n);
    trap_if(n == 0);
    cx a = {__uint_as_float(v[7].x), __uint_as_float(v[7].y)};
#pragma unroll
    for (int j = 6; j >= 0; j--) a = cfma(l256, a, {__uint_as_float(v[j].x), __uint_as_float(v[j].y)});
    a = cmul(a, fa);
    const cx t1 = {__shfl_xor_sync(~0u, a.r, 1), __shfl_xor_sync(~0u, a.i, 1)};
    const cx t2 = {__shfl_xor_sync(~0u, a.r, 2), __shfl_xor_sync(~0u, a.i, 2)};
    const cx t3 = {__shfl_xor_sync(~0u, a.r, 3), __shfl_xor_sync(~0u, a.i, 3)};
    const cx own = {a.r + t2.r, a.i + t2.i}, oth = {t1.r + t3.r, t1.i + t3.i};
#pragma unroll
    for (int q = 0; q < 2; q++) h[q] = cmul(csel((c & 1) == q, own, oth), h[q]);
  } else {
    h[0] = h[1] = {0.f, 0.f};
  }
  TIM(9 + ph * 4);
  cx lam[2];
  uint32_t cr[2], nci[2];
#pragma unroll
  for (int q = 0; q < 2; q++) {
    const uint4 v = lds128(par + q * 128);
    lam[q] = {__uint_as_float(v.x), __uint_as_float(v.y)};
    cr[q] = v.z; nci[q] = v.w;
  }
  uint4* hg = g_h + (size_t)(ti * 32 + ph * 16 + pj) * 1024 + w * 64 + r * 4 + (c ^ (r >> 1));
  uint32_t pr[4][2][4], pi[4][2][4], re[4][2][4];
#pragma unroll
  for (int i = 0; i < 4; i++) {
#pragma unroll
    for (int s2 = 0; s2 < 4; s2++)
#pragma unroll
      for (int q = 0; q < 2; q++) {
        const int k = 4 * (4 * i + s2) + 2 * q;
        cx h0 = cfma(lam[q], h[q], {aR[k], aI[k]});
        h[q] = cfma(lam[q], h0, {aR[k + 1], aI[k + 1]});
        pr[i][q][s2] = pack2(h0.r, h[q].r);
        pi[i][q][s2] = pack2(h0.i, h[q].i);
        re[i][q][s2] = hfma2(pr[i][q][s2], cr[q], hmul2(pi[i][q][s2], nci[q]));
      }
#pragma unroll
    for (int q = 0; q < 2; q++) stg128(hg + i * 256 + q * 32, re[i][q][0], re[i][q][1], re[i][q][2], re[i][q][3]);
    if (i == 0 && (P2F & 1)) sched_fence<7>();
    if (i == 1 && (P2F & 2)) sched_fence<8>();
    if (i == 2 && (P2F & 1)) sched_fence<6>();
  }
  bar_arrive(9, 160);
  sched_fence<9>();
  TIM(10 + ph * 4);
  mbar_wait(B_SFREE + 16 * ph, 0);
  if (ph == 0) mbar_wait(B_SFREE + 8, 0);
  const uint32_t hs = S_STG + w * 1024 + r * 64 + ((c ^ (r >> 1)) << 4);
#pragma unroll
  for (int q = 0; q < 2; q++) {
    const uint32_t ncr = cr[q] ^ 0x80008000u;
#pragma unroll
    for (int i = 0; i < 4; i++) {
      uint32_t o[4];
#pragma unroll
      for (int s2 = 0; s2 < 4; s2++) o[s2] = hfma2(pi[i][q][s2], ncr, hmul2(pr[i][q][s2], nci[q]));
      sts128(hs + i * 4096 + q * 512, re[i][q][0], re[i][q][1], re[i][q][2], re[i][q][3]);
      sts128(hs + 16384 + i * 4096 + q * 512, o[0], o[1], o[2], o[3]);
      if (IM_NS) __nanosleep(IM_NS);
      stg128(hg + 8192 + i * 256 + q * 32, o[0], o[1], o[2], o[3]);
    }
  }
  fence_async_smem();
  __syncwarp();
  if (elect_one()) mbar_arrive(B_LOC + 8 * ph);
  bar_arrive(10, 160);
  bar_sync(1 + ph, 128);
  asm volatile("setmaxnreg.dec.sync.aligned.u32 160;");
}

__device__ __forceinline__ constexpr uint32_t e_addr(int o, int mh) { return S_STG + (o * 2 + mh) * 2048; }
__device__ __forceinline__ void eterm(const Ptrs& p, int ti, int pj, int tid) {
  const int w = tid >> 5, lane = tid & 31, r = lane >> 2, c = lane & 3;
  const int trow = 64 * (w & 1) + 8 * (w >> 1) + r;
  const int rs = 2 * (r & 3) + (r >> 2);
  uint2 xv[2][8][2], ds[8];
  {
    uint2 gw[8];
#pragma unroll
    for (int jj = 0; jj < 8; jj++) {
      gw[jj] = ldg64(p.gw + pj * 128 + 16 * jj + 4 * c);
      ds[jj] = ldg64(p.dskip + pj * 128 + 16 * jj + 4 * c);
    }
#pragma unroll
    for (int g = 0; g < 2; g++) {
      mbar_wait(B_XT + 8 * g, 0);
#pragma unroll
      for (int i = 0; i < 4; i++)
#pragma unroll
        for (int jj = 4 * g; jj < 4 * g + 4; jj++)
          xv[i >> 1][jj][i & 1] = lds64(sb + ((48 + g) % NS) * STAGE + (trow - r + rs + 16 * (i >> 1) + 32 * (i & 1)) * 128 + (((2 * (jj & 3) + (c >> 1)) ^ rs) << 4) + (c & 1) * 8);
      fence_async_smem();
      __syncwarp();
      if (elect_one()) mbar_arrive(B_XT + 16 + 8 * g);
    }
    sched_fence<55>();
    TIM(27);
    float s[4];
#pragma unroll
    for (int i = 0; i < 4; i++) {
      s[i] = 0.f;
#pragma unroll
      for (int jj = 0; jj < 8; jj += 2) {
        const uint2 x = xv[i >> 1][jj][i & 1], y = xv[i >> 1][jj + 1][i & 1];
        const uint32_t q = hfma2(x.x, gw[jj].x, hfma2(x.y, gw[jj].y, hfma2(y.x, gw[jj + 1].x, hmul2(y.y, gw[jj + 1].y))));
        s[i] += bf_lo(q) + bf_hi(q);
      }
    }
    float u0 = (c & 1) ? s[1] : s[0], v0 = (c & 1) ? s[0] : s[1];
    float u1 = (c & 1) ? s[3] : s[2], v1 = (c & 1) ? s[2] : s[3];
    u0 += __shfl_xor_sync(~0u, v0, 1);
    u1 += __shfl_xor_sync(~0u, v1, 1);
    float u = (c & 2) ? u1 : u0;
    u += __shfl_xor_sync(~0u, (c & 2) ? u0 : u1, 2);
    const uint32_t tag = (lds32(S_EP) + 1) & 3;
    asm volatile("st.relaxed.gpu.global.u32 [%0], %1;" ::"l"(g_gate + pj * SEQ + ti * 128 + trow + 16 * (c >> 1) + 32 * (c & 1)),
                 "r"((__float_as_uint(u) & ~3u) | tag) : "memory");
    gate_finish(ti, tid, tag);
  }
  bar_sync(2, 128);
  TIM(31);
  uint32_t g2[2][2], og2[2][2];
#pragma unroll
  for (int mh = 0; mh < 2; mh++)
#pragma unroll
    for (int hf = 0; hf < 2; hf++) {
      uint32_t g;
      asm volatile("ld.shared.u32 %0, [%1];" : "=r"(g) : "r"(S_G + (trow + 16 * mh + 32 * hf) * 4) : "memory");
      g2[mh][hf] = __byte_perm(g, g, 0x3232);
      og2[mh][hf] = hsub2(0x3f803f80u, g2[mh][hf]);
    }
  const int dl = lane & 15;
  const uint32_t za = S_STG + (w & 1) * 2048 + dl * 128;
  const uint32_t tag = (lds32(S_EP) + 1) & 1;
  const int zn = tid >> 4, ck = tid & 15;
  const uint4* zp = g_z + (size_t)(pj * 128 + 4 * (zn >> 1) + (zn & 1)) * 256 + ti * 16 + ck;
  uint4 v[4];
#define ZLOAD(o0) _Pragma("unroll") for (int i = 0; i < 4; i++) \
    asm volatile("ld.relaxed.gpu.global.v4.u32 {%0,%1,%2,%3}, [%4];" : "=r"(v[i].x), "=r"(v[i].y), "=r"(v[i].z), "=r"(v[i].w) \
                 : "l"(zp + (jj_of(o0 + (i >> 1)) * 16 + 2 * (i & 1)) * 256) : "memory")
#pragma unroll
  for (int g = 0; g < 3; g++) {
    const int o0 = g ? 2 + 2 * g : 0, o1 = 4 + 2 * g;
    if (g == 0) {
      mbar_wait_long(B_ZT, 0);
    } else {
      int it = SPIN_LIMIT;
      while (true) {
        uint32_t x = 0;
#pragma unroll
        for (int i = 0; i < 4; i++) {
          v[i].x ^= tag; v[i].y ^= tag; v[i].z ^= tag; v[i].w ^= tag;
          x |= v[i].x | v[i].y | v[i].z | v[i].w;
        }
        if (!__any_sync(~0u, x & 1) || !--it) break;
        __nanosleep(ZL_NS);
        ZLOAD(o0);
      }
      trap_if(it == 0);
#pragma unroll
      for (int i = 0; i < 4; i++)
        sts128(S_STG + (o0 + (i >> 1)) * 4096 + (ck >> 3) * 2048 + (8 * (i & 1) + zn) * 128 + (((ck & 7) ^ zn) << 4), v[i].x, v[i].y, v[i].z, v[i].w);
      bar_sync(2, 128);
    }
    if (g < 2) { ZLOAD(o1); }
    if (g == 2) TIM(16);
#pragma unroll
    for (int mh = 0; mh < 2; mh++) {
      const uint32_t zb = za + (((4 * (lane >> 4) + 2 * mh + (w >> 1)) ^ (dl & 7)) << 4);
#pragma unroll
      for (int o = o0; o < o1; o++) {
        const int jj = jj_of(o);
        uint4 z = ldsm4t(zb + o * 4096);
#pragma unroll
        for (int hf = 0; hf < 2; hf++) {
          uint2& x = xv[mh][jj][hf];
          x.x = hmul2(x.x, hfma2(og2[mh][hf], hf ? z.z : z.x, hmul2(g2[mh][hf], ds[jj].x)));
          x.y = hmul2(x.y, hfma2(og2[mh][hf], hf ? z.w : z.y, hmul2(g2[mh][hf], ds[jj].y)));
        }
      }
    }
    bar_sync(2, 128);
#pragma unroll
    for (int o = o0; o < o1; o++)
#pragma unroll
      for (int mh = 0; mh < 2; mh++) {
        const int jj = jj_of(o);
        sts128(e_addr(o, mh) + tid * 16, xv[mh][jj][0].x, xv[mh][jj][0].y, xv[mh][jj][1].x, xv[mh][jj][1].y);
      }
    bar_arrive(5 + g, 256);
    if (g == 0) TIM(1);
    if (g == 1) TIM(23);
  }
#undef ZLOAD
  TIM(17);
}

__device__ __forceinline__ void store_piece(float (&a)[64], float* op, int jj, const uint4& e, float g0, float g1) {
  stg128(op + 16 * jj, __float_as_uint(fmaf(g0, a[8 * jj], bf_lo(e.x))), __float_as_uint(fmaf(g0, a[8 * jj + 1], bf_hi(e.x))),
         __float_as_uint(fmaf(g0, a[8 * jj + 4], bf_lo(e.y))), __float_as_uint(fmaf(g0, a[8 * jj + 5], bf_hi(e.y))));
  stg128(op + 32 * DM + 16 * jj, __float_as_uint(fmaf(g1, a[8 * jj + 2], bf_lo(e.z))), __float_as_uint(fmaf(g1, a[8 * jj + 3], bf_hi(e.z))),
         __float_as_uint(fmaf(g1, a[8 * jj + 6], bf_lo(e.w))), __float_as_uint(fmaf(g1, a[8 * jj + 7], bf_hi(e.w))));
}

__device__ __forceinline__ void issue_g1(const Maps& m, int s, int sl, int ti, int pj) {
  const uint32_t bar = B_FULL + 8 * sl, dst = sb + sl * STAGE;
  const int k0 = (s & 15) * 64, ch = (s >> 4) * 512 + pj * 64;
  mbar_expect(bar, STAGE);
  tma4d(dst + 16384, &m.x, bar, k0, 0, 4 * ti, 0);
  tma2d(dst, &m.bre, bar, k0, ch);
  tma2d(dst + 8192, &m.bim, bar, k0, ch);
}
__device__ __forceinline__ void producer(const Maps& m, int ti, int pj) {
#pragma unroll
  for (int s = EARLY; s < NS; s++) issue_g1(m, s, s, ti, pj);
  int sl = 0, par = 0;
#pragma unroll 1
  for (int s = NS; s < 32; s++) {
    mbar_wait(B_EMPTY + 8 * sl, par);
    issue_g1(m, s, sl, ti, pj);
    if (++sl == NS) { sl = 0; par ^= 1; }
  }
#pragma unroll 1
  for (int q = 0; q < 32; q++) {
    mbar_wait(B_EMPTY + 8 * sl, par);
    const uint32_t bar = B_FULL + 8 * sl, dst = sb + sl * STAGE;
    const int ph = q >> 4, u = q & 15, part = u < 2 ? u : u >= 9, i = u - 2 - 7 * part;
    const int src = u < 2 ? pj : (i < 4 ? (~pj & 4) + i : (pj & 4) + i - 4 + (i - 4 >= (pj & 3)));
    if (q == 16 + NS || q == 17 + NS) mbar_wait(B_XT + 8 * (q - 14 - NS), 0);
    mbar_expect(bar, u < 2 ? 16384 : STAGE);
    tma5d(dst + 16384, part ? &m.cim : &m.cre, bar, ph * 512 + src * 64, 0, 0, 0, pj * 8);
    if (u < 2) {
      if (ph) {
        mbar_expect(B_XT + 8 * u, 16384);
        tma4d(dst, &m.x2, B_XT + 8 * u, pj * 128 + u * 64, 0, 0, ti * 16);
      }
    } else {
      if (i == 0) {
        mbar_wait(B_FLG + 8 * (2 * ph + part), 0);
        fence_async_global();
        if (part == 0) TIM(24 + ph);
      }
      bulk_load(dst, g_h + (size_t)(ti * 32 + ph * 16 + part * 8 + src) * 1024, 16384, bar);
    }
    if (++sl == NS) { sl = 0; par ^= 1; }
  }
}

__device__ __forceinline__ void poller(int ti, int pj, int lane, unsigned ep) {
  if (lane < 5) {
    const int f = lane < 4 ? F_H + lane * 16 + ti : F_Z + pj;
    const unsigned need = (ep + 1) * (lane < 4 ? 8 : 16);
    int n = SPIN_LIMIT;
    bool done = false;
    do {
      if (!done && (int)(ld_relaxed(g_flag + f * 32) - need) >= 0) {
        done = true;
        asm volatile("fence.acquire.gpu;" ::: "memory");
        mbar_arrive(B_FLG + 8 * lane);
      }
      if (POLL_NS) __nanosleep(POLL_NS);
    } while (!__all_sync(0x1fu, done) && --n);
    trap_if(n == 0);
  }
}
__device__ __forceinline__ void storer(const Maps& m, int ti, int pj) {
#pragma unroll 1
  for (int job = 0; job < 6; job++) {
    bar_sync(job < 2 ? 4 + job : 9 + (job & 1), 160);
    if (elect_one()) flag_release(job < 2 ? F_U + pj * 2 + job : F_H + (job - 2) * 16 + ti);
    __syncwarp();
    if (job == 2 || job == 4) TIM(7 + job * 2);
  }
  if (elect_one()) {
    mbar_wait_long(B_LOC + 16, 0);
    mbar_wait_long(B_FLG + 32, 0);
    fence_async_global();
    mbar_expect(B_ZT, 16384);
#pragma unroll 1
    for (int o = 0; o < 4; o++) {
      tma5d(S_STG + o * 4096, &m.z, B_ZT, ti * 128, 0, 0, 0, pj * 8 + jj_of(o));
      tma5d(S_STG + o * 4096 + 2048, &m.z, B_ZT, ti * 128 + 64, 0, 0, 0, pj * 8 + jj_of(o));
    }
  }
}

__device__ __forceinline__ void kv_loader(const Maps& m, int ti, int pj, unsigned t_start) {
  unsigned tt = t_start + KV0_AT;
#pragma unroll 1
  for (int st = 0; st < 4; st++) {
    const int d = pj * 128 + (st >> 1) * 64, tb = ti * 16 + (st & 1) * 8;
    const uint32_t bar = B_PIN + 8 * st;
    if (st >= 2) { bar_sync(st == 2 ? 3 : 11, 160); fence_async_smem(); }
    if (elect_one()) {
      mbar_expect(bar, 16384 + 384);
      if (st == 2) tt = t_start + KV1_AT;
      if ((int)(clock() - tt) > 0) tt = clock();
#pragma unroll 1
      for (int i = 0; i < 4; i++) {
        wait_clock(tt);
        tt += st >= 2 ? KV_GAP1 : KV_GAP0;
        tma3d(S_STG + (st & 1) * 16384 + i * 4096, (i & 2) ? &m.v : &m.k, bar, d, tb, (i & 1) * 4);
        if (i == 0) tma3d(S_T + st * 512, &m.kh, bar, d, tb - 1, 5);
      }
    }
    tt = __shfl_sync(~0u, tt, 0);
  }
}

__device__ __forceinline__ void conv_loader(const Maps& m, const Ptrs& p, const ConvCtx& cc, int eb, int lane, unsigned t_start) {
  const unsigned ep = ld_relaxed(g_epoch + eb);
  wait_clock(t_start + SPF_AT);
#pragma unroll 1
  for (int ch = 0; ch < cc.n; ch++) {
    const int d = cc.chan(ch);
    const uint32_t bar = cc.inbar + 8 * (ch & 1), dst = cc.buf + (ch & 1) * 8192;
    const bool first = ch == 0 || ch == (cc.j < 0 ? 3 : 1);
    if (ch >= 2) bar_sync(cc.nb + 2 + (ch & 1), 160);
    if (elect_one()) {
      mbar_expect(cc.inbar + 16, 4096);
      bulk_load(dst + 4096, p.f + (size_t)d * SEQ, 4096, cc.inbar + 16);
      if (!first) { mbar_expect(bar, 4096); tma3d(dst, &m.u, bar, 0, d & 31, d & ~31); }
      if (ch + 1 < cc.n) l2_prefetch(p.f + (size_t)cc.chan(ch + 1) * SEQ, 4096);
    }
    __syncwarp();
    const uint32_t a = dst + 4096 + 128 + (lane >> 3) * 256 + (lane & 7) * 16;
    mbar_wait(cc.inbar + 16, ch & 1);
#pragma unroll 1
    for (uint32_t i = a; i < a + 4096; i += 2048) {
      const uint4 x = lds128(i), y = lds128(i + 1024);
      __syncwarp();
      sts128(i ^ 16, x.x, x.y, x.z, x.w);
      sts128((i ^ 16) + 1024, y.x, y.y, y.z, y.w);
    }
    fence_async_smem();
    __syncwarp();
    if (elect_one()) {
      mbar_arrive(bar);
      if (first) {
        int n = SPIN_LIMIT;
        while ((int)(ld_relaxed(g_flag + (F_U + (d >> 6)) * 32) - (ep + 1) * 16) < 0 && --n) __nanosleep(POLL_NS);
        trap_if(n == 0);
        asm volatile("fence.acquire.gpu;" ::: "memory");
        fence_async_global();
        mbar_expect(bar, 4096);
        tma3d(dst, &m.u, bar, 0, d & 31, d & ~31);
      }
    }
    __syncwarp();
    if (cc.j < 0 && ch == 6) {
      bar_sync(0, 160);
      if (elect_one()) flag_release(F_Z + cc.pj);
      __syncwarp();
    }
  }
  if (cc.j >= 0 && lane == 0) g_epoch[eb] = ep + 1;
}

struct Ring { uint32_t off, par, rel; };
__device__ __forceinline__ void desc_touch(const uint64_t (&c)[12][NS]) {
  uint32_t x = 0;
#pragma unroll
  for (int i = 0; i < 12 * NS; i += 4) x |= (uint32_t)(&c[0][0])[i];
  trap_if((x | (uint32_t)c[11][NS - 1]) == 0);
}
template <int TA, bool TAB, bool LOC = false>
__device__ __forceinline__ void gemm_steps(float (&a0)[64], float (&a1)[64], Ring& r, int n, const uint64_t (&c)[12][NS], int slot) {
#pragma unroll 1
  do {
    const uint32_t off = r.off, rel = r.rel;
    full_wait(B_FULL + off, r.par, slot);
    r.rel = off;
    r.off += 8;
    if (r.off == 8 * NS) { r.off = 0; r.par ^= 1; }
    WG_FENCE();
#define DESC(i) (*(const uint64_t*)((const char*)c[i] + off))
#pragma unroll
    for (int k = 0; k < 4; k++) {
      const uint64_t db = TAB ? DESC(3 * k) : mkdesc(off * 256 + dlo(sb + 16384 + 32 * k, 16), 1024, 1);
      if (LOC) {
        wgmma_ss128<TA, 0, 1>(a0, mkdesc(dlo(S_STG + 32768 + 1024 * k, 4096) - n * 1024, 512, 2), db);
        wgmma_ss128<TA, 0, 1>(a1, mkdesc(dlo(S_STG + 32768 + 8192 + 1024 * k, 4096) - n * 1024, 512, 2), db);
      } else {
        wgmma_ss128<TA, 0, 1>(a0, TAB ? DESC(3 * k + 1) : mkdesc(off * 256 + dlo(sb + 32 * k, 16), 1024, 1), db);
        wgmma_ss128<TA, 0, 1>(a1, TAB ? DESC(3 * k + 2) : mkdesc(off * 256 + dlo(sb + 8192 + 32 * k, 16), 1024, 1), db);
      }
      if (k == RELK) {
        WG_COMMIT();
        WG_WAIT(1);
        if (elect_one()) mbar_arrive(B_EMPTY + rel);
      }
    }
#undef DESC
    if (RELK < 3) WG_COMMIT();
  } while (--n);
}

__global__ void __launch_bounds__(512, 1) fused_kernel(const __grid_constant__ Maps m, const __grid_constant__ Ptrs p) {
  extern __shared__ __align__(1024) uint8_t smem_raw[];
  int b = blockIdx.x;
  {
    int sm, nsm;
    asm volatile("mov.u32 %0, %%smid;" : "=r"(sm));
    asm volatile("mov.u32 %0, %%nsmid;" : "=r"(nsm));
    const int tp = sm >> 1, q = ((tp - 32) * 37) >> 8;
    const int g = tp < 32 ? tp & 7 : (tp < 60 ? tp - 31 - 7 * q : (tp < 62 ? 8 : 0));
    const int j = tp < 32 ? tp >> 3 : (tp < 60 ? 4 + q : (tp < 62 ? tp - 60 : tp - 58));
    if (nsm == 132) b = g * 16 + j * 2 + (sm & 1);
    b = __shfl_sync(~0u, b, 0);
  }
  const int spare = b - 128;
  const int ti = ((b >> 5) << 2) | (b & 3), pj = (((b >> 4) & 1) << 2) | ((b >> 2) & 3);
  const int wid = __shfl_sync(~0u, threadIdx.x >> 5, 0), wg = wid >> 2, tid = threadIdx.x & 127, lane = threadIdx.x & 31;
  if (wg == 0) TIM(0);
  const unsigned t_start = clock();
  if (wid == 12) {
    if (elect_one()) {
      asm volatile("prefetch.tensormap [%0];" ::"l"(&m.x) : "memory");
      asm volatile("prefetch.tensormap [%0];" ::"l"(&m.bre) : "memory");
      asm volatile("prefetch.tensormap [%0];" ::"l"(&m.bim) : "memory");
#pragma unroll
      for (int i = 0; i < NS; i++) mbar_init(B_FULL + 8 * i, (i < 2 && spare >= 0) ? 2 : 1);
      fence_async_smem();
#pragma unroll
      for (int s = 0; s < EARLY; s++) if (spare < 0) issue_g1(m, s, s, ti, pj);
    }
  } else if (wid == 13) {
    if (elect_one()) {
      trap_if((uint32_t)__cvta_generic_to_shared(smem_raw) != sb);
#pragma unroll
      for (uint32_t bar = B_EMPTY; bar < S_EP; bar += 8) mbar_init(bar, (bar < B_CINF || (bar >= B_SFREE && bar < B_ZT) || bar == B_XT + 16 || bar == B_XT + 24) ? 4 :
                           (bar < B_CINF + 16 || ((bar == B_PIN || bar == B_PIN + 8) && spare >= 0)) ? 2 : 1);
      fence_async_smem();
    }
  }
  __syncwarp();
  if (wg == 3) {
    asm volatile("setmaxnreg.dec.sync.aligned.u32 %0;" ::"n"(RV == 2 ? 32 : 24));
    bar_sync(1, 128);
    if (spare < 0) {
      if (wid == 13) { bar_arrive(2, 160); bar_arrive(12, 160); }
      bar_arrive(0, 256);
    } else {
      bar_arrive(0, 512);
    }
    if (wid == 13) {
      if (spare < 0) {
        const unsigned ep = ld_relaxed(g_epoch + b);
        kv_loader(m, ti, pj, t_start);
        poller(ti, pj, lane, ep);
      }
    } else if (wid == 15 || spare >= 0) {
      const ConvCtx cc = conv_ctx(spare, wid == 12 ? 0 : wid - 13, ti, pj);
      conv_loader(m, p, cc, spare < 0 ? b : 128 + cc.j, lane, t_start);
    } else if (wid == 12) {
      if (elect_one()) producer(m, ti, pj);
    } else {
      storer(m, ti, pj);
    }
  } else if (wg == 2 || spare >= 0) {
    asm volatile("setmaxnreg.inc.sync.aligned.u32 160;");
    conv_main(p, conv_ctx(spare, wg, ti, pj), spare < 0 ? b : 128 + spare * 3 + wg, tid);
  } else {
    asm volatile("setmaxnreg.inc.sync.aligned.u32 %0;" ::"n"(RV == 3 ? 168 : 160));
    if (wg == 1) {
      const int ch = (tid >> 6) * 512 + pj * 64 + (tid & 63);
      const unsigned ep = ld_relaxed(g_epoch + b);
      const float lr = __bfloat162float(p.lre[ch]), li = __bfloat162float(p.lim[ch]);
      const float dt = bf_round(expf(__bfloat162float(p.ldt[ch])));
      float sn, cs;
      sincosf(dt * li, &sn, &cs);
      const float ex = expf(dt * lr);
      const float ar = ex * cs, ai = ex * sn;
      const float inv = 2.f / (lr * lr + li * li);
      const float cr = ((ar - 1.f) * lr + ai * li) * inv, ci = (ai * lr - (ar - 1.f) * li) * inv;
      sts128(S_PAR + tid * 16, __float_as_uint(ar), __float_as_uint(ai), pack2(cr, cr), pack2(-ci, -ci));
      const cx l32 = csq(csq(csq(csq(csq({ar, ai}))))), l128 = csq(csq(l32));
      sts128(S_PAR + 2048 + tid * 16, __float_as_uint(l32.r), __float_as_uint(l32.i), __float_as_uint(l128.r), __float_as_uint(l128.i));
      if (tid == 0) asm volatile("st.shared.u32 [%0], %1;" ::"r"(S_EP), "r"(ep) : "memory");
      bar_arrive(6, 256);
      bar_sync(2, 160);
      desc_touch(p.dc1);
      prep<0>(p, ti, pj, wid & 3, lane);
    }
    float a0[64], a1[64];
    Ring ring = {8u * wg * (16 % NS), wg * ((16u / NS) & 1), B_DUMMY - B_EMPTY};
    zero(a0); zero(a1);
    reg_fence(a0); reg_fence(a1);
    sched_fence<61>();
    bar_sync(wg * 7, 256);
    TIM(2 + wg * 2);
    if (wg == 0) gemm_steps<0, false>(a0, a1, ring, 15, p.dc1, 0);
    else gemm_steps<0, true>(a0, a1, ring, 15, p.dc1, 1);
    bar_arrive(7 + wg, 256);
    gemm_steps<0, false>(a0, a1, ring, 1, p.dc1, wg);
    if (wg == 0) bar_sync(6, 256);
    scan_epilogue(a0, a1, B_EMPTY + ring.rel, wg, ti, pj, tid);
    if (wg == 1) {
      eterm(p, ti, pj, tid);
    } else {
      ring = {8 * (32 % NS), (32 / NS) & 1, B_DUMMY - B_EMPTY};
      desc_touch(p.dc2);
      zero(a0); zero(a1);
      reg_fence(a0); reg_fence(a1);
      sched_fence<62>();
      bar_sync(8, 256);
      TIM(6);
#pragma unroll 1
      for (int o = 0; o < 4; o++) {
        if (!(o & 1)) {
          if (o) TIM(18);
          full_wait(B_LOC + 4 * o, 0, 2 + 2 * o);
          gemm_steps<1, true, true>(a0, a1, ring, 2, p.dc2, 3 + 2 * o);
        }
        gemm_steps<1, true>(a0, a1, ring, (o & 1) ? (o == 1 ? 13 : 13 - RES) : 1, p.dc2, 4 + 2 * o - (o & 1));
        if (!(o & 1) && elect_one()) {
          mbar_arrive(o ? B_LOC + 16 : B_SFREE + 16);
        }
      }
#pragma unroll
      for (int i = 0; i < RES; i++) {
        const int sl = (64 - RES + i) % NS;
        full_wait(B_FULL + 8 * sl, ((64 - RES + i) / NS) & 1, 10);
        WG_FENCE();
#pragma unroll
        for (int k = 0; k < 4; k++) wgmma_ss128<1, 0, 1>(a0, p.dc2[3 * k + 1][sl], p.dc2[3 * k][sl]);
        WG_COMMIT();
        if (i == 0 && RES == NS) { WG_WAIT(1); if (elect_one()) mbar_arrive(B_EMPTY + ring.rel); }
      }
      const int w = tid >> 5, trow = 16 * 0 + 64 * (w & 1) + 8 * (w >> 1) + (lane >> 2);
      float* op = p.out + (size_t)(ti * 128 + trow) * DM + pj * 128 + 4 * (lane & 3);
      float g[4];
      uint4 e;
#pragma unroll
      for (int i = 0; i < RES; i++) {
        const int sl = (64 - RES + i) % NS;
        if (i == 0) WG_FENCE();
#pragma unroll
        for (int k = 0; k < 4; k++) wgmma_ss128<1, 0, 1>(a1, p.dc2[3 * k + 2][sl], p.dc2[3 * k][sl]);
        WG_COMMIT();
        if (i == 0) {
          bar_sync(5, 256);
#pragma unroll
          for (int q = 0; q < 4; q++) g[q] = __uint_as_float(lds32(S_G + (trow + 16 * (q >> 1) + 32 * (q & 1)) * 4));
          e = lds128(e_addr(0, 0) + tid * 16);
          WG_WAIT(1);
          reg_fence(a0);
        }
        if (i < 4) {
          const uint4 e0 = e;
          e = lds128(e_addr((i + 1) & 3, i == 3) + tid * 16);
          store_piece(a0, op, jj_of(i), e0, g[0], g[1]);
        }
        if (i == 0) sched_fence_async<70>(); if (i == 1) sched_fence_async<71>(); if (i == 2) sched_fence_async<72>(); if (i == 3) sched_fence_async<73>();
      }
      TIM(26);
      WG_WAIT(0);
      reg_fence(a1);
      TIM(7);
#pragma unroll
      for (int o = 0; o < 8; o++) {
        if (o == 4 || o == 6) bar_sync(4 + (o >> 1), 256);
        if (o >= 4) store_piece(a0, op, jj_of(o), lds128(e_addr(o, 0) + tid * 16), g[0], g[1]);
        store_piece(a1, op + 16 * DM, jj_of(o), o ? lds128(e_addr(o, 1) + tid * 16) : e, g[2], g[3]);
      }
      if (tid == 0) g_epoch[b] = lds32(S_EP) + 1;
      TIM(19);
    }
  }
}

typedef CUresult (*EncFn)(CUtensorMap*, CUtensorMapDataType, cuuint32_t, void*, const cuuint64_t*, const cuuint64_t*,
                          const cuuint32_t*, const cuuint32_t*, CUtensorMapInterleave, CUtensorMapSwizzle,
                          CUtensorMapL2promotion, CUtensorMapFloatOOBfill);

void encode(EncFn enc, CUtensorMap* m, const void* ptr, int rank, const cuuint64_t* dims, const cuuint64_t* strides,
            const cuuint32_t* box, CUtensorMapSwizzle sw) {
  cuuint32_t es[5] = {1, 1, 1, 1, 1};
  enc(m, CU_TENSOR_MAP_DATA_TYPE_BFLOAT16, rank, const_cast<void*>(ptr), dims, strides, box, es, CU_TENSOR_MAP_INTERLEAVE_NONE,
      sw, PROMO, CU_TENSOR_MAP_FLOAT_OOB_FILL_NONE);
}

}

extern "C" void kernel_launch(void* const* d_in, const int* in_sizes, int n_in, void* d_out, int out_size) {
  typedef const __nv_bfloat16* bp;
  Ptrs p;
  p.x = (bp)d_in[0]; p.lre = (bp)d_in[1]; p.lim = (bp)d_in[2]; p.bre = (bp)d_in[3]; p.bim = (bp)d_in[4];
  p.cre = (bp)d_in[5]; p.cim = (bp)d_in[6]; p.ldt = (bp)d_in[7]; p.dskip = (bp)d_in[8];
  p.k = (bp)d_in[10]; p.v = (bp)d_in[11]; p.shift = (bp)d_in[12]; p.f = (bp)d_in[13]; p.ssmd = (bp)d_in[14];
  p.gw = (bp)d_in[15]; p.out = (float*)d_out;

  for (int sl = 0; sl < NS; sl++)
    for (int k = 0; k < 4; k++) {
      const uint64_t h128 = (uint64_t)(64u | (1u << 30)) << 32, h64 = (uint64_t)(32u | (2u << 30)) << 32;
      const uint32_t st = sb + sl * STAGE;
      p.dc1[3 * k][sl] = p.dc2[3 * k][sl] = h128 | dlo(st + 16384 + 32 * k, 16);
      p.dc1[3 * k + 1][sl] = h128 | dlo(st + 32 * k, 16);
      p.dc1[3 * k + 2][sl] = h128 | dlo(st + 8192 + 32 * k, 16);
      p.dc2[3 * k + 1][sl] = h64 | dlo(st + 1024 * k, 4096);
      p.dc2[3 * k + 2][sl] = h64 | dlo(st + 8192 + 1024 * k, 4096);
    }
  EncFn enc = nullptr;
  cudaDriverEntryPointQueryResult qr;
  cudaGetDriverEntryPoint("cuTensorMapEncodeTiled", (void**)&enc, cudaEnableDefault, &qr);
  void *zptr = nullptr, *uptr = nullptr;
  cudaGetSymbolAddress(&zptr, g_z);
  cudaGetSymbolAddress(&uptr, g_u);

  Maps m;
  {
    cuuint64_t d[4] = {1024, 2, 64, 16}, s[3] = {2048, 65536, 4096};
    cuuint32_t bx[4] = {64, 2, 4, 16};
    encode(enc, &m.x, p.x, 4, d, s, bx, CU_TENSOR_MAP_SWIZZLE_128B);
  }
  {
    cuuint64_t d[2] = {1024, 1024}, s[1] = {2048};
    cuuint32_t bx[2] = {64, 64};
    encode(enc, &m.bre, p.bre, 2, d, s, bx, CU_TENSOR_MAP_SWIZZLE_128B);
    encode(enc, &m.bim, p.bim, 2, d, s, bx, CU_TENSOR_MAP_SWIZZLE_128B);
  }
  {
    cuuint64_t d[5] = {1024, 2, 4, 2, 64}, s[4] = {2048, 8192, 4096, 32768};
    cuuint32_t bx[5] = {64, 2, 4, 2, 8};
    encode(enc, &m.cre, p.cre, 5, d, s, bx, CU_TENSOR_MAP_SWIZZLE_128B);
    encode(enc, &m.cim, p.cim, 5, d, s, bx, CU_TENSOR_MAP_SWIZZLE_128B);
  }
  {
    cuuint64_t d[3] = {64, 32, 1024}, s[2] = {128, 4096};
    cuuint32_t bx[3] = {64, 1, 32};
    encode(enc, &m.u, uptr, 3, d, s, bx, CU_TENSOR_MAP_SWIZZLE_NONE);
  }
  {
    cuuint64_t d[3] = {1024, 256, 8}, s[2] = {16384, 2048};
    cuuint32_t bx[3] = {64, 8, 4}, bh[3] = {64, 1, 3};
    encode(enc, &m.k, p.k, 3, d, s, bx, CU_TENSOR_MAP_SWIZZLE_128B);
    encode(enc, &m.kh, p.k, 3, d, s, bh, CU_TENSOR_MAP_SWIZZLE_NONE);
    encode(enc, &m.v, p.v, 3, d, s, bx, CU_TENSOR_MAP_SWIZZLE_128B);
  }
  {
    cuuint64_t d[5] = {2048, 2, 4, 2, 64}, s[4] = {4096, 16384, 8192, 65536};
    cuuint32_t bx[5] = {64, 2, 4, 2, 1};
    encode(enc, &m.z, zptr, 5, d, s, bx, CU_TENSOR_MAP_SWIZZLE_128B);
  }
  {
    cuuint64_t d[4] = {1024, 2, 4, 256}, s[3] = {8192, 2048, 16384};
    cuuint32_t bx[4] = {64, 2, 4, 16};
    encode(enc, &m.x2, p.x, 4, d, s, bx, CU_TENSOR_MAP_SWIZZLE_128B);
  }
  cudaFuncSetAttribute(fused_kernel, cudaFuncAttributeMaxDynamicSharedMemorySize, SMEM_BYTES);
  fused_kernel<<<132, 512, SMEM_BYTES, cudaStreamPerThread>>>(m, p);
}
```

```cpp
#include <cuda_runtime.h>
#include <cuda_bf16.h>
#include <cuda.h>
#include <stdint.h>

namespace {

constexpr int SEQ = 2048, DM = 1024;
#define NSV 5
constexpr int NS = NSV;
constexpr int STAGE = 32768;
#define KV0_AT 300
#define KV_GAP0 600
#define KV1_AT 6500
#define KV_GAP1 550
#define EARLY 2
#define SFM 2
#define RV 1
#define POLL_NS 60
#define IM_NS 40
#define SPF_AT 9000
#define RELK 0
#define RES 5
#define AGG_NS 200
#define ZL_NS 60
#define P2F 3
#define KEEP 16
#define RE_EARLY 0
#define MAP 0
#define LD_GAP 400
#define LDQ ""
#define PROMO CU_TENSOR_MAP_L2_PROMOTION_L2_128B
constexpr uint32_t sb = 1024;
constexpr uint32_t S_STG = sb + NS * STAGE;
constexpr uint32_t S_CIN = S_STG + 32768;
constexpr uint32_t S_T = S_CIN + 16384;
constexpr uint32_t S_M1 = S_T + 8192;
constexpr uint32_t S_M2 = S_M1 + 4096;
constexpr uint32_t S_PAR = S_M2 + 2048;
constexpr uint32_t S_G = S_PAR + 4096;
constexpr uint32_t S_BAR = S_G + 512;
constexpr int SMEM_BYTES = S_BAR + 512 - sb;
constexpr uint32_t B_FULL = S_BAR, B_EMPTY = B_FULL + 8 * NS, B_CINF = B_EMPTY + 8 * NS,
                   B_FLG = B_CINF + 24, B_SFREE = B_FLG + 40, B_LOC = B_SFREE + 24, B_ZT = B_LOC + 24,
                   B_XT = B_ZT + 8, B_PIN = B_XT + 32, B_DUMMY = B_PIN + 32, S_EP = B_DUMMY + 8;
constexpr int SPIN_LIMIT = 1 << 21;
constexpr int F_H = 0, F_U = 64, F_Z = 80;

struct alignas(64) Maps { CUtensorMap x, bre, bim, cre, cim, u, z, x2, k, kh, v; };
struct Ptrs {
  const __nv_bfloat16 *x, *lre, *lim, *ldt, *dskip, *k, *v, *shift, *f, *ssmd, *gw, *bre, *bim, *cre, *cim;
  float* out;
  uint64_t dc1[12][NS], dc2[12][NS];
};

__device__ uint4 g_h[16 * 32 * 1024];
__device__ uint4 g_u[1024 * 256];
__device__ uint4 g_z[1024 * 256];
__device__ uint4 g_agg[2 * 16 * 256];
__device__ unsigned g_gate[8 * SEQ];
__device__ unsigned g_flag[88 * 32];
__device__ unsigned g_epoch[140];
#define TIM(i)
#define TIMC(i)

#define WG_FENCE() asm volatile("wgmma.fence.sync.aligned;" ::: "memory")
#define WG_COMMIT() asm volatile("wgmma.commit_group.sync.aligned;" ::: "memory")
#define WG_WAIT(n) asm volatile("wgmma.wait_group.sync.aligned %0;" ::"n"(n) : "memory")
#define R8(d, o) "+f"(d[o + 0]), "+f"(d[o + 1]), "+f"(d[o + 2]), "+f"(d[o + 3]), "+f"(d[o + 4]), "+f"(d[o + 5]), "+f"(d[o + 6]), "+f"(d[o + 7])
#define W8(d, o) "=f"(d[o + 0]), "=f"(d[o + 1]), "=f"(d[o + 2]), "=f"(d[o + 3]), "=f"(d[o + 4]), "=f"(d[o + 5]), "=f"(d[o + 6]), "=f"(d[o + 7])
#define L16 "%0,%1,%2,%3,%4,%5,%6,%7,%8,%9,%10,%11,%12,%13,%14,%15"
#define L64 L16 ",%16,%17,%18,%19,%20,%21,%22,%23,%24,%25,%26,%27,%28,%29,%30,%31," \
  "%32,%33,%34,%35,%36,%37,%38,%39,%40,%41,%42,%43,%44,%45,%46,%47,%48,%49,%50,%51,%52,%53,%54,%55,%56,%57,%58,%59,%60,%61,%62,%63"

template <int TA, int TB, int ACC>
__device__ __forceinline__ void wgmma_ss128(float (&d)[64], uint64_t da, uint64_t db) {
  if (ACC)
    asm volatile("wgmma.mma_async.sync.aligned.m64n128k16.f32.bf16.bf16 {" L64 "}, %64, %65, 1, 1, 1, %66, %67;"
                 : R8(d, 0), R8(d, 8), R8(d, 16), R8(d, 24), R8(d, 32), R8(d, 40), R8(d, 48), R8(d, 56)
                 : "l"(da), "l"(db), "n"(TA), "n"(TB));
  else
    asm volatile("wgmma.mma_async.sync.aligned.m64n128k16.f32.bf16.bf16 {" L64 "}, %64, %65, 0, 1, 1, %66, %67;"
                 : W8(d, 0), W8(d, 8), W8(d, 16), W8(d, 24), W8(d, 32), W8(d, 40), W8(d, 48), W8(d, 56)
                 : "l"(da), "l"(db), "n"(TA), "n"(TB));
}
template <int TA>
__device__ __forceinline__ void wgmma_ss128p(float (&d)[64], uint64_t da, uint64_t db, int acc) {
  asm volatile("{.reg .pred p; setp.ne.b32 p, %67, 0;\n"
               "wgmma.mma_async.sync.aligned.m64n128k16.f32.bf16.bf16 {" L64 "}, %64, %65, p, 1, 1, %66, 0;}"
               : R8(d, 0), R8(d, 8), R8(d, 16), R8(d, 24), R8(d, 32), R8(d, 40), R8(d, 48), R8(d, 56)
               : "l"(da), "l"(db), "n"(TA), "r"(acc));
}
template <int ACC, int TB = 0>
__device__ __forceinline__ void wgmma_rs32(float (&d)[16], uint32_t a0, uint32_t a1, uint32_t a2, uint32_t a3, uint64_t db) {
  if (ACC)
    asm volatile("wgmma.mma_async.sync.aligned.m64n32k16.f32.bf16.bf16 {" L16 "}, {%16,%17,%18,%19}, %20, 1, 1, 1, %21;"
                 : R8(d, 0), R8(d, 8) : "r"(a0), "r"(a1), "r"(a2), "r"(a3), "l"(db), "n"(TB));
  else
    asm volatile("wgmma.mma_async.sync.aligned.m64n32k16.f32.bf16.bf16 {" L16 "}, {%16,%17,%18,%19}, %20, 0, 1, 1, %21;"
                 : W8(d, 0), W8(d, 8) : "r"(a0), "r"(a1), "r"(a2), "r"(a3), "l"(db), "n"(TB));
}
template <int N>
__device__ __forceinline__ void reg_fence(float (&d)[N]) {
#pragma unroll
  for (int i = 0; i < N; i++) asm volatile("" : "+f"(d[i])::"memory");
}
__host__ __device__ __forceinline__ constexpr uint32_t dlo(uint32_t addr, uint32_t lbo) { return (addr >> 4) + ((lbo >> 4) << 16); }
__device__ __forceinline__ uint64_t mkdesc(uint32_t lo, uint32_t sbo, uint32_t mode) {
  uint64_t d;
  asm("mov.b64 %0, {%1, %2};" : "=l"(d) : "r"(lo), "r"((sbo >> 4) | (mode << 30)));
  return d;
}
template <int N>
__device__ __forceinline__ void zero(float (&d)[N]) {
#pragma unroll
  for (int i = 0; i < N; i++) d[i] = 0.f;
}
__device__ __forceinline__ void trap_if(int c) {
  asm volatile("{.reg .pred p; .reg .b64 z; setp.ne.s32 p, %0, 0; mov.b64 z, 0; @p st.global.u32 [z], %0;}" ::"r"(c) : "memory");
}
template <int K>
__device__ __forceinline__ void sched_fence() {
  asm volatile("{.reg .pred p; setp.eq.u32 p, %0, %1; @p exit;}" ::"r"(gridDim.x), "n"(256 + K) : "memory");
}
template <int K>
__device__ __forceinline__ void sched_fence_async() {
  asm volatile("{.reg .pred p; .reg .u32 r; setp.ne.u32 p, %0, %1; @p bra.uni SFE;\n"
               "SFL: nanosleep.u32 1000; mov.u32 r, %%clock; setp.eq.u32 p, r, 0; @p bra.uni SFL;\nSFE: }" ::"r"(gridDim.x), "n"(256 + K) : "memory");
}
__device__ __forceinline__ bool elect_one() {
  uint32_t pred;
  asm volatile("{.reg .pred p; elect.sync _|p, 0xffffffff; selp.u32 %0, 1, 0, p;}" : "=r"(pred));
  return pred;
}
__device__ __forceinline__ void mbar_init(uint32_t bar, uint32_t cnt) {
  asm volatile("mbarrier.init.shared::cta.b64 [%0], %1;" ::"r"(bar), "r"(cnt) : "memory");
}
__device__ __forceinline__ bool mbar_try(uint32_t bar, uint32_t par) {
  uint32_t ok;
  asm volatile("{.reg .pred p; mbarrier.try_wait.parity.shared::cta.b64 p, [%1], %2; selp.u32 %0, 1, 0, p;}"
               : "=r"(ok) : "r"(bar), "r"(par) : "memory");
  return ok;
}
#undef DBGV
#define DBGV ((bar - S_BAR) * 2 + par)
__device__ __forceinline__ void mbar_wait(uint32_t bar, uint32_t par) {
  if (__builtin_expect(!mbar_try(bar, par), 0)) {
    int n = SPIN_LIMIT;
    while (!mbar_try(bar, par) && --n) {}
    trap_if(n == 0);
  }
}
#define full_wait(bar, par, slot) mbar_wait(bar, par)
__device__ __forceinline__ void mbar_wait_long(uint32_t bar, uint32_t par) {
  int n = SPIN_LIMIT;
  while (!mbar_try(bar, par) && --n) __nanosleep(100);
  trap_if(n == 0);
}
#undef DBGV
#define DBGV 0
__device__ __forceinline__ void mbar_arrive(uint32_t bar) {
  asm volatile("mbarrier.arrive.shared::cta.b64 _, [%0];" ::"r"(bar) : "memory");
}
__device__ __forceinline__ void mbar_expect(uint32_t bar, uint32_t bytes) {
  asm volatile("mbarrier.arrive.expect_tx.shared::cta.b64 _, [%0], %1;" ::"r"(bar), "r"(bytes) : "memory");
}
__device__ __forceinline__ void tma2d(uint32_t dst, const CUtensorMap* m, uint32_t bar, int c0, int c1) {
  asm volatile("cp.async.bulk.tensor.2d.shared::cluster.global.mbarrier::complete_tx::bytes [%0], [%1, {%3, %4}], [%2];"
               ::"r"(dst), "l"(m), "r"(bar), "r"(c0), "r"(c1) : "memory");
}
__device__ __forceinline__ void tma3d(uint32_t dst, const CUtensorMap* m, uint32_t bar, int c0, int c1, int c2) {
  asm volatile("cp.async.bulk.tensor.3d.shared::cluster.global.mbarrier::complete_tx::bytes [%0], [%1, {%3, %4, %5}], [%2];"
               ::"r"(dst), "l"(m), "r"(bar), "r"(c0), "r"(c1), "r"(c2) : "memory");
}
__device__ __forceinline__ void tma4d(uint32_t dst, const CUtensorMap* m, uint32_t bar, int c0, int c1, int c2, int c3) {
  asm volatile("cp.async.bulk.tensor.4d.shared::cluster.global.mbarrier::complete_tx::bytes [%0], [%1, {%3, %4, %5, %6}], [%2];"
               ::"r"(dst), "l"(m), "r"(bar), "r"(c0), "r"(c1), "r"(c2), "r"(c3) : "memory");
}
__device__ __forceinline__ void tma5d(uint32_t dst, const CUtensorMap* m, uint32_t bar, int c0, int c1, int c2, int c3, int c4) {
  asm volatile("cp.async.bulk.tensor.5d.shared::cluster.global.mbarrier::complete_tx::bytes [%0], [%1, {%3, %4, %5, %6, %7}], [%2];"
               ::"r"(dst), "l"(m), "r"(bar), "r"(c0), "r"(c1), "r"(c2), "r"(c3), "r"(c4) : "memory");
}
__device__ __forceinline__ void bulk_load(uint32_t dst, const void* src, uint32_t bytes, uint32_t bar) {
  asm volatile("cp.async.bulk.shared::cluster.global.mbarrier::complete_tx::bytes [%0], [%1], %2, [%3];"
               ::"r"(dst), "l"(src), "r"(bytes), "r"(bar) : "memory");
}
__device__ __forceinline__ void l2_prefetch(const void* src, uint32_t bytes) {
  asm volatile("cp.async.bulk.prefetch.L2.global [%0], %1;" ::"l"(src), "r"(bytes) : "memory");
}
__device__ __forceinline__ void bar_sync(int id, int n) { asm volatile("bar.sync %0, %1;" ::"r"(id), "r"(n) : "memory"); }
__device__ __forceinline__ void bar_arrive(int id, int n) { asm volatile("bar.arrive %0, %1;" ::"r"(id), "r"(n) : "memory"); }
__device__ __forceinline__ void fence_async_smem() { asm volatile("fence.proxy.async.shared::cta;" ::: "memory"); }
__device__ __forceinline__ void fence_async_global() { asm volatile("fence.proxy.async.global;" ::: "memory"); }
__device__ __forceinline__ void flag_add(int f) {
  asm volatile("red.relaxed.gpu.global.add.u32 [%0], 1;" ::"l"(g_flag + f * 32) : "memory");
}
__device__ __forceinline__ void flag_release(int f) {
  asm volatile("fence.release.gpu;" ::: "memory");
  flag_add(f);
}
__device__ __forceinline__ unsigned ld_relaxed(const unsigned* p) {
  unsigned v;
  asm volatile("ld.relaxed.gpu.global.u32 %0, [%1];" : "=r"(v) : "l"(p) : "memory");
  return v;
}
__device__ __forceinline__ void wait_clock(unsigned t) {
  int d;
  while ((d = (int)(t - (unsigned)clock())) > 0) __nanosleep(d > 600 ? 200 : 40);
}
__device__ __forceinline__ uint32_t pack2(float lo, float hi) {
  uint32_t r;
  asm("cvt.rn.bf16x2.f32 %0, %1, %2;" : "=r"(r) : "f"(hi), "f"(lo));
  return r;
}
__device__ __forceinline__ float bf_lo(uint32_t v) { return __uint_as_float(v << 16); }
__device__ __forceinline__ float bf_hi(uint32_t v) { return __uint_as_float(v & 0xffff0000u); }
__device__ __forceinline__ float bf_round(float v) { return __bfloat162float(__float2bfloat16_rn(v)); }
__device__ __forceinline__ uint32_t hmul2(uint32_t a, uint32_t b) {
  uint32_t r;
  asm("mul.rn.bf16x2 %0, %1, %2;" : "=r"(r) : "r"(a), "r"(b));
  return r;
}
__device__ __forceinline__ uint32_t hadd2(uint32_t a, uint32_t b) {
  uint32_t r;
  asm("add.rn.bf16x2 %0, %1, %2;" : "=r"(r) : "r"(a), "r"(b));
  return r;
}
__device__ __forceinline__ uint32_t hsub2(uint32_t a, uint32_t b) {
  uint32_t r;
  asm("sub.rn.bf16x2 %0, %1, %2;" : "=r"(r) : "r"(a), "r"(b));
  return r;
}
__device__ __forceinline__ uint32_t hfma2(uint32_t a, uint32_t b, uint32_t c) {
  uint32_t r;
  asm("fma.rn.bf16x2 %0, %1, %2, %3;" : "=r"(r) : "r"(a), "r"(b), "r"(c));
  return r;
}
__device__ __forceinline__ uint32_t hneg2(uint32_t a) {
  uint32_t r;
  asm("neg.bf16x2 %0, %1;" : "=r"(r) : "r"(a));
  return r;
}
__device__ __forceinline__ uint4 ldg128(const void* p) {
  uint4 v;
  asm volatile("ld.global.nc" LDQ ".v4.u32 {%0,%1,%2,%3}, [%4];" : "=r"(v.x), "=r"(v.y), "=r"(v.z), "=r"(v.w) : "l"(p));
  return v;
}
__device__ __forceinline__ uint2 ldg64(const void* p) {
  uint2 v;
  asm volatile("ld.global.nc.v2.u32 {%0,%1}, [%2];" : "=r"(v.x), "=r"(v.y) : "l"(p));
  return v;
}
__device__ __forceinline__ void stg128(void* p, uint32_t a, uint32_t b, uint32_t c, uint32_t d) {
  asm volatile("st.global.v4.u32 [%0], {%1,%2,%3,%4};" ::"l"(p), "r"(a), "r"(b), "r"(c), "r"(d) : "memory");
}
__device__ __forceinline__ void sts128(uint32_t a, uint32_t x, uint32_t y, uint32_t z, uint32_t w) {
  asm volatile("st.shared.v4.u32 [%0], {%1,%2,%3,%4};" ::"r"(a), "r"(x), "r"(y), "r"(z), "r"(w) : "memory");
}
__device__ __forceinline__ uint32_t lds32(uint32_t a) {
  uint32_t v;
  asm volatile("ld.shared.u32 %0, [%1];" : "=r"(v) : "r"(a) : "memory");
  return v;
}
__device__ __forceinline__ uint4 lds128(uint32_t a) {
  uint4 v;
  asm volatile("ld.shared.v4.u32 {%0,%1,%2,%3}, [%4];" : "=r"(v.x), "=r"(v.y), "=r"(v.z), "=r"(v.w) : "r"(a) : "memory");
  return v;
}
__device__ __forceinline__ void stsm4(uint32_t a, uint32_t x, uint32_t y, uint32_t z, uint32_t w) {
  asm volatile("stmatrix.sync.aligned.m8n8.x4.shared.b16 [%0], {%1,%2,%3,%4};" ::"r"(a), "r"(x), "r"(y), "r"(z), "r"(w) : "memory");
}
__device__ __forceinline__ void stsm4t(uint32_t a, uint32_t x, uint32_t y, uint32_t z, uint32_t w) {
  asm volatile("stmatrix.sync.aligned.m8n8.x4.trans.shared.b16 [%0], {%1,%2,%3,%4};" ::"r"(a), "r"(x), "r"(y), "r"(z), "r"(w) : "memory");
}
__device__ __forceinline__ uint4 ldsm4t(uint32_t a) {
  uint4 v;
  asm volatile("ldmatrix.sync.aligned.m8n8.x4.trans.shared.b16 {%0,%1,%2,%3}, [%4];" : "=r"(v.x), "=r"(v.y), "=r"(v.z), "=r"(v.w) : "r"(a) : "memory");
  return v;
}
struct cx { float r, i; };
__device__ __forceinline__ cx cmul(cx a, cx b) { return {a.r * b.r - a.i * b.i, a.r * b.i + a.i * b.r}; }
__device__ __forceinline__ cx cfma(cx a, cx b, cx c) { return {fmaf(a.r, b.r, fmaf(-a.i, b.i, c.r)), fmaf(a.r, b.i, fmaf(a.i, b.r, c.i))}; }
__device__ __forceinline__ cx csq(cx a) { return {a.r * a.r - a.i * a.i, 2.f * a.r * a.i}; }
__device__ __forceinline__ cx unit(int num, int den) {
  int m = num & (den - 1);
  if (m >= den / 2) m -= den;
  float s, c;
  __sincosf((float)m * (-6.283185307179586f / (float)den), &s, &c);
  return {c, s};
}

__device__ __forceinline__ uint2 lds64(uint32_t a) {
  uint2 v;
  asm volatile("ld.shared.v2.u32 {%0,%1}, [%2];" : "=r"(v.x), "=r"(v.y) : "r"(a) : "memory");
  return v;
}
__device__ __forceinline__ void prep_taps(const uint4 (&sh)[2], uint32_t (&s)[2][4]) {
#pragma unroll
  for (int e = 0; e < 2; e++) {
    s[e][0] = __byte_perm(sh[e].x, sh[e].z, 0x5410); s[e][1] = __byte_perm(sh[e].x, sh[e].z, 0x7632);
    s[e][2] = __byte_perm(sh[e].y, sh[e].w, 0x5410); s[e][3] = __byte_perm(sh[e].y, sh[e].w, 0x7632);
  }
}
__device__ __forceinline__ void prep_math(const uint2 (&kk)[11], uint2 (&vv)[8], const uint32_t (&s)[2][4]) {
#pragma unroll
  for (int i = 0; i < 8; i++)
#pragma unroll
    for (int e = 0; e < 2; e++) {
      uint32_t a = hmul2((&kk[i].x)[e], s[e][3]);
      a = hfma2((&kk[i + 1].x)[e], s[e][2], a);
      a = hfma2((&kk[i + 2].x)[e], s[e][1], a);
      a = hfma2((&kk[i + 3].x)[e], s[e][0], a);
      (&vv[i].x)[e] = hmul2(a, (&vv[i].x)[e]);
    }
}
__device__ __forceinline__ void prep_store(const uint2 (&vv)[8], int d, int tb) {
  uint4* dst = g_u + (size_t)((d >> 5) * 32 + (tb >> 3)) * 256 + (d & 31) * 8 + ((tb & 7) ^ ((tb >> 3) & 1));
#pragma unroll
  for (int e = 0; e < 2; e++) {
#define U(i) (&vv[i].x)[e]
    stg128(dst + (2 * e) * 8, __byte_perm(U(0), U(1), 0x5410), __byte_perm(U(2), U(3), 0x5410),
           __byte_perm(U(4), U(5), 0x5410), __byte_perm(U(6), U(7), 0x5410));
    stg128(dst + (2 * e + 1) * 8, __byte_perm(U(0), U(1), 0x7632), __byte_perm(U(2), U(3), 0x7632),
           __byte_perm(U(4), U(5), 0x7632), __byte_perm(U(6), U(7), 0x7632));
#undef U
  }
}
template <int PG>
__device__ __forceinline__ void prep(const Ptrs& p, int ti, int pj, int w, int lane) {
  const int tb = lane & 7, chunk = 2 * w + (lane >> 4), ch = chunk * 8 + ((lane >> 3) & 1) * 4, d = pj * 128 + PG * 64 + ch;
  const uint4 sh[2] = {ldg128(p.shift + d * 4), ldg128(p.shift + d * 4 + 8)};
  uint32_t s[2][4];
  prep_taps(sh, s);
#pragma unroll 1
  for (int th = 0; th < 2; th++) {
    uint2 kk[11], vv[8];
    {
      const uint32_t in = S_STG + th * 16384 + (lane & 8);
      const uint32_t a0 = in + tb * 128 + ((chunk ^ tb) << 4);
      const uint32_t hb = tb ? in + (39 + tb) * 128 + ((chunk ^ (tb - 1)) << 4) : S_T + (PG * 2 + th) * 512 + ch * 2;
      const uint32_t hs = tb ? 1024 : 128;
      mbar_wait_long(B_PIN + 16 * PG + 8 * th, 0);
      if (th) TIM(29 + PG);
#pragma unroll
      for (int i = 0; i < 3; i++) kk[i] = lds64(hb + i * hs);
#pragma unroll
      for (int i = 0; i < 8; i++) { kk[3 + i] = lds64(a0 + i * 1024); vv[i] = lds64(a0 + 8192 + i * 1024); }
      prep_math(kk, vv, s);
      sched_fence<52 + PG>();
    }
    if (!PG) bar_arrive(th ? 11 : 3, 160);
    else if (elect_one()) mbar_arrive(B_SFREE + 8 * th);
    prep_store(vv, d, ti * 16 + th * 8 + tb);
  }
  bar_arrive(4 + PG, 160);
}

__device__ __forceinline__ void gate_finish(int ti, int tid, uint32_t tag) {
  float l;
  int n = SPIN_LIMIT;
  bool bad;
  do {
    __nanosleep(250);
    uint32_t v[8], x = 0;
#pragma unroll
    for (int j = 0; j < 8; j++) v[j] = ld_relaxed(g_gate + j * SEQ + ti * 128 + tid) ^ tag;
    l = 0.f;
#pragma unroll
    for (int j = 0; j < 8; j++) { x |= v[j]; l += __uint_as_float(v[j]); }
    bad = __any_sync(~0u, x & 3);
  } while (bad && --n);
  trap_if(n == 0);
  const float g = bf_round(__fdividef(1.f, 1.f + __expf(-bf_round(l))));
  asm volatile("st.shared.f32 [%0], %1;" ::"r"(S_G + tid * 4), "f"(g) : "memory");
}

__device__ __forceinline__ void conv_tables(int tid) {
  {
    const int s = tid >> 5, n1 = tid & 31;
    uint32_t re[4], im[4];
#pragma unroll
    for (int e = 0; e < 4; e++) {
      cx a = unit(n1 * (4 * (8 * s + 2 * e) + 1), 128), b = unit(n1 * (4 * (8 * s + 2 * e + 1) + 1), 128);
      re[e] = pack2(a.r * 0.125f, b.r * 0.125f); im[e] = pack2(a.i * 0.125f, b.i * 0.125f);
    }
    sts128(S_M1 + (2 * s) * 512 + n1 * 16, re[0], re[1], re[2], re[3]);
    sts128(S_M1 + (2 * s + 1) * 512 + n1 * 16, im[0], im[1], im[2], im[3]);
  }
  {
    const int kg = tid >> 5, n = tid & 31;
    const int pi = kg >> 1, po = n >> 4, f2 = n & 15;
    uint32_t fw[4];
#pragma unroll
    for (int e = 0; e < 4; e++) {
      int n2 = (kg & 1) * 8 + 2 * e;
      cx a = unit(n2 * f2, 16), b = unit((n2 + 1) * f2, 16);
      float sg = pi ? -1.f : 1.f;
      float x0 = (pi == po) ? a.r : sg * a.i, x1 = (pi == po) ? b.r : sg * b.i;
      fw[e] = pack2(x0, x1);
    }
    sts128(S_M2 + kg * 512 + n * 16, fw[0], fw[1], fw[2], fw[3]);
  }
  fence_async_smem();
}
__device__ __forceinline__ constexpr int jj_of(int o) { return o == 7 ? 3 : o + (o >= 3); }
__device__ __forceinline__ int conv_chan(int ti, int pj, int jj) { return pj * 128 + jj * 16 + ti; }

struct ConvCtx {
  uint32_t buf, inbar;
  int nb, n;
  int ti, pj, j;
  __device__ __forceinline__ int chan(int c) const {
    return j < 0 ? conv_chan(ti, pj, jj_of(c)) : conv_chan(((j + 12 * c) >> 3) + (((j + 12 * c) >> 3) >= KEEP), (j + 12 * c) & 7, 3);
  }
};
__device__ __forceinline__ ConvCtx conv_ctx(int spare, int wg, int ti, int pj) {
  const int j = spare < 0 ? -1 : spare * 3 + wg;
  return {wg == 2 ? S_CIN : sb + wg * 32768, wg == 2 ? B_CINF : (wg ? B_PIN : B_FULL), 4 + 4 * wg, j < 0 ? 7 + (ti == KEEP) : (j < 8 && KEEP > 15 ? 11 : 10), ti, pj, j};
}
#define CDESC(a) mkdesc(dlo(a, 512), 128, 0)
struct ConvTw { uint32_t r[2], i[2], n[2]; };

__device__ __forceinline__ void cv_tw1(float (&d)[64], uint32_t (&R)[16], uint32_t (&I)[16], const ConvTw& t, int i) {
#pragma unroll
  for (int j = 8 * (i & 1); j < 8 * (i & 1) + 8; j++) {
    if (i < 2) {
      R[j] = pack2(d[4 * j], d[4 * j + 1]); I[j] = pack2(d[4 * j + 2], d[4 * j + 3]);
    } else {
      const uint32_t xr = R[j], xi = I[j];
      R[j] = hfma2(xr, t.r[j & 1], hmul2(xi, t.n[j & 1]));
      I[j] = hfma2(xr, t.i[j & 1], hmul2(xi, t.r[j & 1]));
    }
  }
}
template <int N>
__device__ __forceinline__ void cv_pack(float (&X)[16], uint32_t (&P)[N][2][2], int q) {
#pragma unroll
  for (int k = 0; k < 2; k++)
#pragma unroll
    for (int j = 0; j < 4; j++) P[2 * q + k][j >> 1][j & 1] = pack2(X[4 * j + 2 * k], X[4 * j + 2 * k + 1]);
}
__device__ __forceinline__ void cv_overlap(uint32_t (&P)[8][2][2]) {
#pragma unroll
  for (int k = 3; k > 0; k--)
#pragma unroll
    for (int hh = 0; hh < 2; hh++) {
      P[k][0][hh] = hsub2(P[k][0][hh], P[k - 1][1][hh]);
      P[k][1][hh] = hadd2(P[k][1][hh], P[k - 1][0][hh]);
    }
}
__device__ __forceinline__ void cv_pw(uint32_t (&P)[8][2][2], uint32_t (&Q)[4][2][2]) {
#pragma unroll
  for (int jh = 0; jh < 8; jh++) {
    const int j = jh >> 1, hh = jh & 1;
    uint32_t qr = hmul2(P[4 + j][0][hh], P[0][0][hh]), qi = hmul2(P[4 + j][0][hh], P[0][1][hh]);
    qr = hfma2(hneg2(P[4 + j][1][hh]), P[0][1][hh], qr);
    qi = hfma2(P[4 + j][1][hh], P[0][0][hh], qi);
#pragma unroll
    for (int k = j - 1; k >= 0; k--) {
      qr = hfma2(P[4 + k][0][hh], P[j - k][0][hh], qr);
      qi = hfma2(P[4 + k][0][hh], P[j - k][1][hh], qi);
      qr = hfma2(hneg2(P[4 + k][1][hh]), P[j - k][1][hh], qr);
      qi = hfma2(P[4 + k][1][hh], P[j - k][0][hh], qi);
    }
    Q[j][0][hh] = qr; Q[j][1][hh] = qi;
  }
}
__device__ __forceinline__ void cv_tw2(uint32_t (&Q)[4][2][2], const ConvTw& t, int k) {
#pragma unroll
  for (int hh = 0; hh < 2; hh++) {
    const uint32_t xr = Q[k][0][hh], xi = Q[k][1][hh];
    Q[k][0][hh] = hfma2(xr, t.r[hh], hmul2(xi, t.i[hh]));
    Q[k][1][hh] = hfma2(xr, t.n[hh], hmul2(xi, t.r[hh]));
  }
}
__device__ __forceinline__ void cv_out0(float (&Y)[16], uint32_t T, int w, int lane) {
  reg_fence(Y);
  const uint32_t za = T + w * 2048 + (lane >> 4) * 256 + (lane & 7) * 32 + (((lane >> 3) ^ (lane >> 2)) & 1) * 16;
#pragma unroll
  for (int jj = 0; jj < 2; jj++)
    stsm4t(za + jj * 512, pack2(Y[8 * jj], Y[8 * jj + 1]), pack2(Y[8 * jj + 2], Y[8 * jj + 3]),
           pack2(Y[8 * jj + 4], Y[8 * jj + 5]), pack2(Y[8 * jj + 6], Y[8 * jj + 7]));
}

__device__ __forceinline__ void cv_out1(const uint4& z0, const uint4& z1, const ConvCtx& cc, uint32_t keep, uint32_t tag, int ch, int w, int lane) {
  uint4* zp = g_z + (size_t)cc.chan(ch) * 256 + w * 64 + lane;
#define TG(v) ((v & keep) | (tag & ~keep))
  asm volatile("st.relaxed.gpu.global.v4.u32 [%0], {%1,%2,%3,%4};" ::"l"(zp), "r"(TG(z0.x)), "r"(TG(z0.y)), "r"(TG(z0.z)), "r"(TG(z0.w)) : "memory");
  asm volatile("st.relaxed.gpu.global.v4.u32 [%0], {%1,%2,%3,%4};" ::"l"(zp + 32), "r"(TG(z1.x)), "r"(TG(z1.y)), "r"(TG(z1.z)), "r"(TG(z1.w)) : "memory");
#undef TG
}
template <bool FW, bool BW, int K>
__device__ __forceinline__ void conv_step(uint32_t (&Q)[4][2][2], const ConvTw& t, const ConvCtx& cc, float dl, uint32_t tag, int ch, int w, int lane) {
#define SF(n) if ((SFM >> (n)) & 1) sched_fence_async<K + (n)>()
  float d[64], X[4][16], Z[2][16], Y[16];
  uint32_t R[16], I[16];
  uint4 a[4];
  const int nx = ch + 1;
  const uint32_t T = cc.buf + 16384;
  float dv;
  TIMC(1);
  if (FW) {
    dv = __shfl_sync(~0u, dl, nx);
    mbar_wait(cc.inbar + 8 * (nx & 1), (nx >> 1) & 1);
  }
  TIMC(2);
  WG_FENCE();
  if (BW) {
#pragma unroll
    for (int q = 0; q < 2; q++) {
      wgmma_rs32<0, 1>(Z[q], Q[2 * q][0][0], Q[2 * q + 1][0][0], Q[2 * q][0][1], Q[2 * q + 1][0][1], mkdesc(dlo(S_M2, 128), 512, 0));
      wgmma_rs32<1, 1>(Z[q], Q[2 * q][1][0], Q[2 * q + 1][1][0], Q[2 * q][1][1], Q[2 * q + 1][1][1], mkdesc(dlo(S_M2 + 256, 128), 512, 0));
    }
    WG_COMMIT();
  }
  if (FW) {
    const uint32_t lo = dlo(0, 1024) + (cc.buf >> 4) + (nx & 1) * 512;
    wgmma_ss128<1, 1, 0>(d, mkdesc(dlo(S_M1, 128), 512, 0), mkdesc(lo, 256, 3));
    wgmma_ss128<1, 1, 1>(d, mkdesc(dlo(S_M1 + 256, 128), 512, 0), mkdesc(lo + 32, 256, 3));
    WG_COMMIT();
  }
  TIMC(3);
  if (BW) {
    TIMC(4);
    WG_WAIT(FW ? 1 : 0);
    TIMC(5);
    reg_fence(Z[0]); reg_fence(Z[1]);
    uint32_t V[4][2][2];
    cv_pack(Z[0], V, 0); cv_pack(Z[1], V, 1);
    SF(0);
#pragma unroll
    for (int k = 0; k < 4; k++) cv_tw2(V, t, k);
    bar_sync(cc.nb, 128);
#pragma unroll
    for (int k = 0; k < 4; k++) stsm4(T + w * 512 + lane * 16 + k * 2048, V[k][0][0], V[k][0][1], V[k][1][0], V[k][1][1]);
    SF(1);
    TIMC(6);
  }
  if (FW) {
    WG_WAIT(0);
    reg_fence(d);
    if (nx + 2 < cc.n) bar_arrive(cc.nb + 2 + (nx & 1), 160);
    cv_tw1(d, R, I, t, 0); cv_tw1(d, R, I, t, 1);
    SF(2);
    TIMC(7);
  }
  if (BW) {
    bar_sync(cc.nb, 128);
#pragma unroll
    for (int s = 0; s < 4; s++) a[s] = ldsm4t(T + (4 * w + s) * 512 + lane * 16);
  }
  if (FW) { cv_tw1(d, R, I, t, 2); cv_tw1(d, R, I, t, 3); }
  sched_fence<K + 3>();
  TIMC(8);
  WG_FENCE();
  if (BW) {
    wgmma_rs32<0>(Y, a[0].x, a[0].y, a[0].z, a[0].w, CDESC(S_M1));
#pragma unroll
    for (int i = 1; i < 4; i++) wgmma_rs32<1>(Y, a[i].x, a[i].y, a[i].z, a[i].w, CDESC(S_M1 + 1024 * i));
  }
  if (FW) {
#pragma unroll
    for (int q = 0; q < 4; q++) {
      if (q == 2) WG_COMMIT();
      wgmma_rs32<0>(X[q], R[4 * q], R[4 * q + 2], R[4 * q + 1], R[4 * q + 3], CDESC(S_M2));
      wgmma_rs32<1>(X[q], I[4 * q], I[4 * q + 2], I[4 * q + 1], I[4 * q + 3], CDESC(S_M2 + 1024));
    }
  }
  WG_COMMIT();
  TIMC(9);
  WG_WAIT(FW ? 1 : 0);
  TIMC(10);
  uint4 z0, z1;
  const uint32_t zr = T + w * 2048 + (lane ^ ((lane >> 3) & 1)) * 16;
  if (BW) {
    cv_out0(Y, T, w, lane);
    __syncwarp();
  }
  if (FW) {
    uint32_t P[8][2][2];
    reg_fence(X[0]); reg_fence(X[1]);
    cv_pack(X[0], P, 0); cv_pack(X[1], P, 1);
    cv_overlap(P);
    if (BW) { z0 = lds128(zr); z1 = lds128(zr + 512); }
    sched_fence_async<K + 7>();
    WG_WAIT(0);
    reg_fence(X[2]); reg_fence(X[3]);
    X[2][0] += dv; X[2][1] += dv; X[2][4] += dv; X[2][5] += dv;
    cv_pack(X[2], P, 2); cv_pack(X[3], P, 3);
    SF(4);
    TIMC(11);
    cv_pw(P, Q);
    SF(8);
  } else {
    z0 = lds128(zr); z1 = lds128(zr + 512);
  }
  if (BW) cv_out1(z0, z1, cc, FW && cc.j < 0 && ch < 4 ? ~0u : ~1u, tag, ch, w, lane);
  sched_fence<K + 5>();
  TIMC(13);
#undef SF
}

__device__ __forceinline__ void conv_main(const Ptrs& p, const ConvCtx& cc, int eb, int tid) {
  const int ti = cc.ti, pj = cc.pj;
  const int w = tid >> 5, lane = tid & 31;
  const unsigned ep = ld_relaxed(g_epoch + eb);
  const __nv_bfloat16 dsk = p.ssmd[cc.chan(min(lane, cc.n - 1))];
  if (cc.nb == 12) conv_tables(tid);
  if (cc.j < 0) bar_sync(12, 160); else bar_sync(0, 512);
  ConvTw t;
#pragma unroll
  for (int hh = 0; hh < 2; hh++) {
    const int n2 = 8 * hh + 2 * (lane & 3), m = 4 * (8 * w + (lane >> 2)) + 1;
    cx a = unit(n2 * m, 2048), b = unit((n2 + 1) * m, 2048);
    t.r[hh] = pack2(a.r, b.r); t.i[hh] = pack2(a.i, b.i); t.n[hh] = pack2(-a.i, -b.i);
  }
  const uint32_t tag = (ep + 1) & 3;
  const float dl = 0.125f * __bfloat162float(dsk);
  if (cc.j < 0) prep<1>(p, ti, pj, w, lane);
  {
    uint32_t P[4][2][2];
    mbar_wait_long(cc.inbar, 0);
    TIM(20);
    conv_step<true, false, 10>(P, t, cc, dl, tag, -1, w, lane);
#pragma unroll 1
    for (int ch = 0; ch < cc.n - 1; ch++) {
      conv_step<true, true, 20>(P, t, cc, dl, tag, ch, w, lane);
      if (cc.j < 0 && ch == 3) bar_arrive(0, 160);
      if (ch == 0) TIM(21);
    }
    conv_step<false, true, 30>(P, t, cc, dl, tag, cc.n - 1, w, lane);
  }
  TIM(22);
}

__device__ __forceinline__ cx csel(bool k, cx a, cx b) { return {k ? a.r : b.r, k ? a.i : b.i}; }
__device__ __forceinline__ void ld2cx(uint32_t a, cx& x, cx& y) {
  const uint4 v = lds128(a);
  x = {__uint_as_float(v.x), __uint_as_float(v.y)};
  y = {__uint_as_float(v.z), __uint_as_float(v.w)};
}
__device__ __forceinline__ cx ldcx(uint32_t a) {
  cx x;
  asm volatile("ld.shared.v2.f32 {%0,%1}, [%2];" : "=f"(x.r), "=f"(x.i) : "r"(a) : "memory");
  return x;
}

__device__ __forceinline__ void scan_epilogue(float (&aR)[64], float (&aI)[64], uint32_t last_empty, int ph, int ti, int pj, int tid) {
  const int w = tid >> 5, lane = tid & 31, r = lane >> 2, c = lane & 3;
  const uint32_t par = S_PAR + (ph * 64 + 16 * w + r) * 16;
  uint4* agg = g_agg + ph * 16 * 256 + pj * 32 + 8 * w + r;
  const uint32_t tag = (lds32(S_EP) + 1) & 3;
  cx h[2];
  {
    cx lam[2], a[2];
#pragma unroll
    for (int q = 0; q < 2; q++) { lam[q] = ldcx(par + q * 128); h[q] = ldcx(par + 2048 + q * 128); }
    WG_WAIT(0);
    if (elect_one()) mbar_arrive(last_empty);
    asm volatile("setmaxnreg.inc.sync.aligned.u32 168;");
    reg_fence(aR); reg_fence(aI);
    TIM(3 + ph * 2);
#pragma unroll
    for (int q = 0; q < 2; q++) a[q] = {aR[2 * q], aI[2 * q]};
#pragma unroll
    for (int s = 1; s < 32; s++)
#pragma unroll
      for (int q = 0; q < 2; q++) {
        const int i = 4 * (s >> 1) + 2 * q + (s & 1);
        a[q] = cfma(lam[q], a[q], {aR[i], aI[i]});
      }
    sched_fence<1>();
    cx t[2][3];
#pragma unroll
    for (int q = 0; q < 2; q++)
#pragma unroll
      for (int k = 0; k < 3; k++) t[q][k] = {__shfl_up_sync(~0u, a[q].r, k + 1, 4), __shfl_up_sync(~0u, a[q].i, k + 1, 4)};
#pragma unroll
    for (int q = 0; q < 2; q++) {
      const cx z = {0.f, 0.f};
      cx ex = cfma(h[q], csel(c >= 3, t[q][2], z), csel(c >= 2, t[q][1], z));
      ex = cfma(h[q], ex, csel(c >= 1, t[q][0], z));
      a[q] = cfma(h[q], ex, a[q]);
      const cx u = cfma(lam[q], ex, {aR[2 * q], aI[2 * q]});
      aR[2 * q] = u.r; aI[2 * q] = u.i;
    }
    if (c == 3)
      asm volatile("st.relaxed.gpu.global.v4.u32 [%0], {%1,%2,%3,%4};" ::"l"(agg + ti * 256),
                   "r"((__float_as_uint(a[0].r) & ~3u) | tag), "r"((__float_as_uint(a[0].i) & ~3u) | tag),
                   "r"((__float_as_uint(a[1].r) & ~3u) | tag), "r"((__float_as_uint(a[1].i) & ~3u) | tag) : "memory");
    TIM(8 + ph * 4);
  }
  if (ti > 0) {
    const uint2* ap = (const uint2*)(agg + (ti - 1 - (c >> 1)) * 256) + (c & 1);
    const int cnt = ti - (c >> 1);
    const cx one = {1.f, 0.f};
    const cx l128 = ldcx(par + 2048 + 8 + (c & 1) * 128), l256 = csq(l128), fa = csel(c & 2, l128, one);
#pragma unroll
    for (int q = 0; q < 2; q++) h[q] = cmul(csel(c & 1, h[q], one), csel(c & 2, csq(h[q]), one));
    uint2 v[8];
    int n = SPIN_LIMIT;
    bool bad;
    __nanosleep(AGG_NS);
    do {
      uint32_t x = 0;
#pragma unroll
      for (int j = 0; j < 8; j++) {
        v[j] = make_uint2(tag, tag);
        asm volatile("{.reg .pred p; setp.lt.s32 p, %3, %4; @p ld.relaxed.gpu.global.v2.u32 {%0,%1}, [%2];}"
                     : "+r"(v[j].x), "+r"(v[j].y) : "l"(ap - j * 1024), "r"(2 * j), "r"(cnt) : "memory");
      }
#pragma unroll
      for (int j = 0; j < 8; j++) { v[j].x ^= tag; v[j].y ^= tag; x |= v[j].x | v[j].y; }
      bad = __any_sync(~0u, x & 3);
    } while (bad && --n);
    trap_if(n == 0);
    cx a = {__uint_as_float(v[7].x), __uint_as_float(v[7].y)};
#pragma unroll
    for (int j = 6; j >= 0; j--) a = cfma(l256, a, {__uint_as_float(v[j].x), __uint_as_float(v[j].y)});
    a = cmul(a, fa);
    const cx t1 = {__shfl_xor_sync(~0u, a.r, 1), __shfl_xor_sync(~0u, a.i, 1)};
    const cx t2 = {__shfl_xor_sync(~0u, a.r, 2), __shfl_xor_sync(~0u, a.i, 2)};
    const cx t3 = {__shfl_xor_sync(~0u, a.r, 3), __shfl_xor_sync(~0u, a.i, 3)};
    const cx own = {a.r + t2.r, a.i + t2.i}, oth = {t1.r + t3.r, t1.i + t3.i};
#pragma unroll
    for (int q = 0; q < 2; q++) h[q] = cmul(csel((c & 1) == q, own, oth), h[q]);
  } else {
    h[0] = h[1] = {0.f, 0.f};
  }
  TIM(9 + ph * 4);
  cx lam[2];
  uint32_t cr[2], nci[2];
#pragma unroll
  for (int q = 0; q < 2; q++) {
    const uint4 v = lds128(par + q * 128);
    lam[q] = {__uint_as_float(v.x), __uint_as_float(v.y)};
    cr[q] = v.z; nci[q] = v.w;
  }
  uint4* hg = g_h + (size_t)(ti * 32 + ph * 16 + pj) * 1024 + w * 64 + r * 4 + (c ^ (r >> 1));
  const uint32_t hs = S_STG + w * 1024 + r * 64 + ((c ^ (r >> 1)) << 4);
  if (RE_EARLY) mbar_wait(B_SFREE + 16 * ph, 0);
  uint32_t pr[4][2][4], pi[4][2][4], re[4][2][4];
#pragma unroll
  for (int i = 0; i < 4; i++) {
#pragma unroll
    for (int s2 = 0; s2 < 4; s2++)
#pragma unroll
      for (int q = 0; q < 2; q++) {
        const int k = 4 * (4 * i + s2) + 2 * q;
        cx h0 = cfma(lam[q], h[q], {aR[k], aI[k]});
        h[q] = cfma(lam[q], h0, {aR[k + 1], aI[k + 1]});
        pr[i][q][s2] = pack2(h0.r, h[q].r);
        pi[i][q][s2] = pack2(h0.i, h[q].i);
        re[i][q][s2] = hfma2(pr[i][q][s2], cr[q], hmul2(pi[i][q][s2], nci[q]));
      }
#pragma unroll
    for (int q = 0; q < 2; q++) {
      stg128(hg + i * 256 + q * 32, re[i][q][0], re[i][q][1], re[i][q][2], re[i][q][3]);
      if (i < RE_EARLY) sts128(hs + i * 4096 + q * 512, re[i][q][0], re[i][q][1], re[i][q][2], re[i][q][3]);
    }
    if (i == 0 && (P2F & 1)) sched_fence<7>();
    if (i == 1 && (P2F & 2)) sched_fence<8>();
    if (i == 2 && (P2F & 1)) sched_fence<6>();
  }
  bar_arrive(9, 160);
  sched_fence<9>();
  TIM(10 + ph * 4);
  if (!RE_EARLY) mbar_wait(B_SFREE + 16 * ph, 0);
  if (ph == 0) mbar_wait(B_SFREE + 8, 0);
#pragma unroll
  for (int q = 0; q < 2; q++) {
    const uint32_t ncr = cr[q] ^ 0x80008000u;
#pragma unroll
    for (int i = 0; i < 4; i++) {
      uint32_t o[4];
#pragma unroll
      for (int s2 = 0; s2 < 4; s2++) o[s2] = hfma2(pi[i][q][s2], ncr, hmul2(pr[i][q][s2], nci[q]));
      if (i >= RE_EARLY) sts128(hs + i * 4096 + q * 512, re[i][q][0], re[i][q][1], re[i][q][2], re[i][q][3]);
      sts128(hs + 16384 + i * 4096 + q * 512, o[0], o[1], o[2], o[3]);
      if (IM_NS) __nanosleep(IM_NS);
      stg128(hg + 8192 + i * 256 + q * 32, o[0], o[1], o[2], o[3]);
    }
  }
  fence_async_smem();
  __syncwarp();
  if (elect_one()) mbar_arrive(B_LOC + 8 * ph);
  bar_arrive(10, 160);
  bar_sync(1 + ph, 128);
  asm volatile("setmaxnreg.dec.sync.aligned.u32 160;");
}

__device__ __forceinline__ constexpr uint32_t e_addr(int o, int mh) { return S_STG + (o * 2 + mh) * 2048; }
__device__ __forceinline__ void eterm(const Ptrs& p, int ti, int pj, int tid) {
  const int w = tid >> 5, lane = tid & 31, r = lane >> 2, c = lane & 3;
  const int trow = 64 * (w & 1) + 8 * (w >> 1) + r;
  const int rs = 2 * (r & 3) + (r >> 2);
  uint2 xv[2][8][2], ds[8];
  {
    uint2 gw[8];
#pragma unroll
    for (int jj = 0; jj < 8; jj++) {
      gw[jj] = ldg64(p.gw + pj * 128 + 16 * jj + 4 * c);
      ds[jj] = ldg64(p.dskip + pj * 128 + 16 * jj + 4 * c);
    }
#pragma unroll
    for (int g = 0; g < 2; g++) {
      mbar_wait(B_XT + 8 * g, 0);
#pragma unroll
      for (int i = 0; i < 4; i++)
#pragma unroll
        for (int jj = 4 * g; jj < 4 * g + 4; jj++)
          xv[i >> 1][jj][i & 1] = lds64(sb + ((48 + g) % NS) * STAGE + (trow - r + rs + 16 * (i >> 1) + 32 * (i & 1)) * 128 + (((2 * (jj & 3) + (c >> 1)) ^ rs) << 4) + (c & 1) * 8);
      fence_async_smem();
      __syncwarp();
      if (elect_one()) mbar_arrive(B_XT + 16 + 8 * g);
    }
    sched_fence<55>();
    TIM(27);
    float s[4];
#pragma unroll
    for (int i = 0; i < 4; i++) {
      s[i] = 0.f;
#pragma unroll
      for (int jj = 0; jj < 8; jj += 2) {
        const uint2 x = xv[i >> 1][jj][i & 1], y = xv[i >> 1][jj + 1][i & 1];
        const uint32_t q = hfma2(x.x, gw[jj].x, hfma2(x.y, gw[jj].y, hfma2(y.x, gw[jj + 1].x, hmul2(y.y, gw[jj + 1].y))));
        s[i] += bf_lo(q) + bf_hi(q);
      }
    }
    float u0 = (c & 1) ? s[1] : s[0], v0 = (c & 1) ? s[0] : s[1];
    float u1 = (c & 1) ? s[3] : s[2], v1 = (c & 1) ? s[2] : s[3];
    u0 += __shfl_xor_sync(~0u, v0, 1);
    u1 += __shfl_xor_sync(~0u, v1, 1);
    float u = (c & 2) ? u1 : u0;
    u += __shfl_xor_sync(~0u, (c & 2) ? u0 : u1, 2);
    const uint32_t tag = (lds32(S_EP) + 1) & 3;
    asm volatile("st.relaxed.gpu.global.u32 [%0], %1;" ::"l"(g_gate + pj * SEQ + ti * 128 + trow + 16 * (c >> 1) + 32 * (c & 1)),
                 "r"((__float_as_uint(u) & ~3u) | tag) : "memory");
    gate_finish(ti, tid, tag);
  }
  bar_sync(2, 128);
  TIM(31);
  uint32_t g2[2][2], og2[2][2];
#pragma unroll
  for (int mh = 0; mh < 2; mh++)
#pragma unroll
    for (int hf = 0; hf < 2; hf++) {
      uint32_t g;
      asm volatile("ld.shared.u32 %0, [%1];" : "=r"(g) : "r"(S_G + (trow + 16 * mh + 32 * hf) * 4) : "memory");
      g2[mh][hf] = __byte_perm(g, g, 0x3232);
      og2[mh][hf] = hsub2(0x3f803f80u, g2[mh][hf]);
    }
  const int dl = lane & 15;
  const uint32_t za = S_STG + (w & 1) * 2048 + dl * 128;
  const uint32_t tag = (lds32(S_EP) + 1) & 1;
  const int zn = tid >> 4, ck = tid & 15;
  const uint4* zp = g_z + (size_t)(pj * 128 + 4 * (zn >> 1) + (zn & 1)) * 256 + ti * 16 + ck;
  uint4 v[4];
#define ZLOAD(o0) _Pragma("unroll") for (int i = 0; i < 4; i++) \
    asm volatile("ld.relaxed.gpu.global.v4.u32 {%0,%1,%2,%3}, [%4];" : "=r"(v[i].x), "=r"(v[i].y), "=r"(v[i].z), "=r"(v[i].w) \
                 : "l"(zp + (jj_of(o0 + (i >> 1)) * 16 + 2 * (i & 1)) * 256) : "memory")
#pragma unroll
  for (int g = 0; g < 3; g++) {
    const int o0 = g ? 2 + 2 * g : 0, o1 = 4 + 2 * g;
    if (g == 0) {
      mbar_wait_long(B_ZT, 0);
    } else {
      int it = SPIN_LIMIT;
      while (true) {
        uint32_t x = 0;
#pragma unroll
        for (int i = 0; i < 4; i++) {
          v[i].x ^= tag; v[i].y ^= tag; v[i].z ^= tag; v[i].w ^= tag;
          x |= v[i].x | v[i].y | v[i].z | v[i].w;
        }
        if (!__any_sync(~0u, x & 1) || !--it) break;
        __nanosleep(ZL_NS);
        ZLOAD(o0);
      }
      trap_if(it == 0);
#pragma unroll
      for (int i = 0; i < 4; i++)
        sts128(S_STG + (o0 + (i >> 1)) * 4096 + (ck >> 3) * 2048 + (8 * (i & 1) + zn) * 128 + (((ck & 7) ^ zn) << 4), v[i].x, v[i].y, v[i].z, v[i].w);
      bar_sync(2, 128);
    }
    if (g < 2) { ZLOAD(o1); }
    if (g == 2) TIM(16);
#pragma unroll
    for (int mh = 0; mh < 2; mh++) {
      const uint32_t zb = za + (((4 * (lane >> 4) + 2 * mh + (w >> 1)) ^ (dl & 7)) << 4);
#pragma unroll
      for (int o = o0; o < o1; o++) {
        const int jj = jj_of(o);
        uint4 z = ldsm4t(zb + o * 4096);
#pragma unroll
        for (int hf = 0; hf < 2; hf++) {
          uint2& x = xv[mh][jj][hf];
          x.x = hmul2(x.x, hfma2(og2[mh][hf], hf ? z.z : z.x, hmul2(g2[mh][hf], ds[jj].x)));
          x.y = hmul2(x.y, hfma2(og2[mh][hf], hf ? z.w : z.y, hmul2(g2[mh][hf], ds[jj].y)));
        }
      }
    }
    bar_sync(2, 128);
#pragma unroll
    for (int o = o0; o < o1; o++)
#pragma unroll
      for (int mh = 0; mh < 2; mh++) {
        const int jj = jj_of(o);
        sts128(e_addr(o, mh) + tid * 16, xv[mh][jj][0].x, xv[mh][jj][0].y, xv[mh][jj][1].x, xv[mh][jj][1].y);
      }
    bar_arrive(5 + g, 256);
    if (g == 0) TIM(1);
    if (g == 1) TIM(23);
  }
#undef ZLOAD
  TIM(17);
}

__device__ __forceinline__ void store_piece(float (&a)[64], float* op, int jj, const uint4& e, float g0, float g1) {
  stg128(op + 16 * jj, __float_as_uint(fmaf(g0, a[8 * jj], bf_lo(e.x))), __float_as_uint(fmaf(g0, a[8 * jj + 1], bf_hi(e.x))),
         __float_as_uint(fmaf(g0, a[8 * jj + 4], bf_lo(e.y))), __float_as_uint(fmaf(g0, a[8 * jj + 5], bf_hi(e.y))));
  stg128(op + 32 * DM + 16 * jj, __float_as_uint(fmaf(g1, a[8 * jj + 2], bf_lo(e.z))), __float_as_uint(fmaf(g1, a[8 * jj + 3], bf_hi(e.z))),
         __float_as_uint(fmaf(g1, a[8 * jj + 6], bf_lo(e.w))), __float_as_uint(fmaf(g1, a[8 * jj + 7], bf_hi(e.w))));
}

__device__ __forceinline__ void issue_g1(const Maps& m, int s, int sl, int ti, int pj) {
  const uint32_t bar = B_FULL + 8 * sl, dst = sb + sl * STAGE;
  const int k0 = (s & 15) * 64, ch = (s >> 4) * 512 + pj * 64;
  mbar_expect(bar, STAGE);
  tma4d(dst + 16384, &m.x, bar, k0, 0, 4 * ti, 0);
  tma2d(dst, &m.bre, bar, k0, ch);
  tma2d(dst + 8192, &m.bim, bar, k0, ch);
}
__device__ __forceinline__ void producer(const Maps& m, int ti, int pj) {
#pragma unroll
  for (int s = EARLY; s < NS; s++) issue_g1(m, s, s, ti, pj);
  int sl = 0, par = 0;
#pragma unroll 1
  for (int s = NS; s < 32; s++) {
    mbar_wait(B_EMPTY + 8 * sl, par);
    issue_g1(m, s, sl, ti, pj);
    if (++sl == NS) { sl = 0; par ^= 1; }
  }
#pragma unroll 1
  for (int q = 0; q < 32; q++) {
    mbar_wait(B_EMPTY + 8 * sl, par);
    const uint32_t bar = B_FULL + 8 * sl, dst = sb + sl * STAGE;
    const int ph = q >> 4, u = q & 15, part = u < 2 ? u : u >= 9, i = u - 2 - 7 * part;
    const int src = u < 2 ? pj : (MAP == 1 || MAP == 2) ? i + (i >= pj) : (i < 4 ? (~pj & 4) + i : (pj & 4) + i - 4 + (i - 4 >= (pj & 3)));
    if (q == 16 + NS || q == 17 + NS) mbar_wait(B_XT + 8 * (q - 14 - NS), 0);
    mbar_expect(bar, u < 2 ? 16384 : STAGE);
    tma5d(dst + 16384, part ? &m.cim : &m.cre, bar, ph * 512 + src * 64, 0, 0, 0, pj * 8);
    if (u < 2) {
      if (ph) {
        mbar_expect(B_XT + 8 * u, 16384);
        tma4d(dst, &m.x2, B_XT + 8 * u, pj * 128 + u * 64, 0, 0, ti * 16);
      }
    } else {
      if (i == 0) {
        mbar_wait(B_FLG + 8 * (2 * ph + part), 0);
        fence_async_global();
        if (part == 0) TIM(24 + ph);
      }
      bulk_load(dst, g_h + (size_t)(ti * 32 + ph * 16 + part * 8 + src) * 1024, 16384, bar);
    }
    if (++sl == NS) { sl = 0; par ^= 1; }
  }
}

__device__ __forceinline__ void poller(int ti, int pj, int lane, unsigned ep) {
  if (lane < 5) {
    const int f = lane < 4 ? F_H + lane * 16 + ti : F_Z + pj;
    const unsigned need = (ep + 1) * (lane < 4 ? 8 : 16);
    int n = SPIN_LIMIT;
    bool done = false;
    do {
      if (!done && (int)(ld_relaxed(g_flag + f * 32) - need) >= 0) {
        done = true;
        asm volatile("fence.acquire.gpu;" ::: "memory");
        mbar_arrive(B_FLG + 8 * lane);
      }
      if (POLL_NS) __nanosleep(POLL_NS);
    } while (!__all_sync(0x1fu, done) && --n);
    trap_if(n == 0);
  }
}
__device__ __forceinline__ void storer(const Maps& m, int ti, int pj) {
#pragma unroll 1
  for (int job = 0; job < 6; job++) {
    bar_sync(job < 2 ? 4 + job : 9 + (job & 1), 160);
    if (elect_one()) flag_release(job < 2 ? F_U + pj * 2 + job : F_H + (job - 2) * 16 + ti);
    __syncwarp();
    if (job == 2 || job == 4) TIM(7 + job * 2);
  }
  if (elect_one()) {
    mbar_wait_long(B_LOC + 16, 0);
    mbar_wait_long(B_FLG + 32, 0);
    fence_async_global();
    mbar_expect(B_ZT, 16384);
#pragma unroll 1
    for (int o = 0; o < 4; o++) {
      tma5d(S_STG + o * 4096, &m.z, B_ZT, ti * 128, 0, 0, 0, pj * 8 + jj_of(o));
      tma5d(S_STG + o * 4096 + 2048, &m.z, B_ZT, ti * 128 + 64, 0, 0, 0, pj * 8 + jj_of(o));
    }
  }
}

__device__ __forceinline__ void kv_loader(const Maps& m, int ti, int pj, unsigned t_start) {
  unsigned tt = t_start + KV0_AT;
#pragma unroll 1
  for (int st = 0; st < 4; st++) {
    const int d = pj * 128 + (st >> 1) * 64, tb = ti * 16 + (st & 1) * 8;
    const uint32_t bar = B_PIN + 8 * st;
    if (st >= 2) { bar_sync(st == 2 ? 3 : 11, 160); fence_async_smem(); }
    if (elect_one()) {
      mbar_expect(bar, 16384 + 384);
      if (st == 2) tt = t_start + KV1_AT;
      if ((int)(clock() - tt) > 0) tt = clock();
#pragma unroll 1
      for (int i = 0; i < 4; i++) {
        wait_clock(tt);
        tt += st >= 2 ? KV_GAP1 : KV_GAP0;
        tma3d(S_STG + (st & 1) * 16384 + i * 4096, (i & 2) ? &m.v : &m.k, bar, d, tb, (i & 1) * 4);
        if (i == 0) tma3d(S_T + st * 512, &m.kh, bar, d, tb - 1, 5);
      }
    }
    tt = __shfl_sync(~0u, tt, 0);
  }
}

__device__ __forceinline__ void conv_loader(const Maps& m, const Ptrs& p, const ConvCtx& cc, int eb, int lane, unsigned t_start) {
  const unsigned ep = ld_relaxed(g_epoch + eb);
  wait_clock(t_start + SPF_AT);
#pragma unroll 1
  for (int ch = 0; ch < cc.n; ch++) {
    const int d = cc.chan(ch);
    const uint32_t bar = cc.inbar + 8 * (ch & 1), dst = cc.buf + (ch & 1) * 8192;
    const bool first = ch == 0 || ch == (cc.j < 0 ? 3 : 1);
    if (ch >= 2) bar_sync(cc.nb + 2 + (ch & 1), 160);
    if (elect_one()) {
      mbar_expect(cc.inbar + 16, 4096);
      bulk_load(dst + 4096, p.f + (size_t)d * SEQ, 4096, cc.inbar + 16);
      if (!first) { mbar_expect(bar, 4096); tma3d(dst, &m.u, bar, 0, d & 31, d & ~31); }
      if (ch + 1 < cc.n) l2_prefetch(p.f + (size_t)cc.chan(ch + 1) * SEQ, 4096);
    }
    __syncwarp();
    const uint32_t a = dst + 4096 + 128 + (lane >> 3) * 256 + (lane & 7) * 16;
    mbar_wait(cc.inbar + 16, ch & 1);
#pragma unroll 1
    for (uint32_t i = a; i < a + 4096; i += 2048) {
      const uint4 x = lds128(i), y = lds128(i + 1024);
      __syncwarp();
      sts128(i ^ 16, x.x, x.y, x.z, x.w);
      sts128((i ^ 16) + 1024, y.x, y.y, y.z, y.w);
    }
    fence_async_smem();
    __syncwarp();
    if (elect_one()) {
      mbar_arrive(bar);
      if (first) {
        int n = SPIN_LIMIT;
        while ((int)(ld_relaxed(g_flag + (F_U + (d >> 6)) * 32) - (ep + 1) * 16) < 0 && --n) __nanosleep(POLL_NS);
        trap_if(n == 0);
        asm volatile("fence.acquire.gpu;" ::: "memory");
        fence_async_global();
        mbar_expect(bar, 4096);
        tma3d(dst, &m.u, bar, 0, d & 31, d & ~31);
      }
    }
    __syncwarp();
    if (cc.j < 0 && ch == 6) {
      bar_sync(0, 160);
      if (elect_one()) flag_release(F_Z + cc.pj);
      __syncwarp();
    }
  }
  if (cc.j >= 0 && lane == 0) g_epoch[eb] = ep + 1;
}

struct Ring { uint32_t off, par, rel; };
__device__ __forceinline__ void desc_touch(const uint64_t (&c)[12][NS]) {
  uint32_t x = 0;
#pragma unroll
  for (int i = 0; i < 12 * NS; i += 4) x |= (uint32_t)(&c[0][0])[i];
  trap_if((x | (uint32_t)c[11][NS - 1]) == 0);
}
template <int TA, bool TAB, bool LOC = false>
__device__ __forceinline__ void gemm_steps(float (&a0)[64], float (&a1)[64], Ring& r, int n, const uint64_t (&c)[12][NS], int slot) {
#pragma unroll 1
  do {
    const uint32_t off = r.off, rel = r.rel;
    full_wait(B_FULL + off, r.par, slot);
    r.rel = off;
    r.off += 8;
    if (r.off == 8 * NS) { r.off = 0; r.par ^= 1; }
    WG_FENCE();
#define DESC(i) (*(const uint64_t*)((const char*)c[i] + off))
#pragma unroll
    for (int k = 0; k < 4; k++) {
      const uint64_t db = TAB ? DESC(3 * k) : mkdesc(off * 256 + dlo(sb + 16384 + 32 * k, 16), 1024, 1);
      if (LOC) {
        const int acc = k || rel != B_DUMMY - B_EMPTY;
        wgmma_ss128p<TA>(a0, mkdesc(dlo(S_STG + 32768 + 1024 * k, 4096) - n * 1024, 512, 2), db, acc);
        wgmma_ss128p<TA>(a1, mkdesc(dlo(S_STG + 32768 + 8192 + 1024 * k, 4096) - n * 1024, 512, 2), db, acc);
      } else {
        wgmma_ss128<TA, 0, 1>(a0, TAB ? DESC(3 * k + 1) : mkdesc(off * 256 + dlo(sb + 32 * k, 16), 1024, 1), db);
        wgmma_ss128<TA, 0, 1>(a1, TAB ? DESC(3 * k + 2) : mkdesc(off * 256 + dlo(sb + 8192 + 32 * k, 16), 1024, 1), db);
      }
      if (k == RELK) {
        WG_COMMIT();
        WG_WAIT(1);
        if (elect_one()) mbar_arrive(B_EMPTY + rel);
      }
    }
#undef DESC
    if (RELK < 3) WG_COMMIT();
  } while (--n);
}

__global__ void __launch_bounds__(512, 1) fused_kernel(const __grid_constant__ Maps m, const __grid_constant__ Ptrs p) {
  extern __shared__ __align__(1024) uint8_t smem_raw[];
  int b = blockIdx.x;
  {
    int sm, nsm;
    asm volatile("mov.u32 %0, %%smid;" : "=r"(sm));
    asm volatile("mov.u32 %0, %%nsmid;" : "=r"(nsm));
    const int tp = sm >> 1, q = ((tp - 32) * 37) >> 8;
    const int g = tp < 32 ? tp & 7 : (tp < 60 ? tp - 31 - 7 * q : (tp < 62 ? 8 : 0));
    const int j = tp < 32 ? tp >> 3 : (tp < 60 ? 4 + q : (tp < 62 ? tp - 60 : tp - 58));
    if (nsm == 132) b = g * 16 + j * 2 + (sm & 1);
    b = __shfl_sync(~0u, b, 0);
  }
  const int spare = b - 128;
  const int ti = ((b >> 5) << 2) | (b & 3), pj = (((b >> 4) & 1) << 2) | ((b >> 2) & 3);
  const int wid = __shfl_sync(~0u, threadIdx.x >> 5, 0), wg = wid >> 2, tid = threadIdx.x & 127, lane = threadIdx.x & 31;
  if (wg == 0) TIM(0);
  const unsigned t_start = clock();
  if (wid == 12) {
    if (elect_one()) {
      asm volatile("prefetch.tensormap [%0];" ::"l"(&m.x) : "memory");
      asm volatile("prefetch.tensormap [%0];" ::"l"(&m.bre) : "memory");
      asm volatile("prefetch.tensormap [%0];" ::"l"(&m.bim) : "memory");
#pragma unroll
      for (int i = 0; i < NS; i++) mbar_init(B_FULL + 8 * i, (i < 2 && spare >= 0) ? 2 : 1);
      fence_async_smem();
#pragma unroll
      for (int s = 0; s < EARLY; s++) if (spare < 0) issue_g1(m, s, s, ti, pj);
    }
  } else if (wid == 13) {
    if (elect_one()) {
      trap_if((uint32_t)__cvta_generic_to_shared(smem_raw) != sb);
#pragma unroll
      for (uint32_t bar = B_EMPTY; bar < S_EP; bar += 8) mbar_init(bar, (bar < B_CINF || (bar >= B_SFREE && bar < B_ZT) || bar == B_XT + 16 || bar == B_XT + 24) ? 4 :
                           (bar < B_CINF + 16 || ((bar == B_PIN || bar == B_PIN + 8) && spare >= 0)) ? 2 : 1);
      fence_async_smem();
    }
  }
  __syncwarp();
  if (wg == 3) {
    asm volatile("setmaxnreg.dec.sync.aligned.u32 %0;" ::"n"(RV == 2 ? 32 : 24));
    bar_sync(1, 128);
    if (spare < 0) {
      if (wid == 13) { bar_arrive(2, 160); bar_arrive(12, 160); }
      bar_arrive(0, 256);
    } else {
      bar_arrive(0, 512);
    }
    if (wid == 13) {
      if (spare < 0) {
        const unsigned ep = ld_relaxed(g_epoch + b);
        kv_loader(m, ti, pj, t_start);
        poller(ti, pj, lane, ep);
      }
    } else if (wid == 15 || spare >= 0) {
      const ConvCtx cc = conv_ctx(spare, wid == 12 ? 0 : wid - 13, ti, pj);
      conv_loader(m, p, cc, spare < 0 ? b : 128 + cc.j, lane, t_start);
    } else if (wid == 12) {
      if (elect_one()) producer(m, ti, pj);
    } else {
      storer(m, ti, pj);
    }
  } else if (wg == 2 || spare >= 0) {
    asm volatile("setmaxnreg.inc.sync.aligned.u32 160;");
    conv_main(p, conv_ctx(spare, wg, ti, pj), spare < 0 ? b : 128 + spare * 3 + wg, tid);
  } else {
    asm volatile("setmaxnreg.inc.sync.aligned.u32 %0;" ::"n"(RV == 3 ? 168 : 160));
    if (wg == 1) {
      const int ch = (tid >> 6) * 512 + pj * 64 + (tid & 63);
      const unsigned ep = ld_relaxed(g_epoch + b);
      const float lr = __bfloat162float(p.lre[ch]), li = __bfloat162float(p.lim[ch]);
      const float dt = bf_round(expf(__bfloat162float(p.ldt[ch])));
      float sn, cs;
      sincosf(dt * li, &sn, &cs);
      const float ex = expf(dt * lr);
      const float ar = ex * cs, ai = ex * sn;
      const float inv = 2.f / (lr * lr + li * li);
      const float cr = ((ar - 1.f) * lr + ai * li) * inv, ci = (ai * lr - (ar - 1.f) * li) * inv;
      sts128(S_PAR + tid * 16, __float_as_uint(ar), __float_as_uint(ai), pack2(cr, cr), pack2(-ci, -ci));
      const cx l32 = csq(csq(csq(csq(csq({ar, ai}))))), l128 = csq(csq(l32));
      sts128(S_PAR + 2048 + tid * 16, __float_as_uint(l32.r), __float_as_uint(l32.i), __float_as_uint(l128.r), __float_as_uint(l128.i));
      if (tid == 0) asm volatile("st.shared.u32 [%0], %1;" ::"r"(S_EP), "r"(ep) : "memory");
      bar_arrive(6, 256);
      bar_sync(2, 160);
      desc_touch(p.dc1);
      desc_touch(p.dc2);
      prep<0>(p, ti, pj, wid & 3, lane);
    }
    float a0[64], a1[64];
    Ring ring = {8u * wg * (16 % NS), wg * ((16u / NS) & 1), B_DUMMY - B_EMPTY};
    zero(a0); zero(a1);
    reg_fence(a0); reg_fence(a1);
    sched_fence<61>();
    bar_sync(wg * 7, 256);
    TIM(2 + wg * 2);
    if (wg == 0) gemm_steps<0, false>(a0, a1, ring, 15, p.dc1, 0);
    else gemm_steps<0, true>(a0, a1, ring, 15, p.dc1, 1);
    bar_arrive(7 + wg, 256);
    gemm_steps<0, false>(a0, a1, ring, 1, p.dc1, wg);
    if (wg == 0) bar_sync(6, 256);
    scan_epilogue(a0, a1, B_EMPTY + ring.rel, wg, ti, pj, tid);
    if (wg == 1) {
      eterm(p, ti, pj, tid);
    } else {
      ring = {8 * (32 % NS), (32 / NS) & 1, B_DUMMY - B_EMPTY};
#pragma unroll
      for (int i = 0; i < 64; i++) asm volatile("" : "=f"(a0[i]), "=f"(a1[i]));
      bar_sync(8, 256);
      TIM(6);
#pragma unroll 1
      for (int o = 0; o < 4; o++) {
        if (!(o & 1)) {
          if (o) TIM(18);
          full_wait(B_LOC + 4 * o, 0, 2 + 2 * o);
          gemm_steps<1, true, true>(a0, a1, ring, 2, p.dc2, 3 + 2 * o);
        }
        gemm_steps<1, true>(a0, a1, ring, (o & 1) ? (o == 1 ? 13 : 13 - RES) : 1, p.dc2, 4 + 2 * o - (o & 1));
        if (!(o & 1) && elect_one()) {
          mbar_arrive(o ? B_LOC + 16 : B_SFREE + 16);
        }
      }
#pragma unroll
      for (int i = 0; i < RES; i++) {
        const int sl = (64 - RES + i) % NS;
        full_wait(B_FULL + 8 * sl, ((64 - RES + i) / NS) & 1, 10);
        WG_FENCE();
#pragma unroll
        for (int k = 0; k < 4; k++) wgmma_ss128<1, 0, 1>(a0, p.dc2[3 * k + 1][sl], p.dc2[3 * k][sl]);
        WG_COMMIT();
        if (i == 0 && RES == NS) { WG_WAIT(1); if (elect_one()) mbar_arrive(B_EMPTY + ring.rel); }
      }
      const int w = tid >> 5, trow = 16 * 0 + 64 * (w & 1) + 8 * (w >> 1) + (lane >> 2);
      float* op = p.out + (size_t)(ti * 128 + trow) * DM + pj * 128 + 4 * (lane & 3);
      float g[4];
      uint4 e;
#pragma unroll
      for (int i = 0; i < RES; i++) {
        const int sl = (64 - RES + i) % NS;
        if (i == 0) WG_FENCE();
#pragma unroll
        for (int k = 0; k < 4; k++) wgmma_ss128<1, 0, 1>(a1, p.dc2[3 * k + 2][sl], p.dc2[3 * k][sl]);
        WG_COMMIT();
        if (i == 0) {
          bar_sync(5, 256);
#pragma unroll
          for (int q = 0; q < 4; q++) g[q] = __uint_as_float(lds32(S_G + (trow + 16 * (q >> 1) + 32 * (q & 1)) * 4));
          e = lds128(e_addr(0, 0) + tid * 16);
          WG_WAIT(1);
          reg_fence(a0);
        }
        if (i < 4) {
          const uint4 e0 = e;
          e = lds128(e_addr((i + 1) & 3, i == 3) + tid * 16);
          store_piece(a0, op, jj_of(i), e0, g[0], g[1]);
        }
        if (i == 0) sched_fence_async<70>(); if (i == 1) sched_fence_async<71>(); if (i == 2) sched_fence_async<72>(); if (i == 3) sched_fence_async<73>();
      }
      TIM(26);
      WG_WAIT(0);
      reg_fence(a1);
      TIM(7);
#pragma unroll
      for (int o = 0; o < 8; o++) {
        if (o == 4 || o == 6) bar_sync(4 + (o >> 1), 256);
        if (o >= 4) store_piece(a0, op, jj_of(o), lds128(e_addr(o, 0) + tid * 16), g[0], g[1]);
        store_piece(a1, op + 16 * DM, jj_of(o), o ? lds128(e_addr(o, 1) + tid * 16) : e, g[2], g[3]);
      }
      if (tid == 0) g_epoch[b] = lds32(S_EP) + 1;
      TIM(19);
    }
  }
}

typedef CUresult (*EncFn)(CUtensorMap*, CUtensorMapDataType, cuuint32_t, void*, const cuuint64_t*, const cuuint64_t*,
                          const cuuint32_t*, const cuuint32_t*, CUtensorMapInterleave, CUtensorMapSwizzle,
                          CUtensorMapL2promotion, CUtensorMapFloatOOBfill);

void encode(EncFn enc, CUtensorMap* m, const void* ptr, int rank, const cuuint64_t* dims, const cuuint64_t* strides,
            const cuuint32_t* box, CUtensorMapSwizzle sw) {
  cuuint32_t es[5] = {1, 1, 1, 1, 1};
  enc(m, CU_TENSOR_MAP_DATA_TYPE_BFLOAT16, rank, const_cast<void*>(ptr), dims, strides, box, es, CU_TENSOR_MAP_INTERLEAVE_NONE,
      sw, PROMO, CU_TENSOR_MAP_FLOAT_OOB_FILL_NONE);
}

}

extern "C" void kernel_launch(void* const* d_in, const int* in_sizes, int n_in, void* d_out, int out_size) {
  typedef const __nv_bfloat16* bp;
  Ptrs p;
  p.x = (bp)d_in[0]; p.lre = (bp)d_in[1]; p.lim = (bp)d_in[2]; p.bre = (bp)d_in[3]; p.bim = (bp)d_in[4];
  p.cre = (bp)d_in[5]; p.cim = (bp)d_in[6]; p.ldt = (bp)d_in[7]; p.dskip = (bp)d_in[8];
  p.k = (bp)d_in[10]; p.v = (bp)d_in[11]; p.shift = (bp)d_in[12]; p.f = (bp)d_in[13]; p.ssmd = (bp)d_in[14];
  p.gw = (bp)d_in[15]; p.out = (float*)d_out;

  for (int sl = 0; sl < NS; sl++)
    for (int k = 0; k < 4; k++) {
      const uint64_t h128 = (uint64_t)(64u | (1u << 30)) << 32, h64 = (uint64_t)(32u | (2u << 30)) << 32;
      const uint32_t st = sb + sl * STAGE;
      p.dc1[3 * k][sl] = p.dc2[3 * k][sl] = h128 | dlo(st + 16384 + 32 * k, 16);
      p.dc1[3 * k + 1][sl] = h128 | dlo(st + 32 * k, 16);
      p.dc1[3 * k + 2][sl] = h128 | dlo(st + 8192 + 32 * k, 16);
      p.dc2[3 * k + 1][sl] = h64 | dlo(st + 1024 * k, 4096);
      p.dc2[3 * k + 2][sl] = h64 | dlo(st + 8192 + 1024 * k, 4096);
    }
  EncFn enc = nullptr;
  cudaDriverEntryPointQueryResult qr;
  cudaGetDriverEntryPoint("cuTensorMapEncodeTiled", (void**)&enc, cudaEnableDefault, &qr);
  void *zptr = nullptr, *uptr = nullptr;
  cudaGetSymbolAddress(&zptr, g_z);
  cudaGetSymbolAddress(&uptr, g_u);

  Maps m;
  {
    cuuint64_t d[4] = {1024, 2, 64, 16}, s[3] = {2048, 65536, 4096};
    cuuint32_t bx[4] = {64, 2, 4, 16};
    encode(enc, &m.x, p.x, 4, d, s, bx, CU_TENSOR_MAP_SWIZZLE_128B);
  }
  {
    cuuint64_t d[2] = {1024, 1024}, s[1] = {2048};
    cuuint32_t bx[2] = {64, 64};
    encode(enc, &m.bre, p.bre, 2, d, s, bx, CU_TENSOR_MAP_SWIZZLE_128B);
    encode(enc, &m.bim, p.bim, 2, d, s, bx, CU_TENSOR_MAP_SWIZZLE_128B);
  }
  {
    cuuint64_t d[5] = {1024, 2, 4, 2, 64}, s[4] = {2048, 8192, 4096, 32768};
    cuuint32_t bx[5] = {64, 2, 4, 2, 8};
    encode(enc, &m.cre, p.cre, 5, d, s, bx, CU_TENSOR_MAP_SWIZZLE_128B);
    encode(enc, &m.cim, p.cim, 5, d, s, bx, CU_TENSOR_MAP_SWIZZLE_128B);
  }
  {
    cuuint64_t d[3] = {64, 32, 1024}, s[2] = {128, 4096};
    cuuint32_t bx[3] = {64, 1, 32};
    encode(enc, &m.u, uptr, 3, d, s, bx, CU_TENSOR_MAP_SWIZZLE_NONE);
  }
  {
    cuuint64_t d[3] = {1024, 256, 8}, s[2] = {16384, 2048};
    cuuint32_t bx[3] = {64, 8, 4}, bh[3] = {64, 1, 3};
    encode(enc, &m.k, p.k, 3, d, s, bx, CU_TENSOR_MAP_SWIZZLE_128B);
    encode(enc, &m.kh, p.k, 3, d, s, bh, CU_TENSOR_MAP_SWIZZLE_NONE);
    encode(enc, &m.v, p.v, 3, d, s, bx, CU_TENSOR_MAP_SWIZZLE_128B);
  }
  {
    cuuint64_t d[5] = {2048, 2, 4, 2, 64}, s[4] = {4096, 16384, 8192, 65536};
    cuuint32_t bx[5] = {64, 2, 4, 2, 1};
    encode(enc, &m.z, zptr, 5, d, s, bx, CU_TENSOR_MAP_SWIZZLE_128B);
  }
  {
    cuuint64_t d[4] = {1024, 2, 4, 256}, s[3] = {8192, 2048, 16384};
    cuuint32_t bx[4] = {64, 2, 4, 16};
    encode(enc, &m.x2, p.x, 4, d, s, bx, CU_TENSOR_MAP_SWIZZLE_128B);
  }
  cudaFuncSetAttribute(fused_kernel, cudaFuncAttributeMaxDynamicSharedMemorySize, SMEM_BYTES);
  fused_kernel<<<132, 512, SMEM_BYTES, cudaStreamPerThread>>>(m, p);
}
```

```cpp
#include <cuda_runtime.h>
#include <cuda_bf16.h>
#include <cuda.h>
#include <stdint.h>

namespace {

constexpr int SEQ = 2048, DM = 1024;
#define NSV 5
constexpr int NS = NSV;
constexpr int STAGE = 32768;
#define KV0_AT 300
#define KV_GAP0 600
#define KV1_AT 8200
#define KV_GAP1 450
#define EARLY 2
#define SFM 2
#define RV 1
#define POLL_NS 60
#define IM_NS 40
#define SPF_AT 7000
#define RELK 0
#define RES 5
#define AGG_NS 200
#define ZL_NS 60
#define P2F 3
#define KEEP 16
#define RE_EARLY 0
#define MAP 0
#define WIN 5
#define NPB 4
#define TOFF 1
#define TPACE 0
#define LD_GAP 400
#define LDQ ""
#define PROMO CU_TENSOR_MAP_L2_PROMOTION_L2_128B
constexpr uint32_t sb = 1024;
constexpr uint32_t S_STG = sb + NS * STAGE;
constexpr uint32_t S_CIN = S_STG + 32768;
constexpr uint32_t S_T = S_CIN + 16384;
constexpr uint32_t S_M1 = S_T + 8192;
constexpr uint32_t S_M2 = S_M1 + 4096;
constexpr uint32_t S_PAR = S_M2 + 2048;
constexpr uint32_t S_G = S_PAR + 4096;
constexpr uint32_t S_BAR = S_G + 512;
constexpr int SMEM_BYTES = S_BAR + 512 - sb;
constexpr uint32_t B_FULL = S_BAR, B_EMPTY = B_FULL + 8 * NS, B_CINF = B_EMPTY + 8 * NS,
                   B_FLG = B_CINF + 24, B_SFREE = B_FLG + 40, B_LOC = B_SFREE + 24, B_ZT = B_LOC + 24,
                   B_XT = B_ZT + 8, B_PIN = B_XT + 32, B_DUMMY = B_PIN + 32, S_EP = B_DUMMY + 8;
constexpr int SPIN_LIMIT = 1 << 21;
constexpr int F_H = 0, F_U = 64, F_Z = 80;

struct alignas(64) Maps { CUtensorMap x, bre, bim, cre, cim, u, z, x2, k, kh, v; };
struct Ptrs {
  const __nv_bfloat16 *x, *lre, *lim, *ldt, *dskip, *k, *v, *shift, *f, *ssmd, *gw, *bre, *bim, *cre, *cim;
  float* out;
  uint64_t dc1[12][NS], dc2[12][NS];
};

__device__ uint4 g_h[16 * 32 * 1024];
__device__ uint4 g_u[1024 * 256];
__device__ uint4 g_z[1024 * 256];
__device__ uint4 g_agg[2 * 16 * 256];
__device__ unsigned g_gate[8 * SEQ];
__device__ unsigned g_flag[88 * 32];
__device__ unsigned g_epoch[140];
#define TIM(i)
#define TIMC(i)

#define WG_FENCE() asm volatile("wgmma.fence.sync.aligned;" ::: "memory")
#define WG_COMMIT() asm volatile("wgmma.commit_group.sync.aligned;" ::: "memory")
#define WG_WAIT(n) asm volatile("wgmma.wait_group.sync.aligned %0;" ::"n"(n) : "memory")
#define R8(d, o) "+f"(d[o + 0]), "+f"(d[o + 1]), "+f"(d[o + 2]), "+f"(d[o + 3]), "+f"(d[o + 4]), "+f"(d[o + 5]), "+f"(d[o + 6]), "+f"(d[o + 7])
#define W8(d, o) "=f"(d[o + 0]), "=f"(d[o + 1]), "=f"(d[o + 2]), "=f"(d[o + 3]), "=f"(d[o + 4]), "=f"(d[o + 5]), "=f"(d[o + 6]), "=f"(d[o + 7])
#define L16 "%0,%1,%2,%3,%4,%5,%6,%7,%8,%9,%10,%11,%12,%13,%14,%15"
#define L64 L16 ",%16,%17,%18,%19,%20,%21,%22,%23,%24,%25,%26,%27,%28,%29,%30,%31," \
  "%32,%33,%34,%35,%36,%37,%38,%39,%40,%41,%42,%43,%44,%45,%46,%47,%48,%49,%50,%51,%52,%53,%54,%55,%56,%57,%58,%59,%60,%61,%62,%63"

template <int TA, int TB, int ACC>
__device__ __forceinline__ void wgmma_ss128(float (&d)[64], uint64_t da, uint64_t db) {
  if (ACC)
    asm volatile("wgmma.mma_async.sync.aligned.m64n128k16.f32.bf16.bf16 {" L64 "}, %64, %65, 1, 1, 1, %66, %67;"
                 : R8(d, 0), R8(d, 8), R8(d, 16), R8(d, 24), R8(d, 32), R8(d, 40), R8(d, 48), R8(d, 56)
                 : "l"(da), "l"(db), "n"(TA), "n"(TB));
  else
    asm volatile("wgmma.mma_async.sync.aligned.m64n128k16.f32.bf16.bf16 {" L64 "}, %64, %65, 0, 1, 1, %66, %67;"
                 : W8(d, 0), W8(d, 8), W8(d, 16), W8(d, 24), W8(d, 32), W8(d, 40), W8(d, 48), W8(d, 56)
                 : "l"(da), "l"(db), "n"(TA), "n"(TB));
}
template <int TA>
__device__ __forceinline__ void wgmma_ss128p(float (&d)[64], uint64_t da, uint64_t db, int acc) {
  asm volatile("{.reg .pred p; setp.ne.b32 p, %67, 0;\n"
               "wgmma.mma_async.sync.aligned.m64n128k16.f32.bf16.bf16 {" L64 "}, %64, %65, p, 1, 1, %66, 0;}"
               : R8(d, 0), R8(d, 8), R8(d, 16), R8(d, 24), R8(d, 32), R8(d, 40), R8(d, 48), R8(d, 56)
               : "l"(da), "l"(db), "n"(TA), "r"(acc));
}
template <int ACC, int TB = 0>
__device__ __forceinline__ void wgmma_rs32(float (&d)[16], uint32_t a0, uint32_t a1, uint32_t a2, uint32_t a3, uint64_t db) {
  if (ACC)
    asm volatile("wgmma.mma_async.sync.aligned.m64n32k16.f32.bf16.bf16 {" L16 "}, {%16,%17,%18,%19}, %20, 1, 1, 1, %21;"
                 : R8(d, 0), R8(d, 8) : "r"(a0), "r"(a1), "r"(a2), "r"(a3), "l"(db), "n"(TB));
  else
    asm volatile("wgmma.mma_async.sync.aligned.m64n32k16.f32.bf16.bf16 {" L16 "}, {%16,%17,%18,%19}, %20, 0, 1, 1, %21;"
                 : W8(d, 0), W8(d, 8) : "r"(a0), "r"(a1), "r"(a2), "r"(a3), "l"(db), "n"(TB));
}
template <int N>
__device__ __forceinline__ void reg_fence(float (&d)[N]) {
#pragma unroll
  for (int i = 0; i < N; i++) asm volatile("" : "+f"(d[i])::"memory");
}
__host__ __device__ __forceinline__ constexpr uint32_t dlo(uint32_t addr, uint32_t lbo) { return (addr >> 4) + ((lbo >> 4) << 16); }
__device__ __forceinline__ uint64_t mkdesc(uint32_t lo, uint32_t sbo, uint32_t mode) {
  uint64_t d;
  asm("mov.b64 %0, {%1, %2};" : "=l"(d) : "r"(lo), "r"((sbo >> 4) | (mode << 30)));
  return d;
}
template <int N>
__device__ __forceinline__ void zero(float (&d)[N]) {
#pragma unroll
  for (int i = 0; i < N; i++) d[i] = 0.f;
}
__device__ __forceinline__ void trap_if(int c) {
  asm volatile("{.reg .pred p; .reg .b64 z; setp.ne.s32 p, %0, 0; mov.b64 z, 0; @p st.global.u32 [z], %0;}" ::"r"(c) : "memory");
}
template <int K>
__device__ __forceinline__ void sched_fence() {
  asm volatile("{.reg .pred p; setp.eq.u32 p, %0, %1; @p exit;}" ::"r"(gridDim.x), "n"(256 + K) : "memory");
}
template <int K>
__device__ __forceinline__ void sched_fence_async() {
  asm volatile("{.reg .pred p; .reg .u32 r; setp.ne.u32 p, %0, %1; @p bra.uni SFE;\n"
               "SFL: nanosleep.u32 1000; mov.u32 r, %%clock; setp.eq.u32 p, r, 0; @p bra.uni SFL;\nSFE: }" ::"r"(gridDim.x), "n"(256 + K) : "memory");
}
__device__ __forceinline__ bool elect_one() {
  uint32_t pred;
  asm volatile("{.reg .pred p; elect.sync _|p, 0xffffffff; selp.u32 %0, 1, 0, p;}" : "=r"(pred));
  return pred;
}
__device__ __forceinline__ void mbar_init(uint32_t bar, uint32_t cnt) {
  asm volatile("mbarrier.init.shared::cta.b64 [%0], %1;" ::"r"(bar), "r"(cnt) : "memory");
}
__device__ __forceinline__ bool mbar_try(uint32_t bar, uint32_t par) {
  uint32_t ok;
  asm volatile("{.reg .pred p; mbarrier.try_wait.parity.shared::cta.b64 p, [%1], %2; selp.u32 %0, 1, 0, p;}"
               : "=r"(ok) : "r"(bar), "r"(par) : "memory");
  return ok;
}
#undef DBGV
#define DBGV ((bar - S_BAR) * 2 + par)
__device__ __forceinline__ void mbar_wait(uint32_t bar, uint32_t par) {
  if (__builtin_expect(!mbar_try(bar, par), 0)) {
    int n = SPIN_LIMIT;
    while (!mbar_try(bar, par) && --n) {}
    trap_if(n == 0);
  }
}
#define full_wait(bar, par, slot) mbar_wait(bar, par)
__device__ __forceinline__ void mbar_wait_long(uint32_t bar, uint32_t par) {
  int n = SPIN_LIMIT;
  while (!mbar_try(bar, par) && --n) __nanosleep(100);
  trap_if(n == 0);
}
#undef DBGV
#define DBGV 0
__device__ __forceinline__ void mbar_arrive(uint32_t bar) {
  asm volatile("mbarrier.arrive.shared::cta.b64 _, [%0];" ::"r"(bar) : "memory");
}
__device__ __forceinline__ void mbar_expect(uint32_t bar, uint32_t bytes) {
  asm volatile("mbarrier.arrive.expect_tx.shared::cta.b64 _, [%0], %1;" ::"r"(bar), "r"(bytes) : "memory");
}
__device__ __forceinline__ void tma2d(uint32_t dst, const CUtensorMap* m, uint32_t bar, int c0, int c1) {
  asm volatile("cp.async.bulk.tensor.2d.shared::cluster.global.mbarrier::complete_tx::bytes [%0], [%1, {%3, %4}], [%2];"
               ::"r"(dst), "l"(m), "r"(bar), "r"(c0), "r"(c1) : "memory");
}
__device__ __forceinline__ void tma3d(uint32_t dst, const CUtensorMap* m, uint32_t bar, int c0, int c1, int c2) {
  asm volatile("cp.async.bulk.tensor.3d.shared::cluster.global.mbarrier::complete_tx::bytes [%0], [%1, {%3, %4, %5}], [%2];"
               ::"r"(dst), "l"(m), "r"(bar), "r"(c0), "r"(c1), "r"(c2) : "memory");
}
__device__ __forceinline__ void tma4d(uint32_t dst, const CUtensorMap* m, uint32_t bar, int c0, int c1, int c2, int c3) {
  asm volatile("cp.async.bulk.tensor.4d.shared::cluster.global.mbarrier::complete_tx::bytes [%0], [%1, {%3, %4, %5, %6}], [%2];"
               ::"r"(dst), "l"(m), "r"(bar), "r"(c0), "r"(c1), "r"(c2), "r"(c3) : "memory");
}
__device__ __forceinline__ void tma5d(uint32_t dst, const CUtensorMap* m, uint32_t bar, int c0, int c1, int c2, int c3, int c4) {
  asm volatile("cp.async.bulk.tensor.5d.shared::cluster.global.mbarrier::complete_tx::bytes [%0], [%1, {%3, %4, %5, %6, %7}], [%2];"
               ::"r"(dst), "l"(m), "r"(bar), "r"(c0), "r"(c1), "r"(c2), "r"(c3), "r"(c4) : "memory");
}
__device__ __forceinline__ void bulk_load(uint32_t dst, const void* src, uint32_t bytes, uint32_t bar) {
  asm volatile("cp.async.bulk.shared::cluster.global.mbarrier::complete_tx::bytes [%0], [%1], %2, [%3];"
               ::"r"(dst), "l"(src), "r"(bytes), "r"(bar) : "memory");
}
__device__ __forceinline__ void l2_prefetch(const void* src, uint32_t bytes) {
  asm volatile("cp.async.bulk.prefetch.L2.global [%0], %1;" ::"l"(src), "r"(bytes) : "memory");
}
__device__ __forceinline__ void bar_sync(int id, int n) { asm volatile("bar.sync %0, %1;" ::"r"(id), "r"(n) : "memory"); }
__device__ __forceinline__ void bar_arrive(int id, int n) { asm volatile("bar.arrive %0, %1;" ::"r"(id), "r"(n) : "memory"); }
__device__ __forceinline__ void fence_async_smem() { asm volatile("fence.proxy.async.shared::cta;" ::: "memory"); }
__device__ __forceinline__ void fence_async_global() { asm volatile("fence.proxy.async.global;" ::: "memory"); }
__device__ __forceinline__ void flag_add(int f) {
  asm volatile("red.relaxed.gpu.global.add.u32 [%0], 1;" ::"l"(g_flag + f * 32) : "memory");
}
__device__ __forceinline__ void flag_release(int f) {
  asm volatile("fence.release.gpu;" ::: "memory");
  flag_add(f);
}
__device__ __forceinline__ unsigned ld_relaxed(const unsigned* p) {
  unsigned v;
  asm volatile("ld.relaxed.gpu.global.u32 %0, [%1];" : "=r"(v) : "l"(p) : "memory");
  return v;
}
__device__ __forceinline__ void wait_clock(unsigned t) {
  int d;
  while ((d = (int)(t - (unsigned)clock())) > 0) __nanosleep(d > 600 ? 200 : 40);
}
__device__ __forceinline__ uint32_t pack2(float lo, float hi) {
  uint32_t r;
  asm("cvt.rn.bf16x2.f32 %0, %1, %2;" : "=r"(r) : "f"(hi), "f"(lo));
  return r;
}
__device__ __forceinline__ float bf_lo(uint32_t v) { return __uint_as_float(v << 16); }
__device__ __forceinline__ float bf_hi(uint32_t v) { return __uint_as_float(v & 0xffff0000u); }
__device__ __forceinline__ float bf_round(float v) { return __bfloat162float(__float2bfloat16_rn(v)); }
__device__ __forceinline__ uint32_t hmul2(uint32_t a, uint32_t b) {
  uint32_t r;
  asm("mul.rn.bf16x2 %0, %1, %2;" : "=r"(r) : "r"(a), "r"(b));
  return r;
}
__device__ __forceinline__ uint32_t hadd2(uint32_t a, uint32_t b) {
  uint32_t r;
  asm("add.rn.bf16x2 %0, %1, %2;" : "=r"(r) : "r"(a), "r"(b));
  return r;
}
__device__ __forceinline__ uint32_t hsub2(uint32_t a, uint32_t b) {
  uint32_t r;
  asm("sub.rn.bf16x2 %0, %1, %2;" : "=r"(r) : "r"(a), "r"(b));
  return r;
}
__device__ __forceinline__ uint32_t hfma2(uint32_t a, uint32_t b, uint32_t c) {
  uint32_t r;
  asm("fma.rn.bf16x2 %0, %1, %2, %3;" : "=r"(r) : "r"(a), "r"(b), "r"(c));
  return r;
}
__device__ __forceinline__ uint32_t hneg2(uint32_t a) {
  uint32_t r;
  asm("neg.bf16x2 %0, %1;" : "=r"(r) : "r"(a));
  return r;
}
__device__ __forceinline__ uint4 ldg128(const void* p) {
  uint4 v;
  asm volatile("ld.global.nc" LDQ ".v4.u32 {%0,%1,%2,%3}, [%4];" : "=r"(v.x), "=r"(v.y), "=r"(v.z), "=r"(v.w) : "l"(p));
  return v;
}
__device__ __forceinline__ uint2 ldg64(const void* p) {
  uint2 v;
  asm volatile("ld.global.nc.v2.u32 {%0,%1}, [%2];" : "=r"(v.x), "=r"(v.y) : "l"(p));
  return v;
}
__device__ __forceinline__ void stg128(void* p, uint32_t a, uint32_t b, uint32_t c, uint32_t d) {
  asm volatile("st.global.v4.u32 [%0], {%1,%2,%3,%4};" ::"l"(p), "r"(a), "r"(b), "r"(c), "r"(d) : "memory");
}
__device__ __forceinline__ void sts128(uint32_t a, uint32_t x, uint32_t y, uint32_t z, uint32_t w) {
  asm volatile("st.shared.v4.u32 [%0], {%1,%2,%3,%4};" ::"r"(a), "r"(x), "r"(y), "r"(z), "r"(w) : "memory");
}
__device__ __forceinline__ uint32_t lds32(uint32_t a) {
  uint32_t v;
  asm volatile("ld.shared.u32 %0, [%1];" : "=r"(v) : "r"(a) : "memory");
  return v;
}
__device__ __forceinline__ uint4 lds128(uint32_t a) {
  uint4 v;
  asm volatile("ld.shared.v4.u32 {%0,%1,%2,%3}, [%4];" : "=r"(v.x), "=r"(v.y), "=r"(v.z), "=r"(v.w) : "r"(a) : "memory");
  return v;
}
__device__ __forceinline__ void stsm4(uint32_t a, uint32_t x, uint32_t y, uint32_t z, uint32_t w) {
  asm volatile("stmatrix.sync.aligned.m8n8.x4.shared.b16 [%0], {%1,%2,%3,%4};" ::"r"(a), "r"(x), "r"(y), "r"(z), "r"(w) : "memory");
}
__device__ __forceinline__ void stsm4t(uint32_t a, uint32_t x, uint32_t y, uint32_t z, uint32_t w) {
  asm volatile("stmatrix.sync.aligned.m8n8.x4.trans.shared.b16 [%0], {%1,%2,%3,%4};" ::"r"(a), "r"(x), "r"(y), "r"(z), "r"(w) : "memory");
}
__device__ __forceinline__ uint4 ldsm4t(uint32_t a) {
  uint4 v;
  asm volatile("ldmatrix.sync.aligned.m8n8.x4.trans.shared.b16 {%0,%1,%2,%3}, [%4];" : "=r"(v.x), "=r"(v.y), "=r"(v.z), "=r"(v.w) : "r"(a) : "memory");
  return v;
}
struct cx { float r, i; };
__device__ __forceinline__ cx cmul(cx a, cx b) { return {a.r * b.r - a.i * b.i, a.r * b.i + a.i * b.r}; }
__device__ __forceinline__ cx cfma(cx a, cx b, cx c) { return {fmaf(a.r, b.r, fmaf(-a.i, b.i, c.r)), fmaf(a.r, b.i, fmaf(a.i, b.r, c.i))}; }
__device__ __forceinline__ cx csq(cx a) { return {a.r * a.r - a.i * a.i, 2.f * a.r * a.i}; }
__device__ __forceinline__ cx unit(int num, int den) {
  int m = num & (den - 1);
  if (m >= den / 2) m -= den;
  float s, c;
  __sincosf((float)m * (-6.283185307179586f / (float)den), &s, &c);
  return {c, s};
}

__device__ __forceinline__ uint2 lds64(uint32_t a) {
  uint2 v;
  asm volatile("ld.shared.v2.u32 {%0,%1}, [%2];" : "=r"(v.x), "=r"(v.y) : "r"(a) : "memory");
  return v;
}
__device__ __forceinline__ void prep_taps(const uint4 (&sh)[2], uint32_t (&s)[2][4]) {
#pragma unroll
  for (int e = 0; e < 2; e++) {
    s[e][0] = __byte_perm(sh[e].x, sh[e].z, 0x5410); s[e][1] = __byte_perm(sh[e].x, sh[e].z, 0x7632);
    s[e][2] = __byte_perm(sh[e].y, sh[e].w, 0x5410); s[e][3] = __byte_perm(sh[e].y, sh[e].w, 0x7632);
  }
}
__device__ __forceinline__ void prep_math(const uint2 (&kk)[11], uint2 (&vv)[8], const uint32_t (&s)[2][4]) {
#pragma unroll
  for (int i = 0; i < 8; i++)
#pragma unroll
    for (int e = 0; e < 2; e++) {
      uint32_t a = hmul2((&kk[i].x)[e], s[e][3]);
      a = hfma2((&kk[i + 1].x)[e], s[e][2], a);
      a = hfma2((&kk[i + 2].x)[e], s[e][1], a);
      a = hfma2((&kk[i + 3].x)[e], s[e][0], a);
      (&vv[i].x)[e] = hmul2(a, (&vv[i].x)[e]);
    }
}
__device__ __forceinline__ void prep_store(const uint2 (&vv)[8], int d, int tb) {
  uint4* dst = g_u + (size_t)((d >> 5) * 32 + (tb >> 3)) * 256 + (d & 31) * 8 + ((tb & 7) ^ ((tb >> 3) & 1));
#pragma unroll
  for (int e = 0; e < 2; e++) {
#define U(i) (&vv[i].x)[e]
    stg128(dst + (2 * e) * 8, __byte_perm(U(0), U(1), 0x5410), __byte_perm(U(2), U(3), 0x5410),
           __byte_perm(U(4), U(5), 0x5410), __byte_perm(U(6), U(7), 0x5410));
    stg128(dst + (2 * e + 1) * 8, __byte_perm(U(0), U(1), 0x7632), __byte_perm(U(2), U(3), 0x7632),
           __byte_perm(U(4), U(5), 0x7632), __byte_perm(U(6), U(7), 0x7632));
#undef U
  }
}
template <int PG>
__device__ __forceinline__ void prep(const Ptrs& p, int ti, int pj, int w, int lane) {
  const int tb = lane & 7, chunk = 2 * w + (lane >> 4), ch = chunk * 8 + ((lane >> 3) & 1) * 4, d = pj * 128 + PG * 64 + ch;
  const uint4 sh[2] = {ldg128(p.shift + d * 4), ldg128(p.shift + d * 4 + 8)};
  uint32_t s[2][4];
  prep_taps(sh, s);
#pragma unroll 1
  for (int th = 0; th < 2; th++) {
    uint2 kk[11], vv[8];
    {
      const uint32_t in = S_STG + th * 16384 + (lane & 8);
      const uint32_t a0 = in + tb * 128 + ((chunk ^ tb) << 4);
      const uint32_t hb = tb ? in + (39 + tb) * 128 + ((chunk ^ (tb - 1)) << 4) : S_T + (PG * 2 + th) * 512 + ch * 2;
      const uint32_t hs = tb ? 1024 : 128;
      mbar_wait_long(B_PIN + 16 * PG + 8 * th, 0);
      if (th) TIM(29 + PG);
#pragma unroll
      for (int i = 0; i < 3; i++) kk[i] = lds64(hb + i * hs);
#pragma unroll
      for (int i = 0; i < 8; i++) { kk[3 + i] = lds64(a0 + i * 1024); vv[i] = lds64(a0 + 8192 + i * 1024); }
      prep_math(kk, vv, s);
      sched_fence<52 + PG>();
    }
    if (!PG) bar_arrive(th ? 11 : 3, 160);
    else if (elect_one()) mbar_arrive(B_SFREE + 8 * th);
    prep_store(vv, d, ti * 16 + th * 8 + tb);
  }
  bar_arrive(4 + PG, 160);
}

__device__ __forceinline__ void gate_finish(int ti, int tid, uint32_t tag) {
  float l;
  int n = SPIN_LIMIT;
  bool bad;
  do {
    __nanosleep(250);
    uint32_t v[8], x = 0;
#pragma unroll
    for (int j = 0; j < 8; j++) v[j] = ld_relaxed(g_gate + j * SEQ + ti * 128 + tid) ^ tag;
    l = 0.f;
#pragma unroll
    for (int j = 0; j < 8; j++) { x |= v[j]; l += __uint_as_float(v[j]); }
    bad = __any_sync(~0u, x & 3);
  } while (bad && --n);
  trap_if(n == 0);
  const float g = bf_round(__fdividef(1.f, 1.f + __expf(-bf_round(l))));
  asm volatile("st.shared.f32 [%0], %1;" ::"r"(S_G + tid * 4), "f"(g) : "memory");
}

__device__ __forceinline__ void conv_tables(int tid) {
  {
    const int s = tid >> 5, n1 = tid & 31;
    uint32_t re[4], im[4];
#pragma unroll
    for (int e = 0; e < 4; e++) {
      cx a = unit(n1 * (4 * (8 * s + 2 * e) + 1), 128), b = unit(n1 * (4 * (8 * s + 2 * e + 1) + 1), 128);
      re[e] = pack2(a.r * 0.125f, b.r * 0.125f); im[e] = pack2(a.i * 0.125f, b.i * 0.125f);
    }
    sts128(S_M1 + (2 * s) * 512 + n1 * 16, re[0], re[1], re[2], re[3]);
    sts128(S_M1 + (2 * s + 1) * 512 + n1 * 16, im[0], im[1], im[2], im[3]);
  }
  {
    const int kg = tid >> 5, n = tid & 31;
    const int pi = kg >> 1, po = n >> 4, f2 = n & 15;
    uint32_t fw[4];
#pragma unroll
    for (int e = 0; e < 4; e++) {
      int n2 = (kg & 1) * 8 + 2 * e;
      cx a = unit(n2 * f2, 16), b = unit((n2 + 1) * f2, 16);
      float sg = pi ? -1.f : 1.f;
      float x0 = (pi == po) ? a.r : sg * a.i, x1 = (pi == po) ? b.r : sg * b.i;
      fw[e] = pack2(x0, x1);
    }
    sts128(S_M2 + kg * 512 + n * 16, fw[0], fw[1], fw[2], fw[3]);
  }
  fence_async_smem();
}
__device__ __forceinline__ constexpr int jj_of(int o) { return o == 7 ? 3 : o + (o >= 3); }
__device__ __forceinline__ int conv_chan(int ti, int pj, int jj) { return pj * 128 + jj * 16 + ti; }

struct ConvCtx {
  uint32_t buf, inbar;
  int nb, n;
  int ti, pj, j;
  __device__ __forceinline__ int chan(int c) const {
    return j < 0 ? conv_chan(ti, pj, jj_of(c)) : conv_chan(((j + 12 * c) >> 3) + (((j + 12 * c) >> 3) >= KEEP), (j + 12 * c) & 7, 3);
  }
};
__device__ __forceinline__ ConvCtx conv_ctx(int spare, int wg, int ti, int pj) {
  const int j = spare < 0 ? -1 : spare * 3 + wg;
  return {wg == 2 ? S_CIN : sb + wg * 32768, wg == 2 ? B_CINF : (wg ? B_PIN : B_FULL), 4 + 4 * wg, j < 0 ? 7 + (ti == KEEP) : (j < 8 && KEEP > 15 ? 11 : 10), ti, pj, j};
}
#define CDESC(a) mkdesc(dlo(a, 512), 128, 0)
struct ConvTw { uint32_t r[2], i[2], n[2]; };

__device__ __forceinline__ void cv_tw1(float (&d)[64], uint32_t (&R)[16], uint32_t (&I)[16], const ConvTw& t, int i) {
#pragma unroll
  for (int j = 8 * (i & 1); j < 8 * (i & 1) + 8; j++) {
    if (i < 2) {
      R[j] = pack2(d[4 * j], d[4 * j + 1]); I[j] = pack2(d[4 * j + 2], d[4 * j + 3]);
    } else {
      const uint32_t xr = R[j], xi = I[j];
      R[j] = hfma2(xr, t.r[j & 1], hmul2(xi, t.n[j & 1]));
      I[j] = hfma2(xr, t.i[j & 1], hmul2(xi, t.r[j & 1]));
    }
  }
}
template <int N>
__device__ __forceinline__ void cv_pack(float (&X)[16], uint32_t (&P)[N][2][2], int q) {
#pragma unroll
  for (int k = 0; k < 2; k++)
#pragma unroll
    for (int j = 0; j < 4; j++) P[2 * q + k][j >> 1][j & 1] = pack2(X[4 * j + 2 * k], X[4 * j + 2 * k + 1]);
}
__device__ __forceinline__ void cv_overlap(uint32_t (&P)[8][2][2]) {
#pragma unroll
  for (int k = 3; k > 0; k--)
#pragma unroll
    for (int hh = 0; hh < 2; hh++) {
      P[k][0][hh] = hsub2(P[k][0][hh], P[k - 1][1][hh]);
      P[k][1][hh] = hadd2(P[k][1][hh], P[k - 1][0][hh]);
    }
}
__device__ __forceinline__ void cv_pw(uint32_t (&P)[8][2][2], uint32_t (&Q)[4][2][2]) {
#pragma unroll
  for (int jh = 0; jh < 8; jh++) {
    const int j = jh >> 1, hh = jh & 1;
    uint32_t qr = hmul2(P[4 + j][0][hh], P[0][0][hh]), qi = hmul2(P[4 + j][0][hh], P[0][1][hh]);
    qr = hfma2(hneg2(P[4 + j][1][hh]), P[0][1][hh], qr);
    qi = hfma2(P[4 + j][1][hh], P[0][0][hh], qi);
#pragma unroll
    for (int k = j - 1; k >= 0; k--) {
      qr = hfma2(P[4 + k][0][hh], P[j - k][0][hh], qr);
      qi = hfma2(P[4 + k][0][hh], P[j - k][1][hh], qi);
      qr = hfma2(hneg2(P[4 + k][1][hh]), P[j - k][1][hh], qr);
      qi = hfma2(P[4 + k][1][hh], P[j - k][0][hh], qi);
    }
    Q[j][0][hh] = qr; Q[j][1][hh] = qi;
  }
}
__device__ __forceinline__ void cv_tw2(uint32_t (&Q)[4][2][2], const ConvTw& t, int k) {
#pragma unroll
  for (int hh = 0; hh < 2; hh++) {
    const uint32_t xr = Q[k][0][hh], xi = Q[k][1][hh];
    Q[k][0][hh] = hfma2(xr, t.r[hh], hmul2(xi, t.i[hh]));
    Q[k][1][hh] = hfma2(xr, t.n[hh], hmul2(xi, t.r[hh]));
  }
}
__device__ __forceinline__ void cv_out0(float (&Y)[16], uint32_t T, int w, int lane) {
  reg_fence(Y);
  const uint32_t za = T + w * 2048 + (lane >> 4) * 256 + (lane & 7) * 32 + (((lane >> 3) ^ (lane >> 2)) & 1) * 16;
#pragma unroll
  for (int jj = 0; jj < 2; jj++)
    stsm4t(za + jj * 512, pack2(Y[8 * jj], Y[8 * jj + 1]), pack2(Y[8 * jj + 2], Y[8 * jj + 3]),
           pack2(Y[8 * jj + 4], Y[8 * jj + 5]), pack2(Y[8 * jj + 6], Y[8 * jj + 7]));
}

__device__ __forceinline__ void cv_out1(const uint4& z0, const uint4& z1, const ConvCtx& cc, uint32_t keep, uint32_t tag, int ch, int w, int lane) {
  uint4* zp = g_z + (size_t)cc.chan(ch) * 256 + w * 64 + lane;
#define TG(v) ((v & keep) | (tag & ~keep))
  asm volatile("st.relaxed.gpu.global.v4.u32 [%0], {%1,%2,%3,%4};" ::"l"(zp), "r"(TG(z0.x)), "r"(TG(z0.y)), "r"(TG(z0.z)), "r"(TG(z0.w)) : "memory");
  asm volatile("st.relaxed.gpu.global.v4.u32 [%0], {%1,%2,%3,%4};" ::"l"(zp + 32), "r"(TG(z1.x)), "r"(TG(z1.y)), "r"(TG(z1.z)), "r"(TG(z1.w)) : "memory");
#undef TG
}
template <bool FW, bool BW, int K>
__device__ __forceinline__ void conv_step(uint32_t (&Q)[4][2][2], const ConvTw& t, const ConvCtx& cc, float dl, uint32_t tag, int ch, int w, int lane) {
#define SF(n) if ((SFM >> (n)) & 1) sched_fence_async<K + (n)>()
  float d[64], X[4][16], Z[2][16], Y[16];
  uint32_t R[16], I[16];
  uint4 a[4];
  const int nx = ch + 1;
  const uint32_t T = cc.buf + 16384;
  float dv;
  TIMC(1);
  if (FW) {
    dv = __shfl_sync(~0u, dl, nx);
    mbar_wait(cc.inbar + 8 * (nx & 1), (nx >> 1) & 1);
  }
  TIMC(2);
  WG_FENCE();
  if (BW) {
#pragma unroll
    for (int q = 0; q < 2; q++) {
      wgmma_rs32<0, 1>(Z[q], Q[2 * q][0][0], Q[2 * q + 1][0][0], Q[2 * q][0][1], Q[2 * q + 1][0][1], mkdesc(dlo(S_M2, 128), 512, 0));
      wgmma_rs32<1, 1>(Z[q], Q[2 * q][1][0], Q[2 * q + 1][1][0], Q[2 * q][1][1], Q[2 * q + 1][1][1], mkdesc(dlo(S_M2 + 256, 128), 512, 0));
    }
    WG_COMMIT();
  }
  if (FW) {
    const uint32_t lo = dlo(0, 1024) + (cc.buf >> 4) + (nx & 1) * 512;
    wgmma_ss128<1, 1, 0>(d, mkdesc(dlo(S_M1, 128), 512, 0), mkdesc(lo, 256, 3));
    wgmma_ss128<1, 1, 1>(d, mkdesc(dlo(S_M1 + 256, 128), 512, 0), mkdesc(lo + 32, 256, 3));
    WG_COMMIT();
  }
  TIMC(3);
  if (BW) {
    TIMC(4);
    WG_WAIT(FW ? 1 : 0);
    TIMC(5);
    reg_fence(Z[0]); reg_fence(Z[1]);
    uint32_t V[4][2][2];
    cv_pack(Z[0], V, 0); cv_pack(Z[1], V, 1);
    SF(0);
#pragma unroll
    for (int k = 0; k < 4; k++) cv_tw2(V, t, k);
    bar_sync(cc.nb, 128);
#pragma unroll
    for (int k = 0; k < 4; k++) stsm4(T + w * 512 + lane * 16 + k * 2048, V[k][0][0], V[k][0][1], V[k][1][0], V[k][1][1]);
    SF(1);
    TIMC(6);
  }
  if (FW) {
    WG_WAIT(0);
    reg_fence(d);
    if (nx + 2 < cc.n) bar_arrive(cc.nb + 2 + (nx & 1), 160);
    cv_tw1(d, R, I, t, 0); cv_tw1(d, R, I, t, 1);
    SF(2);
    TIMC(7);
  }
  if (BW) {
    bar_sync(cc.nb, 128);
#pragma unroll
    for (int s = 0; s < 4; s++) a[s] = ldsm4t(T + (4 * w + s) * 512 + lane * 16);
  }
  if (FW) { cv_tw1(d, R, I, t, 2); cv_tw1(d, R, I, t, 3); }
  sched_fence<K + 3>();
  TIMC(8);
  WG_FENCE();
  if (BW) {
    wgmma_rs32<0>(Y, a[0].x, a[0].y, a[0].z, a[0].w, CDESC(S_M1));
#pragma unroll
    for (int i = 1; i < 4; i++) wgmma_rs32<1>(Y, a[i].x, a[i].y, a[i].z, a[i].w, CDESC(S_M1 + 1024 * i));
  }
  if (FW) {
#pragma unroll
    for (int q = 0; q < 4; q++) {
      if (q == 2) WG_COMMIT();
      wgmma_rs32<0>(X[q], R[4 * q], R[4 * q + 2], R[4 * q + 1], R[4 * q + 3], CDESC(S_M2));
      wgmma_rs32<1>(X[q], I[4 * q], I[4 * q + 2], I[4 * q + 1], I[4 * q + 3], CDESC(S_M2 + 1024));
    }
  }
  WG_COMMIT();
  TIMC(9);
  WG_WAIT(FW ? 1 : 0);
  TIMC(10);
  uint4 z0, z1;
  const uint32_t zr = T + w * 2048 + (lane ^ ((lane >> 3) & 1)) * 16;
  if (BW) {
    cv_out0(Y, T, w, lane);
    __syncwarp();
  }
  if (FW) {
    uint32_t P[8][2][2];
    reg_fence(X[0]); reg_fence(X[1]);
    cv_pack(X[0], P, 0); cv_pack(X[1], P, 1);
    cv_overlap(P);
    if (BW) { z0 = lds128(zr); z1 = lds128(zr + 512); }
    sched_fence_async<K + 7>();
    WG_WAIT(0);
    reg_fence(X[2]); reg_fence(X[3]);
    X[2][0] += dv; X[2][1] += dv; X[2][4] += dv; X[2][5] += dv;
    cv_pack(X[2], P, 2); cv_pack(X[3], P, 3);
    SF(4);
    TIMC(11);
    cv_pw(P, Q);
    SF(8);
  } else {
    z0 = lds128(zr); z1 = lds128(zr + 512);
  }
  if (BW) cv_out1(z0, z1, cc, FW && cc.j < 0 && ch < 4 ? ~0u : ~1u, tag, ch, w, lane);
  sched_fence<K + 5>();
  TIMC(13);
#undef SF
}

__device__ __forceinline__ void conv_main(const Ptrs& p, const ConvCtx& cc, int eb, int tid) {
  const int ti = cc.ti, pj = cc.pj;
  const int w = tid >> 5, lane = tid & 31;
  const unsigned ep = ld_relaxed(g_epoch + eb);
  const __nv_bfloat16 dsk = p.ssmd[cc.chan(min(lane, cc.n - 1))];
  if (cc.nb == 12) conv_tables(tid);
  if (cc.j < 0) bar_sync(12, 160); else bar_sync(0, 512);
  ConvTw t;
#pragma unroll
  for (int hh = 0; hh < 2; hh++) {
    const int n2 = 8 * hh + 2 * (lane & 3), m = 4 * (8 * w + (lane >> 2)) + 1;
    cx a = unit(n2 * m, 2048), b = unit((n2 + 1) * m, 2048);
    t.r[hh] = pack2(a.r, b.r); t.i[hh] = pack2(a.i, b.i); t.n[hh] = pack2(-a.i, -b.i);
  }
  const uint32_t tag = (ep + 1) & 3;
  const float dl = 0.125f * __bfloat162float(dsk);
  if (cc.j < 0) prep<1>(p, ti, pj, w, lane);
  {
    uint32_t P[4][2][2];
    mbar_wait_long(cc.inbar, 0);
    TIM(20);
    conv_step<true, false, 10>(P, t, cc, dl, tag, -1, w, lane);
#pragma unroll 1
    for (int ch = 0; ch < cc.n - 1; ch++) {
      conv_step<true, true, 20>(P, t, cc, dl, tag, ch, w, lane);
      if (cc.j < 0 && ch == 3) bar_arrive(0, 160);
      if (ch == 0) TIM(21);
    }
    conv_step<false, true, 30>(P, t, cc, dl, tag, cc.n - 1, w, lane);
  }
  TIM(22);
}

__device__ __forceinline__ cx csel(bool k, cx a, cx b) { return {k ? a.r : b.r, k ? a.i : b.i}; }
__device__ __forceinline__ void ld2cx(uint32_t a, cx& x, cx& y) {
  const uint4 v = lds128(a);
  x = {__uint_as_float(v.x), __uint_as_float(v.y)};
  y = {__uint_as_float(v.z), __uint_as_float(v.w)};
}
__device__ __forceinline__ cx ldcx(uint32_t a) {
  cx x;
  asm volatile("ld.shared.v2.f32 {%0,%1}, [%2];" : "=f"(x.r), "=f"(x.i) : "r"(a) : "memory");
  return x;
}

__device__ __forceinline__ void scan_epilogue(float (&aR)[64], float (&aI)[64], uint32_t last_empty, int ph, int ti, int pj, int tid) {
  const int w = tid >> 5, lane = tid & 31, r = lane >> 2, c = lane & 3;
  const uint32_t par = S_PAR + (ph * 64 + 16 * w + r) * 16;
  uint4* agg = g_agg + ph * 16 * 256 + pj * 32 + 8 * w + r;
  const uint32_t tag = (lds32(S_EP) + 1) & 3;
  cx h[2];
  {
    cx lam[2], a[2];
#pragma unroll
    for (int q = 0; q < 2; q++) { lam[q] = ldcx(par + q * 128); h[q] = ldcx(par + 2048 + q * 128); }
    WG_WAIT(0);
    if (elect_one()) mbar_arrive(last_empty);
    asm volatile("setmaxnreg.inc.sync.aligned.u32 168;");
    reg_fence(aR); reg_fence(aI);
    TIM(3 + ph * 2);
#pragma unroll
    for (int q = 0; q < 2; q++) a[q] = {aR[2 * q], aI[2 * q]};
#pragma unroll
    for (int s = 1; s < 32; s++)
#pragma unroll
      for (int q = 0; q < 2; q++) {
        const int i = 4 * (s >> 1) + 2 * q + (s & 1);
        a[q] = cfma(lam[q], a[q], {aR[i], aI[i]});
      }
    sched_fence<1>();
    cx t[2][3];
#pragma unroll
    for (int q = 0; q < 2; q++)
#pragma unroll
      for (int k = 0; k < 3; k++) t[q][k] = {__shfl_up_sync(~0u, a[q].r, k + 1, 4), __shfl_up_sync(~0u, a[q].i, k + 1, 4)};
#pragma unroll
    for (int q = 0; q < 2; q++) {
      const cx z = {0.f, 0.f};
      cx ex = cfma(h[q], csel(c >= 3, t[q][2], z), csel(c >= 2, t[q][1], z));
      ex = cfma(h[q], ex, csel(c >= 1, t[q][0], z));
      a[q] = cfma(h[q], ex, a[q]);
      const cx u = cfma(lam[q], ex, {aR[2 * q], aI[2 * q]});
      aR[2 * q] = u.r; aI[2 * q] = u.i;
    }
    if (c == 3)
      asm volatile("st.relaxed.gpu.global.v4.u32 [%0], {%1,%2,%3,%4};" ::"l"(agg + ti * 256),
                   "r"((__float_as_uint(a[0].r) & ~3u) | tag), "r"((__float_as_uint(a[0].i) & ~3u) | tag),
                   "r"((__float_as_uint(a[1].r) & ~3u) | tag), "r"((__float_as_uint(a[1].i) & ~3u) | tag) : "memory");
    TIM(8 + ph * 4);
  }
  if (ti > 0) {
    const uint2* ap = (const uint2*)(agg + (ti - 1 - (c >> 1)) * 256) + (c & 1);
    const int cnt = ti - (c >> 1);
    const cx one = {1.f, 0.f};
    const cx l128 = ldcx(par + 2048 + 8 + (c & 1) * 128), l256 = csq(l128), fa = csel(c & 2, l128, one);
#pragma unroll
    for (int q = 0; q < 2; q++) h[q] = cmul(csel(c & 1, h[q], one), csel(c & 2, csq(h[q]), one));
    uint2 v[8];
    int n = SPIN_LIMIT;
    bool bad;
    __nanosleep(AGG_NS);
    do {
      uint32_t x = 0;
#pragma unroll
      for (int j = 0; j < 8; j++) {
        v[j] = make_uint2(tag, tag);
        asm volatile("{.reg .pred p; setp.lt.s32 p, %3, %4; @p ld.relaxed.gpu.global.v2.u32 {%0,%1}, [%2];}"
                     : "+r"(v[j].x), "+r"(v[j].y) : "l"(ap - j * 1024), "r"(2 * j), "r"(cnt) : "memory");
      }
#pragma unroll
      for (int j = 0; j < 8; j++) { v[j].x ^= tag; v[j].y ^= tag; x |= v[j].x | v[j].y; }
      bad = __any_sync(~0u, x & 3);
    } while (bad && --n);
    trap_if(n == 0);
    cx a = {__uint_as_float(v[7].x), __uint_as_float(v[7].y)};
#pragma unroll
    for (int j = 6; j >= 0; j--) a = cfma(l256, a, {__uint_as_float(v[j].x), __uint_as_float(v[j].y)});
    a = cmul(a, fa);
    const cx t1 = {__shfl_xor_sync(~0u, a.r, 1), __shfl_xor_sync(~0u, a.i, 1)};
    const cx t2 = {__shfl_xor_sync(~0u, a.r, 2), __shfl_xor_sync(~0u, a.i, 2)};
    const cx t3 = {__shfl_xor_sync(~0u, a.r, 3), __shfl_xor_sync(~0u, a.i, 3)};
    const cx own = {a.r + t2.r, a.i + t2.i}, oth = {t1.r + t3.r, t1.i + t3.i};
#pragma unroll
    for (int q = 0; q < 2; q++) h[q] = cmul(csel((c & 1) == q, own, oth), h[q]);
  } else {
    h[0] = h[1] = {0.f, 0.f};
  }
  TIM(9 + ph * 4);
  cx lam[2];
  uint32_t cr[2], nci[2];
#pragma unroll
  for (int q = 0; q < 2; q++) {
    const uint4 v = lds128(par + q * 128);
    lam[q] = {__uint_as_float(v.x), __uint_as_float(v.y)};
    cr[q] = v.z; nci[q] = v.w;
  }
  uint4* hg = g_h + (size_t)(ti * 32 + ph * 16 + pj) * 1024 + w * 64 + r * 4 + (c ^ (r >> 1));
  const uint32_t hs = S_STG + w * 1024 + r * 64 + ((c ^ (r >> 1)) << 4);
  if (RE_EARLY) mbar_wait(B_SFREE + 16 * ph, 0);
  uint32_t pr[4][2][4], pi[4][2][4], re[4][2][4];
#pragma unroll
  for (int i = 0; i < 4; i++) {
#pragma unroll
    for (int s2 = 0; s2 < 4; s2++)
#pragma unroll
      for (int q = 0; q < 2; q++) {
        const int k = 4 * (4 * i + s2) + 2 * q;
        cx h0 = cfma(lam[q], h[q], {aR[k], aI[k]});
        h[q] = cfma(lam[q], h0, {aR[k + 1], aI[k + 1]});
        pr[i][q][s2] = pack2(h0.r, h[q].r);
        pi[i][q][s2] = pack2(h0.i, h[q].i);
        re[i][q][s2] = hfma2(pr[i][q][s2], cr[q], hmul2(pi[i][q][s2], nci[q]));
      }
#pragma unroll
    for (int q = 0; q < 2; q++) {
      stg128(hg + i * 256 + q * 32, re[i][q][0], re[i][q][1], re[i][q][2], re[i][q][3]);
      if (i < RE_EARLY) sts128(hs + i * 4096 + q * 512, re[i][q][0], re[i][q][1], re[i][q][2], re[i][q][3]);
    }
    if (i == 0 && (P2F & 1)) sched_fence<7>();
    if (i == 1 && (P2F & 2)) sched_fence<8>();
    if (i == 2 && (P2F & 1)) sched_fence<6>();
  }
  bar_arrive(9, 160);
  sched_fence<9>();
  TIM(10 + ph * 4);
  if (!RE_EARLY) mbar_wait(B_SFREE + 16 * ph, 0);
  if (ph == 0) mbar_wait(B_SFREE + 8, 0);
#pragma unroll
  for (int q = 0; q < 2; q++) {
    const uint32_t ncr = cr[q] ^ 0x80008000u;
#pragma unroll
    for (int i = 0; i < 4; i++) {
      uint32_t o[4];
#pragma unroll
      for (int s2 = 0; s2 < 4; s2++) o[s2] = hfma2(pi[i][q][s2], ncr, hmul2(pr[i][q][s2], nci[q]));
      if (i >= RE_EARLY) sts128(hs + i * 4096 + q * 512, re[i][q][0], re[i][q][1], re[i][q][2], re[i][q][3]);
      sts128(hs + 16384 + i * 4096 + q * 512, o[0], o[1], o[2], o[3]);
      if (IM_NS) __nanosleep(IM_NS);
      stg128(hg + 8192 + i * 256 + q * 32, o[0], o[1], o[2], o[3]);
    }
  }
  fence_async_smem();
  __syncwarp();
  if (elect_one()) mbar_arrive(B_LOC + 8 * ph);
  bar_arrive(10, 160);
  bar_sync(1 + ph, 128);
  asm volatile("setmaxnreg.dec.sync.aligned.u32 160;");
}

__device__ __forceinline__ constexpr uint32_t e_addr(int o, int mh) { return S_STG + (o * 2 + mh) * 2048; }
__device__ __forceinline__ void eterm(const Ptrs& p, int ti, int pj, int tid) {
  const int w = tid >> 5, lane = tid & 31, r = lane >> 2, c = lane & 3;
  const int trow = 64 * (w & 1) + 8 * (w >> 1) + r;
  const int rs = 2 * (r & 3) + (r >> 2);
  uint2 xv[2][8][2], ds[8];
  {
    uint2 gw[8];
#pragma unroll
    for (int jj = 0; jj < 8; jj++) {
      gw[jj] = ldg64(p.gw + pj * 128 + 16 * jj + 4 * c);
      ds[jj] = ldg64(p.dskip + pj * 128 + 16 * jj + 4 * c);
    }
#pragma unroll
    for (int g = 0; g < 2; g++) {
      mbar_wait(B_XT + 8 * g, 0);
#pragma unroll
      for (int i = 0; i < 4; i++)
#pragma unroll
        for (int jj = 4 * g; jj < 4 * g + 4; jj++)
          xv[i >> 1][jj][i & 1] = lds64(sb + ((48 + g) % NS) * STAGE + (trow - r + rs + 16 * (i >> 1) + 32 * (i & 1)) * 128 + (((2 * (jj & 3) + (c >> 1)) ^ rs) << 4) + (c & 1) * 8);
      fence_async_smem();
      __syncwarp();
      if (elect_one()) mbar_arrive(B_XT + 16 + 8 * g);
    }
    sched_fence<55>();
    TIM(27);
    float s[4];
#pragma unroll
    for (int i = 0; i < 4; i++) {
      s[i] = 0.f;
#pragma unroll
      for (int jj = 0; jj < 8; jj += 2) {
        const uint2 x = xv[i >> 1][jj][i & 1], y = xv[i >> 1][jj + 1][i & 1];
        const uint32_t q = hfma2(x.x, gw[jj].x, hfma2(x.y, gw[jj].y, hfma2(y.x, gw[jj + 1].x, hmul2(y.y, gw[jj + 1].y))));
        s[i] += bf_lo(q) + bf_hi(q);
      }
    }
    float u0 = (c & 1) ? s[1] : s[0], v0 = (c & 1) ? s[0] : s[1];
    float u1 = (c & 1) ? s[3] : s[2], v1 = (c & 1) ? s[2] : s[3];
    u0 += __shfl_xor_sync(~0u, v0, 1);
    u1 += __shfl_xor_sync(~0u, v1, 1);
    float u = (c & 2) ? u1 : u0;
    u += __shfl_xor_sync(~0u, (c & 2) ? u0 : u1, 2);
    const uint32_t tag = (lds32(S_EP) + 1) & 3;
    asm volatile("st.relaxed.gpu.global.u32 [%0], %1;" ::"l"(g_gate + pj * SEQ + ti * 128 + trow + 16 * (c >> 1) + 32 * (c & 1)),
                 "r"((__float_as_uint(u) & ~3u) | tag) : "memory");
    gate_finish(ti, tid, tag);
  }
  bar_sync(2, 128);
  TIM(31);
  uint32_t g2[2][2], og2[2][2];
#pragma unroll
  for (int mh = 0; mh < 2; mh++)
#pragma unroll
    for (int hf = 0; hf < 2; hf++) {
      uint32_t g;
      asm volatile("ld.shared.u32 %0, [%1];" : "=r"(g) : "r"(S_G + (trow + 16 * mh + 32 * hf) * 4) : "memory");
      g2[mh][hf] = __byte_perm(g, g, 0x3232);
      og2[mh][hf] = hsub2(0x3f803f80u, g2[mh][hf]);
    }
  const int dl = lane & 15;
  const uint32_t za = S_STG + (w & 1) * 2048 + dl * 128;
  const uint32_t tag = (lds32(S_EP) + 1) & 1;
  const int zn = tid >> 4, ck = tid & 15;
  const uint4* zp = g_z + (size_t)(pj * 128 + 4 * (zn >> 1) + (zn & 1)) * 256 + ti * 16 + ck;
  uint4 v[4];
#define ZLOAD(o0) _Pragma("unroll") for (int i = 0; i < 4; i++) \
    asm volatile("ld.relaxed.gpu.global.v4.u32 {%0,%1,%2,%3}, [%4];" : "=r"(v[i].x), "=r"(v[i].y), "=r"(v[i].z), "=r"(v[i].w) \
                 : "l"(zp + (jj_of(o0 + (i >> 1)) * 16 + 2 * (i & 1)) * 256) : "memory")
#pragma unroll
  for (int g = 0; g < 3; g++) {
    const int o0 = g ? 2 + 2 * g : 0, o1 = 4 + 2 * g;
    if (g == 0) {
      mbar_wait_long(B_ZT, 0);
    } else {
      int it = SPIN_LIMIT;
      while (true) {
        uint32_t x = 0;
#pragma unroll
        for (int i = 0; i < 4; i++) {
          v[i].x ^= tag; v[i].y ^= tag; v[i].z ^= tag; v[i].w ^= tag;
          x |= v[i].x | v[i].y | v[i].z | v[i].w;
        }
        if (!__any_sync(~0u, x & 1) || !--it) break;
        __nanosleep(ZL_NS);
        ZLOAD(o0);
      }
      trap_if(it == 0);
#pragma unroll
      for (int i = 0; i < 4; i++)
        sts128(S_STG + (o0 + (i >> 1)) * 4096 + (ck >> 3) * 2048 + (8 * (i & 1) + zn) * 128 + (((ck & 7) ^ zn) << 4), v[i].x, v[i].y, v[i].z, v[i].w);
      bar_sync(2, 128);
    }
    if (g < 2) { ZLOAD(o1); }
    if (g == 2) TIM(16);
#pragma unroll
    for (int mh = 0; mh < 2; mh++) {
      const uint32_t zb = za + (((4 * (lane >> 4) + 2 * mh + (w >> 1)) ^ (dl & 7)) << 4);
#pragma unroll
      for (int o = o0; o < o1; o++) {
        const int jj = jj_of(o);
        uint4 z = ldsm4t(zb + o * 4096);
#pragma unroll
        for (int hf = 0; hf < 2; hf++) {
          uint2& x = xv[mh][jj][hf];
          x.x = hmul2(x.x, hfma2(og2[mh][hf], hf ? z.z : z.x, hmul2(g2[mh][hf], ds[jj].x)));
          x.y = hmul2(x.y, hfma2(og2[mh][hf], hf ? z.w : z.y, hmul2(g2[mh][hf], ds[jj].y)));
        }
      }
    }
    bar_sync(2, 128);
#pragma unroll
    for (int o = o0; o < o1; o++)
#pragma unroll
      for (int mh = 0; mh < 2; mh++) {
        const int jj = jj_of(o);
        sts128(e_addr(o, mh) + tid * 16, xv[mh][jj][0].x, xv[mh][jj][0].y, xv[mh][jj][1].x, xv[mh][jj][1].y);
      }
    bar_arrive(5 + g, 256);
    if (g == 0) TIM(1);
    if (g == 1) TIM(23);
  }
#undef ZLOAD
  TIM(17);
}

__device__ __forceinline__ void store_piece(float (&a)[64], float* op, int jj, const uint4& e, float g0, float g1) {
  stg128(op + 16 * jj, __float_as_uint(fmaf(g0, a[8 * jj], bf_lo(e.x))), __float_as_uint(fmaf(g0, a[8 * jj + 1], bf_hi(e.x))),
         __float_as_uint(fmaf(g0, a[8 * jj + 4], bf_lo(e.y))), __float_as_uint(fmaf(g0, a[8 * jj + 5], bf_hi(e.y))));
  stg128(op + 32 * DM + 16 * jj, __float_as_uint(fmaf(g1, a[8 * jj + 2], bf_lo(e.z))), __float_as_uint(fmaf(g1, a[8 * jj + 3], bf_hi(e.z))),
         __float_as_uint(fmaf(g1, a[8 * jj + 6], bf_lo(e.w))), __float_as_uint(fmaf(g1, a[8 * jj + 7], bf_hi(e.w))));
}

__device__ __forceinline__ void issue_g1(const Maps& m, int s, int sl, int ti, int pj) {
  const uint32_t bar = B_FULL + 8 * sl, dst = sb + sl * STAGE;
  const int k0 = (s & 15) * 64, ch = (s >> 4) * 512 + pj * 64;
  mbar_expect(bar, STAGE);
  tma4d(dst + 16384, &m.x, bar, k0, 0, 4 * ti, 0);
  tma2d(dst, &m.bre, bar, k0, ch);
  tma2d(dst + 8192, &m.bim, bar, k0, ch);
}
__device__ __forceinline__ void producer(const Maps& m, int ti, int pj) {
#pragma unroll
  for (int s = EARLY; s < NS; s++) issue_g1(m, s, s, ti, pj);
  int sl = 0, par = 0;
#pragma unroll 1
  for (int s = NS; s < 32; s++) {
    mbar_wait(B_EMPTY + 8 * sl, par);
    issue_g1(m, s, sl, ti, pj);
    if (++sl == NS) { sl = 0; par ^= 1; }
  }
#pragma unroll 1
  for (int q = 0; q < 32; q++) {
    mbar_wait(B_EMPTY + 8 * sl, par);
    const uint32_t bar = B_FULL + 8 * sl, dst = sb + sl * STAGE;
    const int ph = q >> 4, u = q & 15, part = u < 2 ? u : u >= 9, i = u - 2 - 7 * part;
    const int src = u < 2 ? pj : (MAP == 1 || MAP == 2) ? i + (i >= pj) : (i < 4 ? (~pj & 4) + i : (pj & 4) + i - 4 + (i - 4 >= (pj & 3)));
    if (q == 16 + NS || q == 17 + NS) mbar_wait(B_XT + 8 * (q - 14 - NS), 0);
    mbar_expect(bar, u < 2 ? 16384 : STAGE);
    tma5d(dst + 16384, part ? &m.cim : &m.cre, bar, ph * 512 + src * 64, 0, 0, 0, pj * 8);
    if (u < 2) {
      if (ph) {
        mbar_expect(B_XT + 8 * u, 16384);
        tma4d(dst, &m.x2, B_XT + 8 * u, pj * 128 + u * 64, 0, 0, ti * 16);
      }
    } else {
      if (i == 0) {
        mbar_wait(B_FLG + 8 * (2 * ph + part), 0);
        fence_async_global();
        if (part == 0 && ph == 0) TIM(24);
      }
      bulk_load(dst, g_h + (size_t)(ti * 32 + ph * 16 + part * 8 + src) * 1024, 16384, bar);
    }
    if (++sl == NS) { sl = 0; par ^= 1; }
  }
}

__device__ __forceinline__ void poller(int ti, int pj, int lane, unsigned ep) {
  if (lane < 5) {
    const int f = lane < 4 ? F_H + lane * 16 + ti : F_Z + pj;
    const unsigned need = (ep + 1) * (lane < 4 ? 8 : 16);
    int n = SPIN_LIMIT;
    bool done = false;
    do {
      if (!done && (int)(ld_relaxed(g_flag + f * 32) - need) >= 0) {
        done = true;
        asm volatile("fence.acquire.gpu;" ::: "memory");
        mbar_arrive(B_FLG + 8 * lane);
      }
      if (POLL_NS) __nanosleep(POLL_NS);
    } while (!__all_sync(0x1fu, done) && --n);
    trap_if(n == 0);
  }
}
__device__ __forceinline__ void storer(const Maps& m, int ti, int pj) {
#pragma unroll 1
  for (int job = 0; job < 6; job++) {
    bar_sync(job < 2 ? 4 + job : 9 + (job & 1), 160);
    if (elect_one()) flag_release(job < 2 ? F_U + pj * 2 + job : F_H + (job - 2) * 16 + ti);
    __syncwarp();
    if (job == 2 || job == 4) TIM(7 + job * 2);
  }
  if (elect_one()) {
    mbar_wait_long(B_LOC + 16, 0);
    mbar_wait_long(B_FLG + 32, 0);
    fence_async_global();
    mbar_expect(B_ZT, 16384);
#pragma unroll 1
    for (int o = 0; o < 4; o++) {
      tma5d(S_STG + o * 4096, &m.z, B_ZT, ti * 128, 0, 0, 0, pj * 8 + jj_of(o));
      tma5d(S_STG + o * 4096 + 2048, &m.z, B_ZT, ti * 128 + 64, 0, 0, 0, pj * 8 + jj_of(o));
    }
  }
}

__device__ __forceinline__ void kv_loader(const Maps& m, int ti, int pj, unsigned t_start) {
  unsigned tt = t_start + KV0_AT;
#pragma unroll 1
  for (int st = 0; st < 4; st++) {
    const int d = pj * 128 + (st >> 1) * 64, tb = ti * 16 + (st & 1) * 8;
    const uint32_t bar = B_PIN + 8 * st;
    if (st >= 2) { bar_sync(st == 2 ? 3 : 11, 160); fence_async_smem(); }
    if (elect_one()) {
      mbar_expect(bar, 16384 + 384);
      if (st == 2) tt = t_start + KV1_AT;
      if ((int)(clock() - tt) > 0) tt = clock();
#pragma unroll 1
      for (int i = 0; i < 4; i++) {
        wait_clock(tt);
        tt += st >= 2 ? KV_GAP1 : KV_GAP0;
        tma3d(S_STG + (st & 1) * 16384 + i * 4096, (i & 2) ? &m.v : &m.k, bar, d, tb, (i & 1) * 4);
        if (i == 0) tma3d(S_T + st * 512, &m.kh, bar, d, tb - 1, 5);
      }
    }
    tt = __shfl_sync(~0u, tt, 0);
  }
}

__device__ __forceinline__ void conv_loader(const Maps& m, const Ptrs& p, const ConvCtx& cc, int eb, int lane, unsigned t_start) {
  const unsigned ep = ld_relaxed(g_epoch + eb);
  wait_clock(t_start + SPF_AT);
#pragma unroll 1
  for (int ch = 0; ch < cc.n; ch++) {
    const int d = cc.chan(ch);
    const uint32_t bar = cc.inbar + 8 * (ch & 1), dst = cc.buf + (ch & 1) * 8192;
    const bool first = ch == 0 || ch == (cc.j < 0 ? 3 : 1);
    if (ch >= 2) bar_sync(cc.nb + 2 + (ch & 1), 160);
    if (elect_one()) {
      mbar_expect(cc.inbar + 16, 4096);
      bulk_load(dst + 4096, p.f + (size_t)d * SEQ, 4096, cc.inbar + 16);
      if (!first) { mbar_expect(bar, 4096); tma3d(dst, &m.u, bar, 0, d & 31, d & ~31); }
      if (ch + 1 < cc.n) l2_prefetch(p.f + (size_t)cc.chan(ch + 1) * SEQ, 4096);
    }
    __syncwarp();
    const uint32_t a = dst + 4096 + 128 + (lane >> 3) * 256 + (lane & 7) * 16;
    mbar_wait(cc.inbar + 16, ch & 1);
#pragma unroll 1
    for (uint32_t i = a; i < a + 4096; i += 2048) {
      const uint4 x = lds128(i), y = lds128(i + 1024);
      __syncwarp();
      sts128(i ^ 16, x.x, x.y, x.z, x.w);
      sts128((i ^ 16) + 1024, y.x, y.y, y.z, y.w);
    }
    fence_async_smem();
    __syncwarp();
    if (elect_one()) {
      mbar_arrive(bar);
      if (first) {
        int n = SPIN_LIMIT;
        while ((int)(ld_relaxed(g_flag + (F_U + (d >> 6)) * 32) - (ep + 1) * 16) < 0 && --n) __nanosleep(POLL_NS);
        trap_if(n == 0);
        asm volatile("fence.acquire.gpu;" ::: "memory");
        fence_async_global();
        mbar_expect(bar, 4096);
        tma3d(dst, &m.u, bar, 0, d & 31, d & ~31);
      }
    }
    __syncwarp();
    if (cc.j < 0 && ch == 6) {
      bar_sync(0, 160);
      if (elect_one()) flag_release(F_Z + cc.pj);
      __syncwarp();
    }
  }
  if (cc.j >= 0 && lane == 0) g_epoch[eb] = ep + 1;
}

struct Ring { uint32_t off, par, rel; };
__device__ __forceinline__ void desc_touch(const uint64_t (&c)[12][NS]) {
  uint32_t x = 0;
#pragma unroll
  for (int i = 0; i < 12 * NS; i += 4) x |= (uint32_t)(&c[0][0])[i];
  trap_if((x | (uint32_t)c[11][NS - 1]) == 0);
}
template <int TA, bool TAB, bool LOC = false>
__device__ __forceinline__ void gemm_steps(float (&a0)[64], float (&a1)[64], Ring& r, int n, const uint64_t (&c)[12][NS], int slot) {
#pragma unroll 1
  do {
    const uint32_t off = r.off, rel = r.rel;
    full_wait(B_FULL + off, r.par, slot++);
    r.rel = off;
    r.off += 8;
    if (r.off == 8 * NS) { r.off = 0; r.par ^= 1; }
    WG_FENCE();
#define DESC(i) (*(const uint64_t*)((const char*)c[i] + off))
#pragma unroll
    for (int k = 0; k < 4; k++) {
      const uint64_t db = TAB ? DESC(3 * k) : mkdesc(off * 256 + dlo(sb + 16384 + 32 * k, 16), 1024, 1);
      if (LOC) {
        const int acc = k || rel != B_DUMMY - B_EMPTY;
        wgmma_ss128p<TA>(a0, mkdesc(dlo(S_STG + 32768 + 1024 * k, 4096) - n * 1024, 512, 2), db, acc);
        wgmma_ss128p<TA>(a1, mkdesc(dlo(S_STG + 32768 + 8192 + 1024 * k, 4096) - n * 1024, 512, 2), db, acc);
      } else {
        wgmma_ss128<TA, 0, 1>(a0, TAB ? DESC(3 * k + 1) : mkdesc(off * 256 + dlo(sb + 32 * k, 16), 1024, 1), db);
        wgmma_ss128<TA, 0, 1>(a1, TAB ? DESC(3 * k + 2) : mkdesc(off * 256 + dlo(sb + 8192 + 32 * k, 16), 1024, 1), db);
      }
      if (k == RELK) {
        WG_COMMIT();
        WG_WAIT(1);
        if (elect_one()) mbar_arrive(B_EMPTY + rel);
      }
    }
#undef DESC
    if (RELK < 3) WG_COMMIT();
  } while (--n);
}

template <int I>
__device__ __forceinline__ void tail_steps(float (&a0)[64], float (&a1)[64], const Ptrs& p, float* op, const float (&g)[4], uint4& e, uint4& e0, int tid) {
  constexpr int sl = (64 - WIN + I / 2) % NS, k = 2 * (I & 1), J = I - TOFF;
  if (I == 0) WG_FENCE();
  wgmma_ss128<1, 0, 1>(a1, p.dc2[3 * k + 2][sl], p.dc2[3 * k][sl]);
  wgmma_ss128<1, 0, 1>(a1, p.dc2[3 * k + 5][sl], p.dc2[3 * k + 3][sl]);
  WG_COMMIT();
  if (J == 0) { WG_WAIT(TOFF + 1); reg_fence(a0); }
  if (J >= 0 && J < 2 * NPB) {
    sched_fence_async<70 + 2 * I>();
    constexpr int o = J >= 0 ? J / 2 : 0, jj = jj_of(o), hf = J & 1;
    if (hf == 0) { e0 = e; e = lds128(e_addr(o + 1 < NPB ? o + 1 : 0, o + 1 == NPB) + tid * 16); }
    const uint32_t ex = hf ? e0.z : e0.x, ey = hf ? e0.w : e0.y;
    stg128(op + hf * 32 * DM + 16 * jj, __float_as_uint(fmaf(g[hf], a0[8 * jj + 2 * hf], bf_lo(ex))), __float_as_uint(fmaf(g[hf], a0[8 * jj + 2 * hf + 1], bf_hi(ex))),
           __float_as_uint(fmaf(g[hf], a0[8 * jj + 2 * hf + 4], bf_lo(ey))), __float_as_uint(fmaf(g[hf], a0[8 * jj + 2 * hf + 5], bf_hi(ey))));
    sched_fence_async<71 + 2 * I>();
  }
  if constexpr (I + 1 < 2 * WIN) tail_steps<I + 1>(a0, a1, p, op, g, e, e0, tid);
}

__global__ void __launch_bounds__(512, 1) fused_kernel(const __grid_constant__ Maps m, const __grid_constant__ Ptrs p) {
  extern __shared__ __align__(1024) uint8_t smem_raw[];
  int b = blockIdx.x;
  {
    int sm, nsm;
    asm volatile("mov.u32 %0, %%smid;" : "=r"(sm));
    asm volatile("mov.u32 %0, %%nsmid;" : "=r"(nsm));
    const int tp = sm >> 1, q = ((tp - 32) * 37) >> 8;
    const int g = tp < 32 ? tp & 7 : (tp < 60 ? tp - 31 - 7 * q : (tp < 62 ? 8 : 0));
    const int j = tp < 32 ? tp >> 3 : (tp < 60 ? 4 + q : (tp < 62 ? tp - 60 : tp - 58));
    if (nsm == 132) b = g * 16 + j * 2 + (sm & 1);
    b = __shfl_sync(~0u, b, 0);
  }
  const int spare = b - 128;
  const int ti = ((b >> 5) << 2) | (b & 3), pj = (((b >> 4) & 1) << 2) | ((b >> 2) & 3);
  const int wid = __shfl_sync(~0u, threadIdx.x >> 5, 0), wg = wid >> 2, tid = threadIdx.x & 127, lane = threadIdx.x & 31;
  if (wg == 0) TIM(0);
  const unsigned t_start = clock();
  if (wid == 12) {
    if (elect_one()) {
      asm volatile("prefetch.tensormap [%0];" ::"l"(&m.x) : "memory");
      asm volatile("prefetch.tensormap [%0];" ::"l"(&m.bre) : "memory");
      asm volatile("prefetch.tensormap [%0];" ::"l"(&m.bim) : "memory");
#pragma unroll
      for (int i = 0; i < NS; i++) mbar_init(B_FULL + 8 * i, (i < 2 && spare >= 0) ? 2 : 1);
      fence_async_smem();
#pragma unroll
      for (int s = 0; s < EARLY; s++) if (spare < 0) issue_g1(m, s, s, ti, pj);
    }
  } else if (wid == 13) {
    if (elect_one()) {
      trap_if((uint32_t)__cvta_generic_to_shared(smem_raw) != sb);
#pragma unroll
      for (uint32_t bar = B_EMPTY; bar < S_EP; bar += 8) mbar_init(bar, (bar < B_CINF || (bar >= B_SFREE && bar < B_ZT) || bar == B_XT + 16 || bar == B_XT + 24) ? 4 :
                           (bar < B_CINF + 16 || ((bar == B_PIN || bar == B_PIN + 8) && spare >= 0)) ? 2 : 1);
      fence_async_smem();
    }
  }
  __syncwarp();
  if (wg == 3) {
    asm volatile("setmaxnreg.dec.sync.aligned.u32 %0;" ::"n"(RV == 2 ? 32 : 24));
    bar_sync(1, 128);
    if (spare < 0) {
      if (wid == 13) { bar_arrive(2, 160); bar_arrive(12, 160); }
      bar_arrive(0, 256);
    } else {
      bar_arrive(0, 512);
    }
    if (wid == 13) {
      if (spare < 0) {
        const unsigned ep = ld_relaxed(g_epoch + b);
        kv_loader(m, ti, pj, t_start);
        poller(ti, pj, lane, ep);
      }
    } else if (wid == 15 || spare >= 0) {
      const ConvCtx cc = conv_ctx(spare, wid == 12 ? 0 : wid - 13, ti, pj);
      conv_loader(m, p, cc, spare < 0 ? b : 128 + cc.j, lane, t_start);
    } else if (wid == 12) {
      if (elect_one()) producer(m, ti, pj);
    } else {
      storer(m, ti, pj);
    }
  } else if (wg == 2 || spare >= 0) {
    asm volatile("setmaxnreg.inc.sync.aligned.u32 160;");
    conv_main(p, conv_ctx(spare, wg, ti, pj), spare < 0 ? b : 128 + spare * 3 + wg, tid);
  } else {
    asm volatile("setmaxnreg.inc.sync.aligned.u32 %0;" ::"n"(RV == 3 ? 168 : 160));
    if (wg == 1) {
      const int ch = (tid >> 6) * 512 + pj * 64 + (tid & 63);
      const unsigned ep = ld_relaxed(g_epoch + b);
      const float lr = __bfloat162float(p.lre[ch]), li = __bfloat162float(p.lim[ch]);
      const float dt = bf_round(expf(__bfloat162float(p.ldt[ch])));
      float sn, cs;
      sincosf(dt * li, &sn, &cs);
      const float ex = expf(dt * lr);
      const float ar = ex * cs, ai = ex * sn;
      const float inv = 2.f / (lr * lr + li * li);
      const float cr = ((ar - 1.f) * lr + ai * li) * inv, ci = (ai * lr - (ar - 1.f) * li) * inv;
      sts128(S_PAR + tid * 16, __float_as_uint(ar), __float_as_uint(ai), pack2(cr, cr), pack2(-ci, -ci));
      const cx l32 = csq(csq(csq(csq(csq({ar, ai}))))), l128 = csq(csq(l32));
      sts128(S_PAR + 2048 + tid * 16, __float_as_uint(l32.r), __float_as_uint(l32.i), __float_as_uint(l128.r), __float_as_uint(l128.i));
      if (tid == 0) asm volatile("st.shared.u32 [%0], %1;" ::"r"(S_EP), "r"(ep) : "memory");
      bar_arrive(6, 256);
      bar_sync(2, 160);
      desc_touch(p.dc1);
      desc_touch(p.dc2);
      prep<0>(p, ti, pj, wid & 3, lane);
    }
    float a0[64], a1[64];
    Ring ring = {8u * wg * (16 % NS), wg * ((16u / NS) & 1), B_DUMMY - B_EMPTY};
    zero(a0); zero(a1);
    reg_fence(a0); reg_fence(a1);
    sched_fence<61>();
    bar_sync(wg * 7, 256);
    TIM(2 + wg * 2);
    if (wg == 0) gemm_steps<0, false>(a0, a1, ring, 15, p.dc1, 0);
    else gemm_steps<0, true>(a0, a1, ring, 15, p.dc1, 16);
    bar_arrive(7 + wg, 256);
    gemm_steps<0, false>(a0, a1, ring, 1, p.dc1, wg * 16 + 15);
    if (wg == 0) bar_sync(6, 256);
    scan_epilogue(a0, a1, B_EMPTY + ring.rel, wg, ti, pj, tid);
    if (wg == 1) {
      eterm(p, ti, pj, tid);
    } else {
      ring = {8 * (32 % NS), (32 / NS) & 1, B_DUMMY - B_EMPTY};
#pragma unroll
      for (int i = 0; i < 64; i++) asm volatile("" : "=f"(a0[i]), "=f"(a1[i]));
      bar_sync(8, 256);
      TIM(6);
#pragma unroll 1
      for (int o = 0; o < 4; o++) {
        if (!(o & 1)) {
          if (o) TIM(18);
          full_wait(B_LOC + 4 * o, 0, 32 + 8 * o);
          gemm_steps<1, true, true>(a0, a1, ring, 2, p.dc2, 32 + 8 * o);
        }
        gemm_steps<1, true>(a0, a1, ring, (o & 1) ? (o == 1 ? 13 : 13 - RES) : 1, p.dc2, 34 + 16 * (o >> 1) + (o & 1));
        if (!(o & 1) && elect_one()) {
          mbar_arrive(o ? B_LOC + 16 : B_SFREE + 16);
        }
      }
      TIM(28);
      const int w = tid >> 5, trow = 64 * (w & 1) + 8 * (w >> 1) + (lane >> 2);
      float* op = p.out + (size_t)(ti * 128 + trow) * DM + pj * 128 + 4 * (lane & 3);
      float g[4];
      uint4 e;
#pragma unroll
      for (int i = 0; i < RES; i++) {
        const int sl = (64 - RES + i) % NS;
        full_wait(B_FULL + 8 * sl, ((64 - RES + i) / NS) & 1, 64 - RES + i);
        WG_FENCE();
#pragma unroll
        for (int k = 0; k < 4; k++) {
          wgmma_ss128<1, 0, 1>(a0, p.dc2[3 * k + 1][sl], p.dc2[3 * k][sl]);
          if (i == 0 && k == 1 && RES == NS) { WG_COMMIT(); WG_WAIT(1); if (elect_one()) mbar_arrive(B_EMPTY + ring.rel); }
        }
        if (i >= WIN - 1 && i < RES - 1) {
          const int s1 = (64 - RES + i - WIN + 1) % NS;
#pragma unroll
          for (int k = 0; k < 4; k++) wgmma_ss128<1, 0, 1>(a1, p.dc2[3 * k + 2][s1], p.dc2[3 * k][s1]);
        }
        WG_COMMIT();
      }
      TIM(25);
      bar_sync(5, 256);
#pragma unroll
      for (int q = 0; q < 4; q++) g[q] = __uint_as_float(lds32(S_G + (trow + 16 * (q >> 1) + 32 * (q & 1)) * 4));
      e = lds128(e_addr(0, NPB == 0) + tid * 16);
      uint4 e0;
      tail_steps<0>(a0, a1, p, op, g, e, e0, tid);
      TIM(26);
      WG_WAIT(0);
      reg_fence(a1);
      TIM(7);
      unsigned tp = clock();
#define PACE() if (TPACE && o < 6) { while ((int)(clock() - tp) < 0) {} tp += TPACE; }
#pragma unroll
      for (int o = 0; o < 8; o++) {
        if (o == 4 || o == 6) bar_sync(4 + (o >> 1), 256);
        if (o >= NPB) { PACE(); store_piece(a0, op, jj_of(o), lds128(e_addr(o, 0) + tid * 16), g[0], g[1]); }
        PACE();
        store_piece(a1, op + 16 * DM, jj_of(o), o ? lds128(e_addr(o, 1) + tid * 16) : e, g[2], g[3]);
      }
#undef PACE
      if (tid == 0) g_epoch[b] = lds32(S_EP) + 1;
      TIM(19);
    }
  }
}

typedef CUresult (*EncFn)(CUtensorMap*, CUtensorMapDataType, cuuint32_t, void*, const cuuint64_t*, const cuuint64_t*,
                          const cuuint32_t*, const cuuint32_t*, CUtensorMapInterleave, CUtensorMapSwizzle,
                          CUtensorMapL2promotion, CUtensorMapFloatOOBfill);

void encode(EncFn enc, CUtensorMap* m, const void* ptr, int rank, const cuuint64_t* dims, const cuuint64_t* strides,
            const cuuint32_t* box, CUtensorMapSwizzle sw) {
  cuuint32_t es[5] = {1, 1, 1, 1, 1};
  enc(m, CU_TENSOR_MAP_DATA_TYPE_BFLOAT16, rank, const_cast<void*>(ptr), dims, strides, box, es, CU_TENSOR_MAP_INTERLEAVE_NONE,
      sw, PROMO, CU_TENSOR_MAP_FLOAT_OOB_FILL_NONE);
}

}

extern "C" void kernel_launch(void* const* d_in, const int* in_sizes, int n_in, void* d_out, int out_size) {
  typedef const __nv_bfloat16* bp;
  Ptrs p;
  p.x = (bp)d_in[0]; p.lre = (bp)d_in[1]; p.lim = (bp)d_in[2]; p.bre = (bp)d_in[3]; p.bim = (bp)d_in[4];
  p.cre = (bp)d_in[5]; p.cim = (bp)d_in[6]; p.ldt = (bp)d_in[7]; p.dskip = (bp)d_in[8];
  p.k = (bp)d_in[10]; p.v = (bp)d_in[11]; p.shift = (bp)d_in[12]; p.f = (bp)d_in[13]; p.ssmd = (bp)d_in[14];
  p.gw = (bp)d_in[15]; p.out = (float*)d_out;

  for (int sl = 0; sl < NS; sl++)
    for (int k = 0; k < 4; k++) {
      const uint64_t h128 = (uint64_t)(64u | (1u << 30)) << 32, h64 = (uint64_t)(32u | (2u << 30)) << 32;
      const uint32_t st = sb + sl * STAGE;
      p.dc1[3 * k][sl] = p.dc2[3 * k][sl] = h128 | dlo(st + 16384 + 32 * k, 16);
      p.dc1[3 * k + 1][sl] = h128 | dlo(st + 32 * k, 16);
      p.dc1[3 * k + 2][sl] = h128 | dlo(st + 8192 + 32 * k, 16);
      p.dc2[3 * k + 1][sl] = h64 | dlo(st + 1024 * k, 4096);
      p.dc2[3 * k + 2][sl] = h64 | dlo(st + 8192 + 1024 * k, 4096);
    }
  EncFn enc = nullptr;
  cudaDriverEntryPointQueryResult qr;
  cudaGetDriverEntryPoint("cuTensorMapEncodeTiled", (void**)&enc, cudaEnableDefault, &qr);
  void *zptr = nullptr, *uptr = nullptr;
  cudaGetSymbolAddress(&zptr, g_z);
  cudaGetSymbolAddress(&uptr, g_u);

  Maps m;
  {
    cuuint64_t d[4] = {1024, 2, 64, 16}, s[3] = {2048, 65536, 4096};
    cuuint32_t bx[4] = {64, 2, 4, 16};
    encode(enc, &m.x, p.x, 4, d, s, bx, CU_TENSOR_MAP_SWIZZLE_128B);
  }
  {
    cuuint64_t d[2] = {1024, 1024}, s[1] = {2048};
    cuuint32_t bx[2] = {64, 64};
    encode(enc, &m.bre, p.bre, 2, d, s, bx, CU_TENSOR_MAP_SWIZZLE_128B);
    encode(enc, &m.bim, p.bim, 2, d, s, bx, CU_TENSOR_MAP_SWIZZLE_128B);
  }
  {
    cuuint64_t d[5] = {1024, 2, 4, 2, 64}, s[4] = {2048, 8192, 4096, 32768};
    cuuint32_t bx[5] = {64, 2, 4, 2, 8};
    encode(enc, &m.cre, p.cre, 5, d, s, bx, CU_TENSOR_MAP_SWIZZLE_128B);
    encode(enc, &m.cim, p.cim, 5, d, s, bx, CU_TENSOR_MAP_SWIZZLE_128B);
  }
  {
    cuuint64_t d[3] = {64, 32, 1024}, s[2] = {128, 4096};
    cuuint32_t bx[3] = {64, 1, 32};
    encode(enc, &m.u, uptr, 3, d, s, bx, CU_TENSOR_MAP_SWIZZLE_NONE);
  }
  {
    cuuint64_t d[3] = {1024, 256, 8}, s[2] = {16384, 2048};
    cuuint32_t bx[3] = {64, 8, 4}, bh[3] = {64, 1, 3};
    encode(enc, &m.k, p.k, 3, d, s, bx, CU_TENSOR_MAP_SWIZZLE_128B);
    encode(enc, &m.kh, p.k, 3, d, s, bh, CU_TENSOR_MAP_SWIZZLE_NONE);
    encode(enc, &m.v, p.v, 3, d, s, bx, CU_TENSOR_MAP_SWIZZLE_128B);
  }
  {
    cuuint64_t d[5] = {2048, 2, 4, 2, 64}, s[4] = {4096, 16384, 8192, 65536};
    cuuint32_t bx[5] = {64, 2, 4, 2, 1};
    encode(enc, &m.z, zptr, 5, d, s, bx, CU_TENSOR_MAP_SWIZZLE_128B);
  }
  {
    cuuint64_t d[4] = {1024, 2, 4, 256}, s[3] = {8192, 2048, 16384};
    cuuint32_t bx[4] = {64, 2, 4, 16};
    encode(enc, &m.x2, p.x, 4, d, s, bx, CU_TENSOR_MAP_SWIZZLE_128B);
  }
  cudaFuncSetAttribute(fused_kernel, cudaFuncAttributeMaxDynamicSharedMemorySize, SMEM_BYTES);
  fused_kernel<<<132, 512, SMEM_BYTES, cudaStreamPerThread>>>(m, p);
}
```

```cpp
#include <cuda_runtime.h>
#include <cuda_bf16.h>
#include <cuda.h>
#include <stdint.h>

namespace {

constexpr int SEQ = 2048, DM = 1024;
#define NSV 5
constexpr int NS = NSV;
constexpr int STAGE = 32768;
#define KV0_AT 300
#define KV_GAP0 600
#define KV1_AT 8200
#define KV_GAP1 450
#define EARLY 2
#define SFM 2
#define RV 1
#define POLL_NS 60
#define IM_NS 40
#define SPF_AT 7000
#define RELK 0
#define RES 4
#define AGG_NS 200
#define ZL_NS 60
#define P2F 3
#define KEEP 16
#define RE_EARLY 0
#define MAP 0
#define WIN 4
#define NPB 3
#define TOFF 1
#define LD_GAP 400
#define LDQ ""
#define PROMO CU_TENSOR_MAP_L2_PROMOTION_L2_128B
constexpr uint32_t sb = 1024;
constexpr uint32_t S_STG = sb + NS * STAGE;
constexpr uint32_t S_CIN = S_STG + 32768;
constexpr uint32_t S_T = S_CIN + 16384;
constexpr uint32_t S_M1 = S_T + 8192;
constexpr uint32_t S_M2 = S_M1 + 4096;
constexpr uint32_t S_PAR = S_M2 + 2048;
constexpr uint32_t S_G = S_PAR + 4096;
constexpr uint32_t S_BAR = S_G + 512;
constexpr int SMEM_BYTES = S_BAR + 512 - sb;
constexpr uint32_t B_FULL = S_BAR, B_EMPTY = B_FULL + 8 * NS, B_CINF = B_EMPTY + 8 * NS,
                   B_FLG = B_CINF + 24, B_SFREE = B_FLG + 40, B_LOC = B_SFREE + 24, B_ZT = B_LOC + 24,
                   B_XT = B_ZT + 16, B_PIN = B_XT + 32, B_DUMMY = B_PIN + 32, S_EP = B_DUMMY + 8;
constexpr int SPIN_LIMIT = 1 << 21;
constexpr int F_H = 0, F_U = 64, F_Z = 80;

struct alignas(64) Maps { CUtensorMap x, bre, bim, cre, cim, u, z, x2, k, kh, v; };
struct Ptrs {
  const __nv_bfloat16 *x, *lre, *lim, *ldt, *dskip, *k, *v, *shift, *f, *ssmd, *gw, *bre, *bim, *cre, *cim;
  float* out;
  uint64_t dc1[12][NS], dc2[12][NS];
};

__device__ uint4 g_h[16 * 32 * 1024];
__device__ uint4 g_u[1024 * 256];
__device__ uint4 g_z[1024 * 256];
__device__ uint4 g_agg[2 * 16 * 256];
__device__ unsigned g_gate[8 * SEQ];
__device__ unsigned g_flag[88 * 32];
__device__ unsigned g_epoch[140];
#define TIM(i)
#define TIMC(i)

#define WG_FENCE() asm volatile("wgmma.fence.sync.aligned;" ::: "memory")
#define WG_COMMIT() asm volatile("wgmma.commit_group.sync.aligned;" ::: "memory")
#define WG_WAIT(n) asm volatile("wgmma.wait_group.sync.aligned %0;" ::"n"(n) : "memory")
#define R8(d, o) "+f"(d[o + 0]), "+f"(d[o + 1]), "+f"(d[o + 2]), "+f"(d[o + 3]), "+f"(d[o + 4]), "+f"(d[o + 5]), "+f"(d[o + 6]), "+f"(d[o + 7])
#define W8(d, o) "=f"(d[o + 0]), "=f"(d[o + 1]), "=f"(d[o + 2]), "=f"(d[o + 3]), "=f"(d[o + 4]), "=f"(d[o + 5]), "=f"(d[o + 6]), "=f"(d[o + 7])
#define L16 "%0,%1,%2,%3,%4,%5,%6,%7,%8,%9,%10,%11,%12,%13,%14,%15"
#define L64 L16 ",%16,%17,%18,%19,%20,%21,%22,%23,%24,%25,%26,%27,%28,%29,%30,%31," \
  "%32,%33,%34,%35,%36,%37,%38,%39,%40,%41,%42,%43,%44,%45,%46,%47,%48,%49,%50,%51,%52,%53,%54,%55,%56,%57,%58,%59,%60,%61,%62,%63"

template <int TA, int TB, int ACC>
__device__ __forceinline__ void wgmma_ss128(float (&d)[64], uint64_t da, uint64_t db) {
  if (ACC)
    asm volatile("wgmma.mma_async.sync.aligned.m64n128k16.f32.bf16.bf16 {" L64 "}, %64, %65, 1, 1, 1, %66, %67;"
                 : R8(d, 0), R8(d, 8), R8(d, 16), R8(d, 24), R8(d, 32), R8(d, 40), R8(d, 48), R8(d, 56)
                 : "l"(da), "l"(db), "n"(TA), "n"(TB));
  else
    asm volatile("wgmma.mma_async.sync.aligned.m64n128k16.f32.bf16.bf16 {" L64 "}, %64, %65, 0, 1, 1, %66, %67;"
                 : W8(d, 0), W8(d, 8), W8(d, 16), W8(d, 24), W8(d, 32), W8(d, 40), W8(d, 48), W8(d, 56)
                 : "l"(da), "l"(db), "n"(TA), "n"(TB));
}
template <int TA>
__device__ __forceinline__ void wgmma_ss128p(float (&d)[64], uint64_t da, uint64_t db, int acc) {
  asm volatile("{.reg .pred p; setp.ne.b32 p, %67, 0;\n"
               "wgmma.mma_async.sync.aligned.m64n128k16.f32.bf16.bf16 {" L64 "}, %64, %65, p, 1, 1, %66, 0;}"
               : R8(d, 0), R8(d, 8), R8(d, 16), R8(d, 24), R8(d, 32), R8(d, 40), R8(d, 48), R8(d, 56)
               : "l"(da), "l"(db), "n"(TA), "r"(acc));
}
template <int ACC, int TB = 0>
__device__ __forceinline__ void wgmma_rs32(float (&d)[16], uint32_t a0, uint32_t a1, uint32_t a2, uint32_t a3, uint64_t db) {
  if (ACC)
    asm volatile("wgmma.mma_async.sync.aligned.m64n32k16.f32.bf16.bf16 {" L16 "}, {%16,%17,%18,%19}, %20, 1, 1, 1, %21;"
                 : R8(d, 0), R8(d, 8) : "r"(a0), "r"(a1), "r"(a2), "r"(a3), "l"(db), "n"(TB));
  else
    asm volatile("wgmma.mma_async.sync.aligned.m64n32k16.f32.bf16.bf16 {" L16 "}, {%16,%17,%18,%19}, %20, 0, 1, 1, %21;"
                 : W8(d, 0), W8(d, 8) : "r"(a0), "r"(a1), "r"(a2), "r"(a3), "l"(db), "n"(TB));
}
template <int N>
__device__ __forceinline__ void reg_fence(float (&d)[N]) {
#pragma unroll
  for (int i = 0; i < N; i++) asm volatile("" : "+f"(d[i])::"memory");
}
__host__ __device__ __forceinline__ constexpr uint32_t dlo(uint32_t addr, uint32_t lbo) { return (addr >> 4) + ((lbo >> 4) << 16); }
__device__ __forceinline__ uint64_t mkdesc(uint32_t lo, uint32_t sbo, uint32_t mode) {
  uint64_t d;
  asm("mov.b64 %0, {%1, %2};" : "=l"(d) : "r"(lo), "r"((sbo >> 4) | (mode << 30)));
  return d;
}
template <int N>
__device__ __forceinline__ void zero(float (&d)[N]) {
#pragma unroll
  for (int i = 0; i < N; i++) d[i] = 0.f;
}
__device__ __forceinline__ void trap_if(int c) {
  asm volatile("{.reg .pred p; .reg .b64 z; setp.ne.s32 p, %0, 0; mov.b64 z, 0; @p st.global.u32 [z], %0;}" ::"r"(c) : "memory");
}
template <int K>
__device__ __forceinline__ void sched_fence() {
  asm volatile("{.reg .pred p; setp.eq.u32 p, %0, %1; @p exit;}" ::"r"(gridDim.x), "n"(256 + K) : "memory");
}
template <int K>
__device__ __forceinline__ void sched_fence_async() {
  asm volatile("{.reg .pred p; .reg .u32 r; setp.ne.u32 p, %0, %1; @p bra.uni SFE;\n"
               "SFL: nanosleep.u32 1000; mov.u32 r, %%clock; setp.eq.u32 p, r, 0; @p bra.uni SFL;\nSFE: }" ::"r"(gridDim.x), "n"(256 + K) : "memory");
}
__device__ __forceinline__ bool elect_one() {
  uint32_t pred;
  asm volatile("{.reg .pred p; elect.sync _|p, 0xffffffff; selp.u32 %0, 1, 0, p;}" : "=r"(pred));
  return pred;
}
__device__ __forceinline__ void mbar_init(uint32_t bar, uint32_t cnt) {
  asm volatile("mbarrier.init.shared::cta.b64 [%0], %1;" ::"r"(bar), "r"(cnt) : "memory");
}
__device__ __forceinline__ bool mbar_try(uint32_t bar, uint32_t par) {
  uint32_t ok;
  asm volatile("{.reg .pred p; mbarrier.try_wait.parity.shared::cta.b64 p, [%1], %2; selp.u32 %0, 1, 0, p;}"
               : "=r"(ok) : "r"(bar), "r"(par) : "memory");
  return ok;
}
#undef DBGV
#define DBGV ((bar - S_BAR) * 2 + par)
__device__ __forceinline__ void mbar_wait(uint32_t bar, uint32_t par) {
  if (__builtin_expect(!mbar_try(bar, par), 0)) {
    int n = SPIN_LIMIT;
    while (!mbar_try(bar, par) && --n) {}
    trap_if(n == 0);
  }
}
#define full_wait(bar, par, slot) mbar_wait(bar, par)
__device__ __forceinline__ void mbar_wait_long(uint32_t bar, uint32_t par) {
  int n = SPIN_LIMIT;
  while (!mbar_try(bar, par) && --n) __nanosleep(100);
  trap_if(n == 0);
}
#undef DBGV
#define DBGV 0
__device__ __forceinline__ void mbar_arrive(uint32_t bar) {
  asm volatile("mbarrier.arrive.shared::cta.b64 _, [%0];" ::"r"(bar) : "memory");
}
__device__ __forceinline__ void mbar_expect(uint32_t bar, uint32_t bytes) {
  asm volatile("mbarrier.arrive.expect_tx.shared::cta.b64 _, [%0], %1;" ::"r"(bar), "r"(bytes) : "memory");
}
__device__ __forceinline__ void tma2d(uint32_t dst, const CUtensorMap* m, uint32_t bar, int c0, int c1) {
  asm volatile("cp.async.bulk.tensor.2d.shared::cluster.global.mbarrier::complete_tx::bytes [%0], [%1, {%3, %4}], [%2];"
               ::"r"(dst), "l"(m), "r"(bar), "r"(c0), "r"(c1) : "memory");
}
__device__ __forceinline__ void tma3d(uint32_t dst, const CUtensorMap* m, uint32_t bar, int c0, int c1, int c2) {
  asm volatile("cp.async.bulk.tensor.3d.shared::cluster.global.mbarrier::complete_tx::bytes [%0], [%1, {%3, %4, %5}], [%2];"
               ::"r"(dst), "l"(m), "r"(bar), "r"(c0), "r"(c1), "r"(c2) : "memory");
}
__device__ __forceinline__ void tma4d(uint32_t dst, const CUtensorMap* m, uint32_t bar, int c0, int c1, int c2, int c3) {
  asm volatile("cp.async.bulk.tensor.4d.shared::cluster.global.mbarrier::complete_tx::bytes [%0], [%1, {%3, %4, %5, %6}], [%2];"
               ::"r"(dst), "l"(m), "r"(bar), "r"(c0), "r"(c1), "r"(c2), "r"(c3) : "memory");
}
__device__ __forceinline__ void tma5d(uint32_t dst, const CUtensorMap* m, uint32_t bar, int c0, int c1, int c2, int c3, int c4) {
  asm volatile("cp.async.bulk.tensor.5d.shared::cluster.global.mbarrier::complete_tx::bytes [%0], [%1, {%3, %4, %5, %6, %7}], [%2];"
               ::"r"(dst), "l"(m), "r"(bar), "r"(c0), "r"(c1), "r"(c2), "r"(c3), "r"(c4) : "memory");
}
__device__ __forceinline__ void bulk_load(uint32_t dst, const void* src, uint32_t bytes, uint32_t bar) {
  asm volatile("cp.async.bulk.shared::cluster.global.mbarrier::complete_tx::bytes [%0], [%1], %2, [%3];"
               ::"r"(dst), "l"(src), "r"(bytes), "r"(bar) : "memory");
}
__device__ __forceinline__ void l2_prefetch(const void* src, uint32_t bytes) {
  asm volatile("cp.async.bulk.prefetch.L2.global [%0], %1;" ::"l"(src), "r"(bytes) : "memory");
}
__device__ __forceinline__ void bar_sync(int id, int n) { asm volatile("bar.sync %0, %1;" ::"r"(id), "r"(n) : "memory"); }
__device__ __forceinline__ void bar_arrive(int id, int n) { asm volatile("bar.arrive %0, %1;" ::"r"(id), "r"(n) : "memory"); }
__device__ __forceinline__ void fence_async_smem() { asm volatile("fence.proxy.async.shared::cta;" ::: "memory"); }
__device__ __forceinline__ void fence_async_global() { asm volatile("fence.proxy.async.global;" ::: "memory"); }
__device__ __forceinline__ void flag_add(int f) {
  asm volatile("red.relaxed.gpu.global.add.u32 [%0], 1;" ::"l"(g_flag + f * 32) : "memory");
}
__device__ __forceinline__ void flag_release(int f) {
  asm volatile("fence.release.gpu;" ::: "memory");
  flag_add(f);
}
__device__ __forceinline__ unsigned ld_relaxed(const unsigned* p) {
  unsigned v;
  asm volatile("ld.relaxed.gpu.global.u32 %0, [%1];" : "=r"(v) : "l"(p) : "memory");
  return v;
}
__device__ __forceinline__ void wait_clock(unsigned t) {
  int d;
  while ((d = (int)(t - (unsigned)clock())) > 0) __nanosleep(d > 600 ? 200 : 40);
}
__device__ __forceinline__ uint32_t pack2(float lo, float hi) {
  uint32_t r;
  asm("cvt.rn.bf16x2.f32 %0, %1, %2;" : "=r"(r) : "f"(hi), "f"(lo));
  return r;
}
__device__ __forceinline__ float bf_lo(uint32_t v) { return __uint_as_float(v << 16); }
__device__ __forceinline__ float bf_hi(uint32_t v) { return __uint_as_float(v & 0xffff0000u); }
__device__ __forceinline__ float bf_round(float v) { return __bfloat162float(__float2bfloat16_rn(v)); }
__device__ __forceinline__ uint32_t hmul2(uint32_t a, uint32_t b) {
  uint32_t r;
  asm("mul.rn.bf16x2 %0, %1, %2;" : "=r"(r) : "r"(a), "r"(b));
  return r;
}
__device__ __forceinline__ uint32_t hadd2(uint32_t a, uint32_t b) {
  uint32_t r;
  asm("add.rn.bf16x2 %0, %1, %2;" : "=r"(r) : "r"(a), "r"(b));
  return r;
}
__device__ __forceinline__ uint32_t hsub2(uint32_t a, uint32_t b) {
  uint32_t r;
  asm("sub.rn.bf16x2 %0, %1, %2;" : "=r"(r) : "r"(a), "r"(b));
  return r;
}
__device__ __forceinline__ uint32_t hfma2(uint32_t a, uint32_t b, uint32_t c) {
  uint32_t r;
  asm("fma.rn.bf16x2 %0, %1, %2, %3;" : "=r"(r) : "r"(a), "r"(b), "r"(c));
  return r;
}
__device__ __forceinline__ uint32_t hneg2(uint32_t a) {
  uint32_t r;
  asm("neg.bf16x2 %0, %1;" : "=r"(r) : "r"(a));
  return r;
}
__device__ __forceinline__ uint4 ldg128(const void* p) {
  uint4 v;
  asm volatile("ld.global.nc" LDQ ".v4.u32 {%0,%1,%2,%3}, [%4];" : "=r"(v.x), "=r"(v.y), "=r"(v.z), "=r"(v.w) : "l"(p));
  return v;
}
__device__ __forceinline__ uint2 ldg64(const void* p) {
  uint2 v;
  asm volatile("ld.global.nc.v2.u32 {%0,%1}, [%2];" : "=r"(v.x), "=r"(v.y) : "l"(p));
  return v;
}
__device__ __forceinline__ void stg128(void* p, uint32_t a, uint32_t b, uint32_t c, uint32_t d) {
  asm volatile("st.global.v4.u32 [%0], {%1,%2,%3,%4};" ::"l"(p), "r"(a), "r"(b), "r"(c), "r"(d) : "memory");
}
__device__ __forceinline__ void sts128(uint32_t a, uint32_t x, uint32_t y, uint32_t z, uint32_t w) {
  asm volatile("st.shared.v4.u32 [%0], {%1,%2,%3,%4};" ::"r"(a), "r"(x), "r"(y), "r"(z), "r"(w) : "memory");
}
__device__ __forceinline__ uint32_t lds32(uint32_t a) {
  uint32_t v;
  asm volatile("ld.shared.u32 %0, [%1];" : "=r"(v) : "r"(a) : "memory");
  return v;
}
__device__ __forceinline__ uint4 lds128(uint32_t a) {
  uint4 v;
  asm volatile("ld.shared.v4.u32 {%0,%1,%2,%3}, [%4];" : "=r"(v.x), "=r"(v.y), "=r"(v.z), "=r"(v.w) : "r"(a) : "memory");
  return v;
}
__device__ __forceinline__ void stsm4(uint32_t a, uint32_t x, uint32_t y, uint32_t z, uint32_t w) {
  asm volatile("stmatrix.sync.aligned.m8n8.x4.shared.b16 [%0], {%1,%2,%3,%4};" ::"r"(a), "r"(x), "r"(y), "r"(z), "r"(w) : "memory");
}
__device__ __forceinline__ void stsm4t(uint32_t a, uint32_t x, uint32_t y, uint32_t z, uint32_t w) {
  asm volatile("stmatrix.sync.aligned.m8n8.x4.trans.shared.b16 [%0], {%1,%2,%3,%4};" ::"r"(a), "r"(x), "r"(y), "r"(z), "r"(w) : "memory");
}
__device__ __forceinline__ uint4 ldsm4t(uint32_t a) {
  uint4 v;
  asm volatile("ldmatrix.sync.aligned.m8n8.x4.trans.shared.b16 {%0,%1,%2,%3}, [%4];" : "=r"(v.x), "=r"(v.y), "=r"(v.z), "=r"(v.w) : "r"(a) : "memory");
  return v;
}
struct cx { float r, i; };
__device__ __forceinline__ cx cmul(cx a, cx b) { return {a.r * b.r - a.i * b.i, a.r * b.i + a.i * b.r}; }
__device__ __forceinline__ cx cfma(cx a, cx b, cx c) { return {fmaf(a.r, b.r, fmaf(-a.i, b.i, c.r)), fmaf(a.r, b.i, fmaf(a.i, b.r, c.i))}; }
__device__ __forceinline__ cx csq(cx a) { return {a.r * a.r - a.i * a.i, 2.f * a.r * a.i}; }
__device__ __forceinline__ cx unit(int num, int den) {
  int m = num & (den - 1);
  if (m >= den / 2) m -= den;
  float s, c;
  __sincosf((float)m * (-6.283185307179586f / (float)den), &s, &c);
  return {c, s};
}

__device__ __forceinline__ uint2 lds64(uint32_t a) {
  uint2 v;
  asm volatile("ld.shared.v2.u32 {%0,%1}, [%2];" : "=r"(v.x), "=r"(v.y) : "r"(a) : "memory");
  return v;
}
__device__ __forceinline__ void prep_taps(const uint4 (&sh)[2], uint32_t (&s)[2][4]) {
#pragma unroll
  for (int e = 0; e < 2; e++) {
    s[e][0] = __byte_perm(sh[e].x, sh[e].z, 0x5410); s[e][1] = __byte_perm(sh[e].x, sh[e].z, 0x7632);
    s[e][2] = __byte_perm(sh[e].y, sh[e].w, 0x5410); s[e][3] = __byte_perm(sh[e].y, sh[e].w, 0x7632);
  }
}
__device__ __forceinline__ void prep_math(const uint2 (&kk)[11], uint2 (&vv)[8], const uint32_t (&s)[2][4]) {
#pragma unroll
  for (int i = 0; i < 8; i++)
#pragma unroll
    for (int e = 0; e < 2; e++) {
      uint32_t a = hmul2((&kk[i].x)[e], s[e][3]);
      a = hfma2((&kk[i + 1].x)[e], s[e][2], a);
      a = hfma2((&kk[i + 2].x)[e], s[e][1], a);
      a = hfma2((&kk[i + 3].x)[e], s[e][0], a);
      (&vv[i].x)[e] = hmul2(a, (&vv[i].x)[e]);
    }
}
__device__ __forceinline__ void prep_store(const uint2 (&vv)[8], int d, int tb) {
  uint4* dst = g_u + (size_t)((d >> 5) * 32 + (tb >> 3)) * 256 + (d & 31) * 8 + ((tb & 7) ^ ((tb >> 3) & 1));
#pragma unroll
  for (int e = 0; e < 2; e++) {
#define U(i) (&vv[i].x)[e]
    stg128(dst + (2 * e) * 8, __byte_perm(U(0), U(1), 0x5410), __byte_perm(U(2), U(3), 0x5410),
           __byte_perm(U(4), U(5), 0x5410), __byte_perm(U(6), U(7), 0x5410));
    stg128(dst + (2 * e + 1) * 8, __byte_perm(U(0), U(1), 0x7632), __byte_perm(U(2), U(3), 0x7632),
           __byte_perm(U(4), U(5), 0x7632), __byte_perm(U(6), U(7), 0x7632));
#undef U
  }
}
template <int PG>
__device__ __forceinline__ void prep(const Ptrs& p, int ti, int pj, int w, int lane) {
  const int tb = lane & 7, chunk = 2 * w + (lane >> 4), ch = chunk * 8 + ((lane >> 3) & 1) * 4, d = pj * 128 + PG * 64 + ch;
  const uint4 sh[2] = {ldg128(p.shift + d * 4), ldg128(p.shift + d * 4 + 8)};
  uint32_t s[2][4];
  prep_taps(sh, s);
#pragma unroll 1
  for (int th = 0; th < 2; th++) {
    uint2 kk[11], vv[8];
    {
      const uint32_t in = S_STG + th * 16384 + (lane & 8);
      const uint32_t a0 = in + tb * 128 + ((chunk ^ tb) << 4);
      const uint32_t hb = tb ? in + (39 + tb) * 128 + ((chunk ^ (tb - 1)) << 4) : S_T + (PG * 2 + th) * 512 + ch * 2;
      const uint32_t hs = tb ? 1024 : 128;
      mbar_wait_long(B_PIN + 16 * PG + 8 * th, 0);
      if (th) TIM(29 + PG);
#pragma unroll
      for (int i = 0; i < 3; i++) kk[i] = lds64(hb + i * hs);
#pragma unroll
      for (int i = 0; i < 8; i++) { kk[3 + i] = lds64(a0 + i * 1024); vv[i] = lds64(a0 + 8192 + i * 1024); }
      prep_math(kk, vv, s);
      sched_fence<52 + PG>();
    }
    if (!PG) bar_arrive(th ? 11 : 3, 160);
    else if (elect_one()) mbar_arrive(B_SFREE + 8 * th);
    prep_store(vv, d, ti * 16 + th * 8 + tb);
  }
  bar_arrive(4 + PG, 160);
}

__device__ __forceinline__ void gate_finish(int ti, int tid, uint32_t tag) {
  float l;
  int n = SPIN_LIMIT;
  bool bad;
  do {
    __nanosleep(250);
    uint32_t v[8], x = 0;
#pragma unroll
    for (int j = 0; j < 8; j++) v[j] = ld_relaxed(g_gate + j * SEQ + ti * 128 + tid) ^ tag;
    l = 0.f;
#pragma unroll
    for (int j = 0; j < 8; j++) { x |= v[j]; l += __uint_as_float(v[j]); }
    bad = __any_sync(~0u, x & 3);
  } while (bad && --n);
  trap_if(n == 0);
  const float g = bf_round(__fdividef(1.f, 1.f + __expf(-bf_round(l))));
  asm volatile("st.shared.f32 [%0], %1;" ::"r"(S_G + tid * 4), "f"(g) : "memory");
}

__device__ __forceinline__ void conv_tables(int tid) {
  {
    const int s = tid >> 5, n1 = tid & 31;
    uint32_t re[4], im[4];
#pragma unroll
    for (int e = 0; e < 4; e++) {
      cx a = unit(n1 * (4 * (8 * s + 2 * e) + 1), 128), b = unit(n1 * (4 * (8 * s + 2 * e + 1) + 1), 128);
      re[e] = pack2(a.r * 0.125f, b.r * 0.125f); im[e] = pack2(a.i * 0.125f, b.i * 0.125f);
    }
    sts128(S_M1 + (2 * s) * 512 + n1 * 16, re[0], re[1], re[2], re[3]);
    sts128(S_M1 + (2 * s + 1) * 512 + n1 * 16, im[0], im[1], im[2], im[3]);
  }
  {
    const int kg = tid >> 5, n = tid & 31;
    const int pi = kg >> 1, po = n >> 4, f2 = n & 15;
    uint32_t fw[4];
#pragma unroll
    for (int e = 0; e < 4; e++) {
      int n2 = (kg & 1) * 8 + 2 * e;
      cx a = unit(n2 * f2, 16), b = unit((n2 + 1) * f2, 16);
      float sg = pi ? -1.f : 1.f;
      float x0 = (pi == po) ? a.r : sg * a.i, x1 = (pi == po) ? b.r : sg * b.i;
      fw[e] = pack2(x0, x1);
    }
    sts128(S_M2 + kg * 512 + n * 16, fw[0], fw[1], fw[2], fw[3]);
  }
  fence_async_smem();
}
__device__ __forceinline__ constexpr int jj_of(int o) { return o == 7 ? 3 : o + (o >= 3); }
__device__ __forceinline__ int conv_chan(int ti, int pj, int jj) { return pj * 128 + jj * 16 + ti; }

struct ConvCtx {
  uint32_t buf, inbar;
  int nb, n;
  int ti, pj, j;
  __device__ __forceinline__ int chan(int c) const {
    return j < 0 ? conv_chan(ti, pj, jj_of(c)) : conv_chan(((j + 12 * c) >> 3) + (((j + 12 * c) >> 3) >= KEEP), (j + 12 * c) & 7, 3);
  }
};
__device__ __forceinline__ ConvCtx conv_ctx(int spare, int wg, int ti, int pj) {
  const int j = spare < 0 ? -1 : spare * 3 + wg;
  return {wg == 2 ? S_CIN : sb + wg * 32768, wg == 2 ? B_CINF : (wg ? B_PIN : B_FULL), 4 + 4 * wg, j < 0 ? 7 + (ti == KEEP) : (j < 8 && KEEP > 15 ? 11 : 10), ti, pj, j};
}
#define CDESC(a) mkdesc(dlo(a, 512), 128, 0)
struct ConvTw { uint32_t r[2], i[2], n[2]; };

__device__ __forceinline__ void cv_tw1(float (&d)[64], uint32_t (&R)[16], uint32_t (&I)[16], const ConvTw& t, int i) {
#pragma unroll
  for (int j = 8 * (i & 1); j < 8 * (i & 1) + 8; j++) {
    if (i < 2) {
      R[j] = pack2(d[4 * j], d[4 * j + 1]); I[j] = pack2(d[4 * j + 2], d[4 * j + 3]);
    } else {
      const uint32_t xr = R[j], xi = I[j];
      R[j] = hfma2(xr, t.r[j & 1], hmul2(xi, t.n[j & 1]));
      I[j] = hfma2(xr, t.i[j & 1], hmul2(xi, t.r[j & 1]));
    }
  }
}
template <int N>
__device__ __forceinline__ void cv_pack(float (&X)[16], uint32_t (&P)[N][2][2], int q) {
#pragma unroll
  for (int k = 0; k < 2; k++)
#pragma unroll
    for (int j = 0; j < 4; j++) P[2 * q + k][j >> 1][j & 1] = pack2(X[4 * j + 2 * k], X[4 * j + 2 * k + 1]);
}
__device__ __forceinline__ void cv_overlap(uint32_t (&P)[8][2][2]) {
#pragma unroll
  for (int k = 3; k > 0; k--)
#pragma unroll
    for (int hh = 0; hh < 2; hh++) {
      P[k][0][hh] = hsub2(P[k][0][hh], P[k - 1][1][hh]);
      P[k][1][hh] = hadd2(P[k][1][hh], P[k - 1][0][hh]);
    }
}
__device__ __forceinline__ void cv_pw(uint32_t (&P)[8][2][2], uint32_t (&Q)[4][2][2]) {
#pragma unroll
  for (int jh = 0; jh < 8; jh++) {
    const int j = jh >> 1, hh = jh & 1;
    uint32_t qr = hmul2(P[4 + j][0][hh], P[0][0][hh]), qi = hmul2(P[4 + j][0][hh], P[0][1][hh]);
    qr = hfma2(hneg2(P[4 + j][1][hh]), P[0][1][hh], qr);
    qi = hfma2(P[4 + j][1][hh], P[0][0][hh], qi);
#pragma unroll
    for (int k = j - 1; k >= 0; k--) {
      qr = hfma2(P[4 + k][0][hh], P[j - k][0][hh], qr);
      qi = hfma2(P[4 + k][0][hh], P[j - k][1][hh], qi);
      qr = hfma2(hneg2(P[4 + k][1][hh]), P[j - k][1][hh], qr);
      qi = hfma2(P[4 + k][1][hh], P[j - k][0][hh], qi);
    }
    Q[j][0][hh] = qr; Q[j][1][hh] = qi;
  }
}
__device__ __forceinline__ void cv_tw2(uint32_t (&Q)[4][2][2], const ConvTw& t, int k) {
#pragma unroll
  for (int hh = 0; hh < 2; hh++) {
    const uint32_t xr = Q[k][0][hh], xi = Q[k][1][hh];
    Q[k][0][hh] = hfma2(xr, t.r[hh], hmul2(xi, t.i[hh]));
    Q[k][1][hh] = hfma2(xr, t.n[hh], hmul2(xi, t.r[hh]));
  }
}
__device__ __forceinline__ void cv_out0(float (&Y)[16], uint32_t T, int w, int lane) {
  reg_fence(Y);
  const uint32_t za = T + w * 2048 + (lane >> 4) * 256 + (lane & 7) * 32 + (((lane >> 3) ^ (lane >> 2)) & 1) * 16;
#pragma unroll
  for (int jj = 0; jj < 2; jj++)
    stsm4t(za + jj * 512, pack2(Y[8 * jj], Y[8 * jj + 1]), pack2(Y[8 * jj + 2], Y[8 * jj + 3]),
           pack2(Y[8 * jj + 4], Y[8 * jj + 5]), pack2(Y[8 * jj + 6], Y[8 * jj + 7]));
}

__device__ __forceinline__ void cv_out1(const uint4& z0, const uint4& z1, const ConvCtx& cc, uint32_t keep, uint32_t tag, int ch, int w, int lane) {
  uint4* zp = g_z + (size_t)cc.chan(ch) * 256 + w * 64 + lane;
#define TG(v) ((v & keep) | (tag & ~keep))
  asm volatile("st.relaxed.gpu.global.v4.u32 [%0], {%1,%2,%3,%4};" ::"l"(zp), "r"(TG(z0.x)), "r"(TG(z0.y)), "r"(TG(z0.z)), "r"(TG(z0.w)) : "memory");
  asm volatile("st.relaxed.gpu.global.v4.u32 [%0], {%1,%2,%3,%4};" ::"l"(zp + 32), "r"(TG(z1.x)), "r"(TG(z1.y)), "r"(TG(z1.z)), "r"(TG(z1.w)) : "memory");
#undef TG
}
template <bool FW, bool BW, int K>
__device__ __forceinline__ void conv_step(uint32_t (&Q)[4][2][2], const ConvTw& t, const ConvCtx& cc, float dl, uint32_t tag, int ch, int w, int lane) {
#define SF(n) if ((SFM >> (n)) & 1) sched_fence_async<K + (n)>()
  float d[64], X[4][16], Z[2][16], Y[16];
  uint32_t R[16], I[16];
  uint4 a[4];
  const int nx = ch + 1;
  const uint32_t T = cc.buf + 16384;
  float dv;
  TIMC(1);
  if (FW) {
    dv = __shfl_sync(~0u, dl, nx);
    mbar_wait(cc.inbar + 8 * (nx & 1), (nx >> 1) & 1);
  }
  TIMC(2);
  WG_FENCE();
  if (BW) {
#pragma unroll
    for (int q = 0; q < 2; q++) {
      wgmma_rs32<0, 1>(Z[q], Q[2 * q][0][0], Q[2 * q + 1][0][0], Q[2 * q][0][1], Q[2 * q + 1][0][1], mkdesc(dlo(S_M2, 128), 512, 0));
      wgmma_rs32<1, 1>(Z[q], Q[2 * q][1][0], Q[2 * q + 1][1][0], Q[2 * q][1][1], Q[2 * q + 1][1][1], mkdesc(dlo(S_M2 + 256, 128), 512, 0));
    }
    WG_COMMIT();
  }
  if (FW) {
    const uint32_t lo = dlo(0, 1024) + (cc.buf >> 4) + (nx & 1) * 512;
    wgmma_ss128<1, 1, 0>(d, mkdesc(dlo(S_M1, 128), 512, 0), mkdesc(lo, 256, 3));
    wgmma_ss128<1, 1, 1>(d, mkdesc(dlo(S_M1 + 256, 128), 512, 0), mkdesc(lo + 32, 256, 3));
    WG_COMMIT();
  }
  TIMC(3);
  if (BW) {
    TIMC(4);
    WG_WAIT(FW ? 1 : 0);
    TIMC(5);
    reg_fence(Z[0]); reg_fence(Z[1]);
    uint32_t V[4][2][2];
    cv_pack(Z[0], V, 0); cv_pack(Z[1], V, 1);
    SF(0);
#pragma unroll
    for (int k = 0; k < 4; k++) cv_tw2(V, t, k);
    bar_sync(cc.nb, 128);
#pragma unroll
    for (int k = 0; k < 4; k++) stsm4(T + w * 512 + lane * 16 + k * 2048, V[k][0][0], V[k][0][1], V[k][1][0], V[k][1][1]);
    SF(1);
    TIMC(6);
  }
  if (FW) {
    WG_WAIT(0);
    reg_fence(d);
    if (nx + 2 < cc.n) bar_arrive(cc.nb + 2 + (nx & 1), 160);
    cv_tw1(d, R, I, t, 0); cv_tw1(d, R, I, t, 1);
    SF(2);
    TIMC(7);
  }
  if (BW) {
    bar_sync(cc.nb, 128);
#pragma unroll
    for (int s = 0; s < 4; s++) a[s] = ldsm4t(T + (4 * w + s) * 512 + lane * 16);
  }
  if (FW) { cv_tw1(d, R, I, t, 2); cv_tw1(d, R, I, t, 3); }
  sched_fence<K + 3>();
  TIMC(8);
  WG_FENCE();
  if (BW) {
    wgmma_rs32<0>(Y, a[0].x, a[0].y, a[0].z, a[0].w, CDESC(S_M1));
#pragma unroll
    for (int i = 1; i < 4; i++) wgmma_rs32<1>(Y, a[i].x, a[i].y, a[i].z, a[i].w, CDESC(S_M1 + 1024 * i));
  }
  if (FW) {
#pragma unroll
    for (int q = 0; q < 4; q++) {
      if (q == 2) WG_COMMIT();
      wgmma_rs32<0>(X[q], R[4 * q], R[4 * q + 2], R[4 * q + 1], R[4 * q + 3], CDESC(S_M2));
      wgmma_rs32<1>(X[q], I[4 * q], I[4 * q + 2], I[4 * q + 1], I[4 * q + 3], CDESC(S_M2 + 1024));
    }
  }
  WG_COMMIT();
  TIMC(9);
  WG_WAIT(FW ? 1 : 0);
  TIMC(10);
  uint4 z0, z1;
  const uint32_t zr = T + w * 2048 + (lane ^ ((lane >> 3) & 1)) * 16;
  if (BW) {
    cv_out0(Y, T, w, lane);
    __syncwarp();
  }
  if (FW) {
    uint32_t P[8][2][2];
    reg_fence(X[0]); reg_fence(X[1]);
    cv_pack(X[0], P, 0); cv_pack(X[1], P, 1);
    cv_overlap(P);
    if (BW) { z0 = lds128(zr); z1 = lds128(zr + 512); }
    sched_fence_async<K + 7>();
    WG_WAIT(0);
    reg_fence(X[2]); reg_fence(X[3]);
    X[2][0] += dv; X[2][1] += dv; X[2][4] += dv; X[2][5] += dv;
    cv_pack(X[2], P, 2); cv_pack(X[3], P, 3);
    SF(4);
    TIMC(11);
    cv_pw(P, Q);
    SF(8);
  } else {
    z0 = lds128(zr); z1 = lds128(zr + 512);
  }
  if (BW) cv_out1(z0, z1, cc, FW && cc.j < 0 && ch < 4 ? ~0u : ~1u, tag, ch, w, lane);
  sched_fence<K + 5>();
  TIMC(13);
#undef SF
}

__device__ __forceinline__ void conv_main(const Ptrs& p, const ConvCtx& cc, int eb, int tid) {
  const int ti = cc.ti, pj = cc.pj;
  const int w = tid >> 5, lane = tid & 31;
  const unsigned ep = ld_relaxed(g_epoch + eb);
  const __nv_bfloat16 dsk = p.ssmd[cc.chan(min(lane, cc.n - 1))];
  if (cc.nb == 12) conv_tables(tid);
  if (cc.j < 0) bar_sync(12, 160); else bar_sync(0, 512);
  ConvTw t;
#pragma unroll
  for (int hh = 0; hh < 2; hh++) {
    const int n2 = 8 * hh + 2 * (lane & 3), m = 4 * (8 * w + (lane >> 2)) + 1;
    cx a = unit(n2 * m, 2048), b = unit((n2 + 1) * m, 2048);
    t.r[hh] = pack2(a.r, b.r); t.i[hh] = pack2(a.i, b.i); t.n[hh] = pack2(-a.i, -b.i);
  }
  const uint32_t tag = (ep + 1) & 3;
  const float dl = 0.125f * __bfloat162float(dsk);
  if (cc.j < 0) prep<1>(p, ti, pj, w, lane);
  {
    uint32_t P[4][2][2];
    mbar_wait_long(cc.inbar, 0);
    TIM(20);
    conv_step<true, false, 10>(P, t, cc, dl, tag, -1, w, lane);
#pragma unroll 1
    for (int ch = 0; ch < cc.n - 1; ch++) {
      conv_step<true, true, 20>(P, t, cc, dl, tag, ch, w, lane);
      if (cc.j < 0 && ch == 3) bar_arrive(0, 160);
      if (ch == 0) TIM(21);
    }
    conv_step<false, true, 30>(P, t, cc, dl, tag, cc.n - 1, w, lane);
  }
  TIM(22);
}

__device__ __forceinline__ cx csel(bool k, cx a, cx b) { return {k ? a.r : b.r, k ? a.i : b.i}; }
__device__ __forceinline__ void ld2cx(uint32_t a, cx& x, cx& y) {
  const uint4 v = lds128(a);
  x = {__uint_as_float(v.x), __uint_as_float(v.y)};
  y = {__uint_as_float(v.z), __uint_as_float(v.w)};
}
__device__ __forceinline__ cx ldcx(uint32_t a) {
  cx x;
  asm volatile("ld.shared.v2.f32 {%0,%1}, [%2];" : "=f"(x.r), "=f"(x.i) : "r"(a) : "memory");
  return x;
}

__device__ __forceinline__ void scan_epilogue(float (&aR)[64], float (&aI)[64], uint32_t last_empty, int ph, int ti, int pj, int tid) {
  const int w = tid >> 5, lane = tid & 31, r = lane >> 2, c = lane & 3;
  const uint32_t par = S_PAR + (ph * 64 + 16 * w + r) * 16;
  uint4* agg = g_agg + ph * 16 * 256 + pj * 32 + 8 * w + r;
  const uint32_t tag = (lds32(S_EP) + 1) & 3;
  cx h[2];
  {
    cx lam[2], a[2];
#pragma unroll
    for (int q = 0; q < 2; q++) { lam[q] = ldcx(par + q * 128); h[q] = ldcx(par + 2048 + q * 128); }
    WG_WAIT(0);
    if (elect_one()) mbar_arrive(last_empty);
    asm volatile("setmaxnreg.inc.sync.aligned.u32 168;");
    reg_fence(aR); reg_fence(aI);
    TIM(3 + ph * 2);
#pragma unroll
    for (int q = 0; q < 2; q++) a[q] = {aR[2 * q], aI[2 * q]};
#pragma unroll
    for (int s = 1; s < 32; s++)
#pragma unroll
      for (int q = 0; q < 2; q++) {
        const int i = 4 * (s >> 1) + 2 * q + (s & 1);
        a[q] = cfma(lam[q], a[q], {aR[i], aI[i]});
      }
    sched_fence<1>();
    cx t[2][3];
#pragma unroll
    for (int q = 0; q < 2; q++)
#pragma unroll
      for (int k = 0; k < 3; k++) t[q][k] = {__shfl_up_sync(~0u, a[q].r, k + 1, 4), __shfl_up_sync(~0u, a[q].i, k + 1, 4)};
#pragma unroll
    for (int q = 0; q < 2; q++) {
      const cx z = {0.f, 0.f};
      cx ex = cfma(h[q], csel(c >= 3, t[q][2], z), csel(c >= 2, t[q][1], z));
      ex = cfma(h[q], ex, csel(c >= 1, t[q][0], z));
      a[q] = cfma(h[q], ex, a[q]);
      const cx u = cfma(lam[q], ex, {aR[2 * q], aI[2 * q]});
      aR[2 * q] = u.r; aI[2 * q] = u.i;
    }
    if (c == 3)
      asm volatile("st.relaxed.gpu.global.v4.u32 [%0], {%1,%2,%3,%4};" ::"l"(agg + ti * 256),
                   "r"((__float_as_uint(a[0].r) & ~3u) | tag), "r"((__float_as_uint(a[0].i) & ~3u) | tag),
                   "r"((__float_as_uint(a[1].r) & ~3u) | tag), "r"((__float_as_uint(a[1].i) & ~3u) | tag) : "memory");
    TIM(8 + ph * 4);
  }
  if (ti > 0) {
    const uint2* ap = (const uint2*)(agg + (ti - 1 - (c >> 1)) * 256) + (c & 1);
    const int cnt = ti - (c >> 1);
    const cx one = {1.f, 0.f};
    const cx l128 = ldcx(par + 2048 + 8 + (c & 1) * 128), l256 = csq(l128), fa = csel(c & 2, l128, one);
#pragma unroll
    for (int q = 0; q < 2; q++) h[q] = cmul(csel(c & 1, h[q], one), csel(c & 2, csq(h[q]), one));
    uint2 v[8];
    int n = SPIN_LIMIT;
    bool bad;
    __nanosleep(AGG_NS);
    do {
      uint32_t x = 0;
#pragma unroll
      for (int j = 0; j < 8; j++) {
        v[j] = make_uint2(tag, tag);
        asm volatile("{.reg .pred p; setp.lt.s32 p, %3, %4; @p ld.relaxed.gpu.global.v2.u32 {%0,%1}, [%2];}"
                     : "+r"(v[j].x), "+r"(v[j].y) : "l"(ap - j * 1024), "r"(2 * j), "r"(cnt) : "memory");
      }
#pragma unroll
      for (int j = 0; j < 8; j++) { v[j].x ^= tag; v[j].y ^= tag; x |= v[j].x | v[j].y; }
      bad = __any_sync(~0u, x & 3);
    } while (bad && --n);
    trap_if(n == 0);
    cx a = {__uint_as_float(v[7].x), __uint_as_float(v[7].y)};
#pragma unroll
    for (int j = 6; j >= 0; j--) a = cfma(l256, a, {__uint_as_float(v[j].x), __uint_as_float(v[j].y)});
    a = cmul(a, fa);
    const cx t1 = {__shfl_xor_sync(~0u, a.r, 1), __shfl_xor_sync(~0u, a.i, 1)};
    const cx t2 = {__shfl_xor_sync(~0u, a.r, 2), __shfl_xor_sync(~0u, a.i, 2)};
    const cx t3 = {__shfl_xor_sync(~0u, a.r, 3), __shfl_xor_sync(~0u, a.i, 3)};
    const cx own = {a.r + t2.r, a.i + t2.i}, oth = {t1.r + t3.r, t1.i + t3.i};
#pragma unroll
    for (int q = 0; q < 2; q++) h[q] = cmul(csel((c & 1) == q, own, oth), h[q]);
  } else {
    h[0] = h[1] = {0.f, 0.f};
  }
  TIM(9 + ph * 4);
  cx lam[2];
  uint32_t cr[2], nci[2];
#pragma unroll
  for (int q = 0; q < 2; q++) {
    const uint4 v = lds128(par + q * 128);
    lam[q] = {__uint_as_float(v.x), __uint_as_float(v.y)};
    cr[q] = v.z; nci[q] = v.w;
  }
  uint4* hg = g_h + (size_t)(ti * 32 + ph * 16 + pj) * 1024 + w * 64 + r * 4 + (c ^ (r >> 1));
  const uint32_t hs = S_STG + w * 1024 + r * 64 + ((c ^ (r >> 1)) << 4);
  if (RE_EARLY) mbar_wait(B_SFREE + 16 * ph, 0);
  uint32_t pr[4][2][4], pi[4][2][4], re[4][2][4];
#pragma unroll
  for (int i = 0; i < 4; i++) {
#pragma unroll
    for (int s2 = 0; s2 < 4; s2++)
#pragma unroll
      for (int q = 0; q < 2; q++) {
        const int k = 4 * (4 * i + s2) + 2 * q;
        cx h0 = cfma(lam[q], h[q], {aR[k], aI[k]});
        h[q] = cfma(lam[q], h0, {aR[k + 1], aI[k + 1]});
        pr[i][q][s2] = pack2(h0.r, h[q].r);
        pi[i][q][s2] = pack2(h0.i, h[q].i);
        re[i][q][s2] = hfma2(pr[i][q][s2], cr[q], hmul2(pi[i][q][s2], nci[q]));
      }
#pragma unroll
    for (int q = 0; q < 2; q++) {
      stg128(hg + i * 256 + q * 32, re[i][q][0], re[i][q][1], re[i][q][2], re[i][q][3]);
      if (i < RE_EARLY) sts128(hs + i * 4096 + q * 512, re[i][q][0], re[i][q][1], re[i][q][2], re[i][q][3]);
    }
    if (i == 0 && (P2F & 1)) sched_fence<7>();
    if (i == 1 && (P2F & 2)) sched_fence<8>();
    if (i == 2 && (P2F & 1)) sched_fence<6>();
  }
  bar_arrive(9, 160);
  sched_fence<9>();
  TIM(10 + ph * 4);
  if (!RE_EARLY) mbar_wait(B_SFREE + 16 * ph, 0);
  if (ph == 0) mbar_wait(B_SFREE + 8, 0);
#pragma unroll
  for (int q = 0; q < 2; q++) {
    const uint32_t ncr = cr[q] ^ 0x80008000u;
#pragma unroll
    for (int i = 0; i < 4; i++) {
      uint32_t o[4];
#pragma unroll
      for (int s2 = 0; s2 < 4; s2++) o[s2] = hfma2(pi[i][q][s2], ncr, hmul2(pr[i][q][s2], nci[q]));
      if (i >= RE_EARLY) sts128(hs + i * 4096 + q * 512, re[i][q][0], re[i][q][1], re[i][q][2], re[i][q][3]);
      sts128(hs + 16384 + i * 4096 + q * 512, o[0], o[1], o[2], o[3]);
      if (IM_NS) __nanosleep(IM_NS);
      stg128(hg + 8192 + i * 256 + q * 32, o[0], o[1], o[2], o[3]);
    }
  }
  fence_async_smem();
  __syncwarp();
  if (elect_one()) mbar_arrive(B_LOC + 8 * ph);
  bar_arrive(10, 160);
  bar_sync(1 + ph, 128);
  asm volatile("setmaxnreg.dec.sync.aligned.u32 160;");
}

__device__ __forceinline__ constexpr uint32_t e_addr(int o, int mh) { return S_STG + (o * 2 + mh) * 2048; }
__device__ __forceinline__ uint32_t z_off(int w, int lane, int mh) {
  return (w & 1) * 2048 + (lane & 15) * 128 + (((4 * (lane >> 4) + 2 * mh + (w >> 1)) ^ (lane & 7)) << 4);
}
constexpr uint32_t S_ZL = sb + (59 % NS) * STAGE;
__device__ __forceinline__ void eterm(const Ptrs& p, int ti, int pj, int tid) {
  const int w = tid >> 5, lane = tid & 31, r = lane >> 2, c = lane & 3;
  const int trow = 64 * (w & 1) + 8 * (w >> 1) + r;
  const int rs = 2 * (r & 3) + (r >> 2);
  uint2 xv[2][8][2], ds[8];
  {
    uint2 gw[8];
#pragma unroll
    for (int jj = 0; jj < 8; jj++) {
      gw[jj] = ldg64(p.gw + pj * 128 + 16 * jj + 4 * c);
      ds[jj] = ldg64(p.dskip + pj * 128 + 16 * jj + 4 * c);
    }
#pragma unroll
    for (int g = 0; g < 2; g++) {
      mbar_wait(B_XT + 8 * g, 0);
#pragma unroll
      for (int i = 0; i < 4; i++)
#pragma unroll
        for (int jj = 4 * g; jj < 4 * g + 4; jj++)
          xv[i >> 1][jj][i & 1] = lds64(sb + ((48 + g) % NS) * STAGE + (trow - r + rs + 16 * (i >> 1) + 32 * (i & 1)) * 128 + (((2 * (jj & 3) + (c >> 1)) ^ rs) << 4) + (c & 1) * 8);
      fence_async_smem();
      __syncwarp();
      if (elect_one()) mbar_arrive(B_XT + 16 + 8 * g);
    }
    sched_fence<55>();
    TIM(27);
    float s[4];
#pragma unroll
    for (int i = 0; i < 4; i++) {
      s[i] = 0.f;
#pragma unroll
      for (int jj = 0; jj < 8; jj += 2) {
        const uint2 x = xv[i >> 1][jj][i & 1], y = xv[i >> 1][jj + 1][i & 1];
        const uint32_t q = hfma2(x.x, gw[jj].x, hfma2(x.y, gw[jj].y, hfma2(y.x, gw[jj + 1].x, hmul2(y.y, gw[jj + 1].y))));
        s[i] += bf_lo(q) + bf_hi(q);
      }
    }
    float u0 = (c & 1) ? s[1] : s[0], v0 = (c & 1) ? s[0] : s[1];
    float u1 = (c & 1) ? s[3] : s[2], v1 = (c & 1) ? s[2] : s[3];
    u0 += __shfl_xor_sync(~0u, v0, 1);
    u1 += __shfl_xor_sync(~0u, v1, 1);
    float u = (c & 2) ? u1 : u0;
    u += __shfl_xor_sync(~0u, (c & 2) ? u0 : u1, 2);
    const uint32_t tag = (lds32(S_EP) + 1) & 3;
    asm volatile("st.relaxed.gpu.global.u32 [%0], %1;" ::"l"(g_gate + pj * SEQ + ti * 128 + trow + 16 * (c >> 1) + 32 * (c & 1)),
                 "r"((__float_as_uint(u) & ~3u) | tag) : "memory");
    gate_finish(ti, tid, tag);
  }
  bar_sync(2, 128);
  TIM(31);
  uint32_t g2[2][2], og2[2][2];
#pragma unroll
  for (int mh = 0; mh < 2; mh++)
#pragma unroll
    for (int hf = 0; hf < 2; hf++) {
      uint32_t g;
      asm volatile("ld.shared.u32 %0, [%1];" : "=r"(g) : "r"(S_G + (trow + 16 * mh + 32 * hf) * 4) : "memory");
      g2[mh][hf] = __byte_perm(g, g, 0x3232);
      og2[mh][hf] = hsub2(0x3f803f80u, g2[mh][hf]);
    }
  mbar_wait_long(B_LOC + 16, 0);
#pragma unroll
  for (int o = 4; o < 8; o++) {
    const int jj = jj_of(o);
#pragma unroll
    for (int mh = 0; mh < 2; mh++) sts128(e_addr(o, mh) + tid * 16, xv[mh][jj][0].x, xv[mh][jj][0].y, xv[mh][jj][1].x, xv[mh][jj][1].y);
    if (tid < 4) asm volatile("st.shared.v2.u32 [%0], {%1,%2};" ::"r"(S_PAR + o * 32 + tid * 8), "r"(ds[jj].x), "r"(ds[jj].y) : "memory");
  }
  mbar_wait_long(B_ZT, 0);
#pragma unroll
  for (int mh = 0; mh < 2; mh++)
#pragma unroll
    for (int o = 0; o < 4; o++) {
      const int jj = jj_of(o);
      const uint4 z = ldsm4t(S_STG + o * 4096 + z_off(w, lane, mh));
#pragma unroll
      for (int hf = 0; hf < 2; hf++) {
        uint2& x = xv[mh][jj][hf];
        x.x = hmul2(x.x, hfma2(og2[mh][hf], hf ? z.z : z.x, hmul2(g2[mh][hf], ds[jj].x)));
        x.y = hmul2(x.y, hfma2(og2[mh][hf], hf ? z.w : z.y, hmul2(g2[mh][hf], ds[jj].y)));
      }
    }
  bar_sync(2, 128);
#pragma unroll
  for (int mh = 0; mh < 2; mh++)
#pragma unroll
    for (int o = 0; o < 4; o++) {
      const int jj = jj_of(o);
      sts128(e_addr(o, mh) + tid * 16, xv[mh][jj][0].x, xv[mh][jj][0].y, xv[mh][jj][1].x, xv[mh][jj][1].y);
    }
  bar_arrive(5, 256);
  TIM(1);
  const uint32_t tag = (lds32(S_EP) + 1) & 1;
  const int zn = tid >> 4, ck = tid & 15;
  const uint4* zp = g_z + (size_t)(pj * 128 + 4 * (zn >> 1) + (zn & 1)) * 256 + ti * 16 + ck;
  uint4 v[2][4];
#define ZLOAD(g) _Pragma("unroll") for (int i = 0; i < 4; i++) \
    asm volatile("ld.relaxed.gpu.global.v4.u32 {%0,%1,%2,%3}, [%4];" : "=r"(v[g][i].x), "=r"(v[g][i].y), "=r"(v[g][i].z), "=r"(v[g][i].w) \
                 : "l"(zp + (jj_of(4 + 2 * g + (i >> 1)) * 16 + 2 * (i & 1)) * 256) : "memory")
  mbar_wait_long(B_ZT + 8, 0);
  ZLOAD(0);
  ZLOAD(1);
#pragma unroll
  for (int g = 0; g < 2; g++) {
    int it = SPIN_LIMIT;
    while (true) {
      uint32_t x = 0;
#pragma unroll
      for (int i = 0; i < 4; i++) {
        v[g][i].x ^= tag; v[g][i].y ^= tag; v[g][i].z ^= tag; v[g][i].w ^= tag;
        x |= v[g][i].x | v[g][i].y | v[g][i].z | v[g][i].w;
      }
      if (!__any_sync(~0u, x & 1) || !--it) break;
      __nanosleep(ZL_NS);
      ZLOAD(g);
    }
    trap_if(it == 0);
#pragma unroll
    for (int i = 0; i < 4; i++)
      sts128(S_ZL + (2 * g + (i >> 1)) * 4096 + (ck >> 3) * 2048 + (8 * (i & 1) + zn) * 128 + (((ck & 7) ^ zn) << 4), v[g][i].x, v[g][i].y, v[g][i].z, v[g][i].w);
    bar_arrive(6 + g, 256);
    if (g == 0) TIM(23);
  }
#undef ZLOAD
  TIM(17);
}

__device__ __forceinline__ void store_late(float (&a)[64], float* op, int jj, const uint4& x, const uint4& z, const uint2& ds, float g0, float g1) {
#pragma unroll
  for (int hf = 0; hf < 2; hf++) {
    const float g = hf ? g1 : g0, og = bf_round(1.f - g);
    const uint32_t x0 = hf ? x.z : x.x, x1 = hf ? x.w : x.y, z0 = hf ? z.z : z.x, z1 = hf ? z.w : z.y;
    const int k = 8 * jj + 2 * hf;
    stg128(op + hf * 32 * DM + 16 * jj,
           __float_as_uint(fmaf(g, a[k], bf_lo(x0) * fmaf(og, bf_lo(z0), g * bf_lo(ds.x)))),
           __float_as_uint(fmaf(g, a[k + 1], bf_hi(x0) * fmaf(og, bf_hi(z0), g * bf_hi(ds.x)))),
           __float_as_uint(fmaf(g, a[k + 4], bf_lo(x1) * fmaf(og, bf_lo(z1), g * bf_lo(ds.y)))),
           __float_as_uint(fmaf(g, a[k + 5], bf_hi(x1) * fmaf(og, bf_hi(z1), g * bf_hi(ds.y)))));
  }
}
__device__ __forceinline__ void store_piece(float (&a)[64], float* op, int jj, const uint4& e, float g0, float g1) {
  stg128(op + 16 * jj, __float_as_uint(fmaf(g0, a[8 * jj], bf_lo(e.x))), __float_as_uint(fmaf(g0, a[8 * jj + 1], bf_hi(e.x))),
         __float_as_uint(fmaf(g0, a[8 * jj + 4], bf_lo(e.y))), __float_as_uint(fmaf(g0, a[8 * jj + 5], bf_hi(e.y))));
  stg128(op + 32 * DM + 16 * jj, __float_as_uint(fmaf(g1, a[8 * jj + 2], bf_lo(e.z))), __float_as_uint(fmaf(g1, a[8 * jj + 3], bf_hi(e.z))),
         __float_as_uint(fmaf(g1, a[8 * jj + 6], bf_lo(e.w))), __float_as_uint(fmaf(g1, a[8 * jj + 7], bf_hi(e.w))));
}

__device__ __forceinline__ void issue_g1(const Maps& m, int s, int sl, int ti, int pj) {
  const uint32_t bar = B_FULL + 8 * sl, dst = sb + sl * STAGE;
  const int k0 = (s & 15) * 64, ch = (s >> 4) * 512 + pj * 64;
  mbar_expect(bar, STAGE);
  tma4d(dst + 16384, &m.x, bar, k0, 0, 4 * ti, 0);
  tma2d(dst, &m.bre, bar, k0, ch);
  tma2d(dst + 8192, &m.bim, bar, k0, ch);
}
__device__ __forceinline__ void producer(const Maps& m, int ti, int pj) {
#pragma unroll
  for (int s = EARLY; s < NS; s++) issue_g1(m, s, s, ti, pj);
  int sl = 0, par = 0;
#pragma unroll 1
  for (int s = NS; s < 32; s++) {
    mbar_wait(B_EMPTY + 8 * sl, par);
    issue_g1(m, s, sl, ti, pj);
    if (++sl == NS) { sl = 0; par ^= 1; }
  }
#pragma unroll 1
  for (int q = 0; q < 32; q++) {
    mbar_wait(B_EMPTY + 8 * sl, par);
    const uint32_t bar = B_FULL + 8 * sl, dst = sb + sl * STAGE;
    const int ph = q >> 4, u = q & 15, part = u < 2 ? u : u >= 9, i = u - 2 - 7 * part;
    const int src = u < 2 ? pj : (MAP == 1 || MAP == 2) ? i + (i >= pj) : (i < 4 ? (~pj & 4) + i : (pj & 4) + i - 4 + (i - 4 >= (pj & 3)));
    if (q == 16 + NS || q == 17 + NS) mbar_wait(B_XT + 8 * (q - 14 - NS), 0);
    mbar_expect(bar, u < 2 ? 16384 : STAGE);
    tma5d(dst + 16384, part ? &m.cim : &m.cre, bar, ph * 512 + src * 64, 0, 0, 0, pj * 8);
    if (u < 2) {
      if (ph) {
        mbar_expect(B_XT + 8 * u, 16384);
        tma4d(dst, &m.x2, B_XT + 8 * u, pj * 128 + u * 64, 0, 0, ti * 16);
      }
    } else {
      if (i == 0) {
        mbar_wait(B_FLG + 8 * (2 * ph + part), 0);
        fence_async_global();
        if (part == 0 && ph == 0) TIM(24);
      }
      bulk_load(dst, g_h + (size_t)(ti * 32 + ph * 16 + part * 8 + src) * 1024, 16384, bar);
    }
    if (++sl == NS) { sl = 0; par ^= 1; }
  }
}

__device__ __forceinline__ void poller(int ti, int pj, int lane, unsigned ep) {
  if (lane < 5) {
    const int f = lane < 4 ? F_H + lane * 16 + ti : F_Z + pj;
    const unsigned need = (ep + 1) * (lane < 4 ? 8 : 16);
    int n = SPIN_LIMIT;
    bool done = false;
    do {
      if (!done && (int)(ld_relaxed(g_flag + f * 32) - need) >= 0) {
        done = true;
        asm volatile("fence.acquire.gpu;" ::: "memory");
        mbar_arrive(B_FLG + 8 * lane);
      }
      if (POLL_NS) __nanosleep(POLL_NS);
    } while (!__all_sync(0x1fu, done) && --n);
    trap_if(n == 0);
  }
}
__device__ __forceinline__ void storer(const Maps& m, int ti, int pj) {
#pragma unroll 1
  for (int job = 0; job < 6; job++) {
    bar_sync(job < 2 ? 4 + job : 9 + (job & 1), 160);
    if (elect_one()) flag_release(job < 2 ? F_U + pj * 2 + job : F_H + (job - 2) * 16 + ti);
    __syncwarp();
    if (job == 2 || job == 4) TIM(7 + job * 2);
  }
  if (elect_one()) {
    mbar_wait_long(B_LOC + 16, 0);
    mbar_wait_long(B_FLG + 32, 0);
    fence_async_global();
    mbar_expect(B_ZT, 16384);
#pragma unroll 1
    for (int o = 0; o < 4; o++) {
      tma5d(S_STG + o * 4096, &m.z, B_ZT, ti * 128, 0, 0, 0, pj * 8 + jj_of(o));
      tma5d(S_STG + o * 4096 + 2048, &m.z, B_ZT, ti * 128 + 64, 0, 0, 0, pj * 8 + jj_of(o));
    }
  }
}

__device__ __forceinline__ void kv_loader(const Maps& m, int ti, int pj, unsigned t_start) {
  unsigned tt = t_start + KV0_AT;
#pragma unroll 1
  for (int st = 0; st < 4; st++) {
    const int d = pj * 128 + (st >> 1) * 64, tb = ti * 16 + (st & 1) * 8;
    const uint32_t bar = B_PIN + 8 * st;
    if (st >= 2) { bar_sync(st == 2 ? 3 : 11, 160); fence_async_smem(); }
    if (elect_one()) {
      mbar_expect(bar, 16384 + 384);
      if (st == 2) tt = t_start + KV1_AT;
      if ((int)(clock() - tt) > 0) tt = clock();
#pragma unroll 1
      for (int i = 0; i < 4; i++) {
        wait_clock(tt);
        tt += st >= 2 ? KV_GAP1 : KV_GAP0;
        tma3d(S_STG + (st & 1) * 16384 + i * 4096, (i & 2) ? &m.v : &m.k, bar, d, tb, (i & 1) * 4);
        if (i == 0) tma3d(S_T + st * 512, &m.kh, bar, d, tb - 1, 5);
      }
    }
    tt = __shfl_sync(~0u, tt, 0);
  }
}

__device__ __forceinline__ void conv_loader(const Maps& m, const Ptrs& p, const ConvCtx& cc, int eb, int lane, unsigned t_start) {
  const unsigned ep = ld_relaxed(g_epoch + eb);
  wait_clock(t_start + SPF_AT);
#pragma unroll 1
  for (int ch = 0; ch < cc.n; ch++) {
    const int d = cc.chan(ch);
    const uint32_t bar = cc.inbar + 8 * (ch & 1), dst = cc.buf + (ch & 1) * 8192;
    const bool first = ch == 0 || ch == (cc.j < 0 ? 3 : 1);
    if (ch >= 2) bar_sync(cc.nb + 2 + (ch & 1), 160);
    if (elect_one()) {
      mbar_expect(cc.inbar + 16, 4096);
      bulk_load(dst + 4096, p.f + (size_t)d * SEQ, 4096, cc.inbar + 16);
      if (!first) { mbar_expect(bar, 4096); tma3d(dst, &m.u, bar, 0, d & 31, d & ~31); }
      if (ch + 1 < cc.n) l2_prefetch(p.f + (size_t)cc.chan(ch + 1) * SEQ, 4096);
    }
    __syncwarp();
    const uint32_t a = dst + 4096 + 128 + (lane >> 3) * 256 + (lane & 7) * 16;
    mbar_wait(cc.inbar + 16, ch & 1);
#pragma unroll 1
    for (uint32_t i = a; i < a + 4096; i += 2048) {
      const uint4 x = lds128(i), y = lds128(i + 1024);
      __syncwarp();
      sts128(i ^ 16, x.x, x.y, x.z, x.w);
      sts128((i ^ 16) + 1024, y.x, y.y, y.z, y.w);
    }
    fence_async_smem();
    __syncwarp();
    if (elect_one()) {
      mbar_arrive(bar);
      if (first) {
        int n = SPIN_LIMIT;
        while ((int)(ld_relaxed(g_flag + (F_U + (d >> 6)) * 32) - (ep + 1) * 16) < 0 && --n) __nanosleep(POLL_NS);
        trap_if(n == 0);
        asm volatile("fence.acquire.gpu;" ::: "memory");
        fence_async_global();
        mbar_expect(bar, 4096);
        tma3d(dst, &m.u, bar, 0, d & 31, d & ~31);
      }
    }
    __syncwarp();
    if (cc.j < 0 && ch == 6) {
      bar_sync(0, 160);
      if (elect_one()) flag_release(F_Z + cc.pj);
      __syncwarp();
    }
  }
  if (cc.j >= 0 && lane == 0) g_epoch[eb] = ep + 1;
}

struct Ring { uint32_t off, par, rel; };
__device__ __forceinline__ void desc_touch(const uint64_t (&c)[12][NS]) {
  uint32_t x = 0;
#pragma unroll
  for (int i = 0; i < 12 * NS; i += 4) x |= (uint32_t)(&c[0][0])[i];
  trap_if((x | (uint32_t)c[11][NS - 1]) == 0);
}
template <int TA, bool TAB, bool LOC = false>
__device__ __forceinline__ void gemm_steps(float (&a0)[64], float (&a1)[64], Ring& r, int n, const uint64_t (&c)[12][NS], int slot) {
#pragma unroll 1
  do {
    const uint32_t off = r.off, rel = r.rel;
    full_wait(B_FULL + off, r.par, slot++);
    r.rel = off;
    r.off += 8;
    if (r.off == 8 * NS) { r.off = 0; r.par ^= 1; }
    WG_FENCE();
#define DESC(i) (*(const uint64_t*)((const char*)c[i] + off))
#pragma unroll
    for (int k = 0; k < 4; k++) {
      const uint64_t db = TAB ? DESC(3 * k) : mkdesc(off * 256 + dlo(sb + 16384 + 32 * k, 16), 1024, 1);
      if (LOC) {
        const int acc = k || rel != B_DUMMY - B_EMPTY;
        wgmma_ss128p<TA>(a0, mkdesc(dlo(S_STG + 32768 + 1024 * k, 4096) - n * 1024, 512, 2), db, acc);
        wgmma_ss128p<TA>(a1, mkdesc(dlo(S_STG + 32768 + 8192 + 1024 * k, 4096) - n * 1024, 512, 2), db, acc);
      } else {
        wgmma_ss128<TA, 0, 1>(a0, TAB ? DESC(3 * k + 1) : mkdesc(off * 256 + dlo(sb + 32 * k, 16), 1024, 1), db);
        wgmma_ss128<TA, 0, 1>(a1, TAB ? DESC(3 * k + 2) : mkdesc(off * 256 + dlo(sb + 8192 + 32 * k, 16), 1024, 1), db);
      }
      if (k == RELK) {
        WG_COMMIT();
        WG_WAIT(1);
        if (elect_one()) mbar_arrive(B_EMPTY + rel);
      }
    }
#undef DESC
    if (RELK < 3) WG_COMMIT();
  } while (--n);
}

template <int I>
__device__ __forceinline__ void tail_steps(float (&a0)[64], float (&a1)[64], const Ptrs& p, float* op, const float (&g)[4], uint4& e, uint4& e0, int tid) {
  constexpr int sl = (64 - WIN + I / 2) % NS, k = 2 * (I & 1), J = I - TOFF;
  if (I == 0) WG_FENCE();
  wgmma_ss128<1, 0, 1>(a1, p.dc2[3 * k + 2][sl], p.dc2[3 * k][sl]);
  wgmma_ss128<1, 0, 1>(a1, p.dc2[3 * k + 5][sl], p.dc2[3 * k + 3][sl]);
  WG_COMMIT();
  if (J == 0) { WG_WAIT(TOFF + 1); reg_fence(a0); }
  if (RES == NS && I == (WIN == NS ? 3 : 0)) { WG_WAIT(WIN == NS ? 2 : 1); if (elect_one()) mbar_arrive(B_ZT + 8); }
  if (J >= 0 && J < 2 * NPB) {
    sched_fence_async<70 + 2 * I>();
    constexpr int o = J >= 0 ? J / 2 : 0, jj = jj_of(o), hf = J & 1;
    if (hf == 0) { e0 = e; e = lds128(e_addr(o + 1 < NPB ? o + 1 : 0, o + 1 == NPB) + tid * 16); }
    const uint32_t ex = hf ? e0.z : e0.x, ey = hf ? e0.w : e0.y;
    stg128(op + hf * 32 * DM + 16 * jj, __float_as_uint(fmaf(g[hf], a0[8 * jj + 2 * hf], bf_lo(ex))), __float_as_uint(fmaf(g[hf], a0[8 * jj + 2 * hf + 1], bf_hi(ex))),
           __float_as_uint(fmaf(g[hf], a0[8 * jj + 2 * hf + 4], bf_lo(ey))), __float_as_uint(fmaf(g[hf], a0[8 * jj + 2 * hf + 5], bf_hi(ey))));
    sched_fence_async<71 + 2 * I>();
  }
  if constexpr (I + 1 < 2 * WIN) tail_steps<I + 1>(a0, a1, p, op, g, e, e0, tid);
}

__global__ void __launch_bounds__(512, 1) fused_kernel(const __grid_constant__ Maps m, const __grid_constant__ Ptrs p) {
  extern __shared__ __align__(1024) uint8_t smem_raw[];
  int b = blockIdx.x;
  {
    int sm, nsm;
    asm volatile("mov.u32 %0, %%smid;" : "=r"(sm));
    asm volatile("mov.u32 %0, %%nsmid;" : "=r"(nsm));
    const int tp = sm >> 1, q = ((tp - 32) * 37) >> 8;
    const int g = tp < 32 ? tp & 7 : (tp < 60 ? tp - 31 - 7 * q : (tp < 62 ? 8 : 0));
    const int j = tp < 32 ? tp >> 3 : (tp < 60 ? 4 + q : (tp < 62 ? tp - 60 : tp - 58));
    if (nsm == 132) b = g * 16 + j * 2 + (sm & 1);
    b = __shfl_sync(~0u, b, 0);
  }
  const int spare = b - 128;
  const int ti = ((b >> 5) << 2) | (b & 3), pj = (((b >> 4) & 1) << 2) | ((b >> 2) & 3);
  const int wid = __shfl_sync(~0u, threadIdx.x >> 5, 0), wg = wid >> 2, tid = threadIdx.x & 127, lane = threadIdx.x & 31;
  if (wg == 0) TIM(0);
  const unsigned t_start = clock();
  if (wid == 12) {
    if (elect_one()) {
      asm volatile("prefetch.tensormap [%0];" ::"l"(&m.x) : "memory");
      asm volatile("prefetch.tensormap [%0];" ::"l"(&m.bre) : "memory");
      asm volatile("prefetch.tensormap [%0];" ::"l"(&m.bim) : "memory");
#pragma unroll
      for (int i = 0; i < NS; i++) mbar_init(B_FULL + 8 * i, (i < 2 && spare >= 0) ? 2 : 1);
      fence_async_smem();
#pragma unroll
      for (int s = 0; s < EARLY; s++) if (spare < 0) issue_g1(m, s, s, ti, pj);
    }
  } else if (wid == 13) {
    if (elect_one()) {
      trap_if((uint32_t)__cvta_generic_to_shared(smem_raw) != sb);
#pragma unroll
      for (uint32_t bar = B_EMPTY; bar < S_EP; bar += 8) mbar_init(bar, (bar < B_CINF || (bar >= B_SFREE && bar < B_ZT) || bar == B_ZT + 8 || bar == B_XT + 16 || bar == B_XT + 24) ? 4 :
                           (bar < B_CINF + 16 || ((bar == B_PIN || bar == B_PIN + 8) && spare >= 0)) ? 2 : 1);
      fence_async_smem();
    }
  }
  __syncwarp();
  if (wg == 3) {
    asm volatile("setmaxnreg.dec.sync.aligned.u32 %0;" ::"n"(RV == 2 ? 32 : 24));
    bar_sync(1, 128);
    if (spare < 0) {
      if (wid == 13) { bar_arrive(2, 160); bar_arrive(12, 160); }
      bar_arrive(0, 256);
    } else {
      bar_arrive(0, 512);
    }
    if (wid == 13) {
      if (spare < 0) {
        const unsigned ep = ld_relaxed(g_epoch + b);
        kv_loader(m, ti, pj, t_start);
        poller(ti, pj, lane, ep);
      }
    } else if (wid == 15 || spare >= 0) {
      const ConvCtx cc = conv_ctx(spare, wid == 12 ? 0 : wid - 13, ti, pj);
      conv_loader(m, p, cc, spare < 0 ? b : 128 + cc.j, lane, t_start);
    } else if (wid == 12) {
      if (elect_one()) producer(m, ti, pj);
    } else {
      storer(m, ti, pj);
    }
  } else if (wg == 2 || spare >= 0) {
    asm volatile("setmaxnreg.inc.sync.aligned.u32 160;");
    conv_main(p, conv_ctx(spare, wg, ti, pj), spare < 0 ? b : 128 + spare * 3 + wg, tid);
  } else {
    asm volatile("setmaxnreg.inc.sync.aligned.u32 %0;" ::"n"(RV == 3 ? 168 : 160));
    if (wg == 1) {
      const int ch = (tid >> 6) * 512 + pj * 64 + (tid & 63);
      const unsigned ep = ld_relaxed(g_epoch + b);
      const float lr = __bfloat162float(p.lre[ch]), li = __bfloat162float(p.lim[ch]);
      const float dt = bf_round(expf(__bfloat162float(p.ldt[ch])));
      float sn, cs;
      sincosf(dt * li, &sn, &cs);
      const float ex = expf(dt * lr);
      const float ar = ex * cs, ai = ex * sn;
      const float inv = 2.f / (lr * lr + li * li);
      const float cr = ((ar - 1.f) * lr + ai * li) * inv, ci = (ai * lr - (ar - 1.f) * li) * inv;
      sts128(S_PAR + tid * 16, __float_as_uint(ar), __float_as_uint(ai), pack2(cr, cr), pack2(-ci, -ci));
      const cx l32 = csq(csq(csq(csq(csq({ar, ai}))))), l128 = csq(csq(l32));
      sts128(S_PAR + 2048 + tid * 16, __float_as_uint(l32.r), __float_as_uint(l32.i), __float_as_uint(l128.r), __float_as_uint(l128.i));
      if (tid == 0) asm volatile("st.shared.u32 [%0], %1;" ::"r"(S_EP), "r"(ep) : "memory");
      bar_arrive(6, 256);
      bar_sync(2, 160);
      desc_touch(p.dc1);
      desc_touch(p.dc2);
      prep<0>(p, ti, pj, wid & 3, lane);
    }
    float a0[64], a1[64];
    Ring ring = {8u * wg * (16 % NS), wg * ((16u / NS) & 1), B_DUMMY - B_EMPTY};
    zero(a0); zero(a1);
    reg_fence(a0); reg_fence(a1);
    sched_fence<61>();
    bar_sync(wg * 7, 256);
    TIM(2 + wg * 2);
    if (wg == 0) gemm_steps<0, false>(a0, a1, ring, 15, p.dc1, 0);
    else gemm_steps<0, true>(a0, a1, ring, 15, p.dc1, 16);
    bar_arrive(7 + wg, 256);
    gemm_steps<0, false>(a0, a1, ring, 1, p.dc1, wg * 16 + 15);
    if (wg == 0) bar_sync(6, 256);
    scan_epilogue(a0, a1, B_EMPTY + ring.rel, wg, ti, pj, tid);
    if (wg == 1) {
      eterm(p, ti, pj, tid);
    } else {
      ring = {8 * (32 % NS), (32 / NS) & 1, B_DUMMY - B_EMPTY};
#pragma unroll
      for (int i = 0; i < 64; i++) asm volatile("" : "=f"(a0[i]), "=f"(a1[i]));
      bar_sync(8, 256);
      TIM(6);
#pragma unroll 1
      for (int o = 0; o < 4; o++) {
        if (!(o & 1)) {
          if (o) TIM(18);
          full_wait(B_LOC + 4 * o, 0, 32 + 8 * o);
          gemm_steps<1, true, true>(a0, a1, ring, 2, p.dc2, 32 + 8 * o);
        }
        gemm_steps<1, true>(a0, a1, ring, (o & 1) ? (o == 1 ? 13 : 13 - RES) : 1, p.dc2, 34 + 16 * (o >> 1) + (o & 1));
        if (!(o & 1) && elect_one()) {
          mbar_arrive(o ? B_LOC + 16 : B_SFREE + 16);
        }
      }
      TIM(28);
      const int w = tid >> 5, trow = 64 * (w & 1) + 8 * (w >> 1) + (lane >> 2);
      float* op = p.out + (size_t)(ti * 128 + trow) * DM + pj * 128 + 4 * (lane & 3);
      float g[4];
      uint4 e;
#pragma unroll
      for (int i = 0; i < RES; i++) {
        const int sl = (64 - RES + i) % NS;
        full_wait(B_FULL + 8 * sl, ((64 - RES + i) / NS) & 1, 64 - RES + i);
        WG_FENCE();
#pragma unroll
        for (int k = 0; k < 4; k++) {
          wgmma_ss128<1, 0, 1>(a0, p.dc2[3 * k + 1][sl], p.dc2[3 * k][sl]);
          if (i == 0 && k == 1) { WG_COMMIT(); WG_WAIT(1); if (elect_one()) mbar_arrive(RES == NS ? B_EMPTY + ring.rel : B_ZT + 8); }
        }
        if (i >= WIN - 1 && i < RES - 1) {
          const int s1 = (64 - RES + i - WIN + 1) % NS;
#pragma unroll
          for (int k = 0; k < 4; k++) wgmma_ss128<1, 0, 1>(a1, p.dc2[3 * k + 2][s1], p.dc2[3 * k][s1]);
        }
        WG_COMMIT();
      }
      TIM(25);
      bar_sync(5, 256);
#pragma unroll
      for (int q = 0; q < 4; q++) g[q] = __uint_as_float(lds32(S_G + (trow + 16 * (q >> 1) + 32 * (q & 1)) * 4));
      e = lds128(e_addr(0, NPB == 0) + tid * 16);
      uint4 e0;
      tail_steps<0>(a0, a1, p, op, g, e, e0, tid);
      TIM(26);
      WG_WAIT(0);
      reg_fence(a1);
      TIM(7);
      uint4 ee[4], x[8], z[8];
      uint2 ds[4];
#pragma unroll
      for (int o = 1; o < 4; o++) ee[o] = lds128(e_addr(o, 1) + tid * 16);
      if (NPB < 4) ee[0] = lds128(e_addr(3, 0) + tid * 16);
      store_piece(a1, op + 16 * DM, jj_of(0), e, g[2], g[3]);
      store_piece(a1, op + 16 * DM, jj_of(1), ee[1], g[2], g[3]);
#define LATE_LOAD(h) { \
        sched_fence<90 + h>(); \
        bar_sync(6 + h, 256); \
        _Pragma("unroll") for (int i = 4 * h; i < 4 * h + 4; i++) { \
          x[i] = lds128(e_addr(4 + (i >> 1), i & 1) + tid * 16); \
          z[i] = ldsm4t(S_ZL + (i >> 1) * 4096 + z_off(w, lane, i & 1)); \
          if (i & 1) ds[i >> 1] = lds64(S_PAR + (4 + (i >> 1)) * 32 + (lane & 3) * 8); \
        } }
#define LATE_STORE(o) { store_late(a0, op, jj_of(4 + o), x[2 * o], z[2 * o], ds[o], g[0], g[1]); \
                        store_late(a1, op + 16 * DM, jj_of(4 + o), x[2 * o + 1], z[2 * o + 1], ds[o], g[2], g[3]); }
      LATE_LOAD(0);
      store_piece(a1, op + 16 * DM, jj_of(2), ee[2], g[2], g[3]);
      store_piece(a1, op + 16 * DM, jj_of(3), ee[3], g[2], g[3]);
      if (NPB < 4) store_piece(a0, op, jj_of(3), ee[0], g[0], g[1]);
      LATE_STORE(0);
      LATE_LOAD(1);
      LATE_STORE(1);
      sched_fence<92>();
      LATE_STORE(2);
      LATE_STORE(3);
#undef LATE_LOAD
#undef LATE_STORE
      if (tid == 0) g_epoch[b] = lds32(S_EP) + 1;
      TIM(19);
    }
  }
}

typedef CUresult (*EncFn)(CUtensorMap*, CUtensorMapDataType, cuuint32_t, void*, const cuuint64_t*, const cuuint64_t*,
                          const cuuint32_t*, const cuuint32_t*, CUtensorMapInterleave, CUtensorMapSwizzle,
                          CUtensorMapL2promotion, CUtensorMapFloatOOBfill);

void encode(EncFn enc, CUtensorMap* m, const void* ptr, int rank, const cuuint64_t* dims, const cuuint64_t* strides,
            const cuuint32_t* box, CUtensorMapSwizzle sw) {
  cuuint32_t es[5] = {1, 1, 1, 1, 1};
  enc(m, CU_TENSOR_MAP_DATA_TYPE_BFLOAT16, rank, const_cast<void*>(ptr), dims, strides, box, es, CU_TENSOR_MAP_INTERLEAVE_NONE,
      sw, PROMO, CU_TENSOR_MAP_FLOAT_OOB_FILL_NONE);
}

}

extern "C" void kernel_launch(void* const* d_in, const int* in_sizes, int n_in, void* d_out, int out_size) {
  typedef const __nv_bfloat16* bp;
  Ptrs p;
  p.x = (bp)d_in[0]; p.lre = (bp)d_in[1]; p.lim = (bp)d_in[2]; p.bre = (bp)d_in[3]; p.bim = (bp)d_in[4];
  p.cre = (bp)d_in[5]; p.cim = (bp)d_in[6]; p.ldt = (bp)d_in[7]; p.dskip = (bp)d_in[8];
  p.k = (bp)d_in[10]; p.v = (bp)d_in[11]; p.shift = (bp)d_in[12]; p.f = (bp)d_in[13]; p.ssmd = (bp)d_in[14];
  p.gw = (bp)d_in[15]; p.out = (float*)d_out;

  for (int sl = 0; sl < NS; sl++)
    for (int k = 0; k < 4; k++) {
      const uint64_t h128 = (uint64_t)(64u | (1u << 30)) << 32, h64 = (uint64_t)(32u | (2u << 30)) << 32;
      const uint32_t st = sb + sl * STAGE;
      p.dc1[3 * k][sl] = p.dc2[3 * k][sl] = h128 | dlo(st + 16384 + 32 * k, 16);
      p.dc1[3 * k + 1][sl] = h128 | dlo(st + 32 * k, 16);
      p.dc1[3 * k + 2][sl] = h128 | dlo(st + 8192 + 32 * k, 16);
      p.dc2[3 * k + 1][sl] = h64 | dlo(st + 1024 * k, 4096);
      p.dc2[3 * k + 2][sl] = h64 | dlo(st + 8192 + 1024 * k, 4096);
    }
  EncFn enc = nullptr;
  cudaDriverEntryPointQueryResult qr;
  cudaGetDriverEntryPoint("cuTensorMapEncodeTiled", (void**)&enc, cudaEnableDefault, &qr);
  void *zptr = nullptr, *uptr = nullptr;
  cudaGetSymbolAddress(&zptr, g_z);
  cudaGetSymbolAddress(&uptr, g_u);

  Maps m;
  {
    cuuint64_t d[4] = {1024, 2, 64, 16}, s[3] = {2048, 65536, 4096};
    cuuint32_t bx[4] = {64, 2, 4, 16};
    encode(enc, &m.x, p.x, 4, d, s, bx, CU_TENSOR_MAP_SWIZZLE_128B);
  }
  {
    cuuint64_t d[2] = {1024, 1024}, s[1] = {2048};
    cuuint32_t bx[2] = {64, 64};
    encode(enc, &m.bre, p.bre, 2, d, s, bx, CU_TENSOR_MAP_SWIZZLE_128B);
    encode(enc, &m.bim, p.bim, 2, d, s, bx, CU_TENSOR_MAP_SWIZZLE_128B);
  }
  {
    cuuint64_t d[5] = {1024, 2, 4, 2, 64}, s[4] = {2048, 8192, 4096, 32768};
    cuuint32_t bx[5] = {64, 2, 4, 2, 8};
    encode(enc, &m.cre, p.cre, 5, d, s, bx, CU_TENSOR_MAP_SWIZZLE_128B);
    encode(enc, &m.cim, p.cim, 5, d, s, bx, CU_TENSOR_MAP_SWIZZLE_128B);
  }
  {
    cuuint64_t d[3] = {64, 32, 1024}, s[2] = {128, 4096};
    cuuint32_t bx[3] = {64, 1, 32};
    encode(enc, &m.u, uptr, 3, d, s, bx, CU_TENSOR_MAP_SWIZZLE_NONE);
  }
  {
    cuuint64_t d[3] = {1024, 256, 8}, s[2] = {16384, 2048};
    cuuint32_t bx[3] = {64, 8, 4}, bh[3] = {64, 1, 3};
    encode(enc, &m.k, p.k, 3, d, s, bx, CU_TENSOR_MAP_SWIZZLE_128B);
    encode(enc, &m.kh, p.k, 3, d, s, bh, CU_TENSOR_MAP_SWIZZLE_NONE);
    encode(enc, &m.v, p.v, 3, d, s, bx, CU_TENSOR_MAP_SWIZZLE_128B);
  }
  {
    cuuint64_t d[5] = {2048, 2, 4, 2, 64}, s[4] = {4096, 16384, 8192, 65536};
    cuuint32_t bx[5] = {64, 2, 4, 2, 1};
    encode(enc, &m.z, zptr, 5, d, s, bx, CU_TENSOR_MAP_SWIZZLE_128B);
  }
  {
    cuuint64_t d[4] = {1024, 2, 4, 256}, s[3] = {8192, 2048, 16384};
    cuuint32_t bx[4] = {64, 2, 4, 16};
    encode(enc, &m.x2, p.x, 4, d, s, bx, CU_TENSOR_MAP_SWIZZLE_128B);
  }
  cudaFuncSetAttribute(fused_kernel, cudaFuncAttributeMaxDynamicSharedMemorySize, SMEM_BYTES);
  fused_kernel<<<132, 512, SMEM_BYTES, cudaStreamPerThread>>>(m, p);
}
```

```cpp
#include <cuda_runtime.h>
#include <cuda_bf16.h>
#include <cuda.h>
#include <stdint.h>

namespace {

constexpr int SEQ = 2048, DM = 1024;
#define NSV 5
constexpr int NS = NSV;
constexpr int STAGE = 32768;
#define KV0_AT 300
#define KV_GAP0 600
#define KV1_AT 8200
#define KV_GAP1 450
#define SFM 2
#define RV 1
#define POLL_NS 60
#define IM_NS 40
#define SPF_AT 7000
#define RELK 0
#define RES 4
#define AGG_NS 200
#define ZL_NS 60
#define P2F 3
#define KEEP 16
#define RE_EARLY 0
#define MAP 0
#define WIN 4
#define NPB 3
#define TOFF 1
#define W0 8
#define HOLD 1200
#define FILL 450
#define LD_GAP 400
#define LDQ ""
#define PROMO CU_TENSOR_MAP_L2_PROMOTION_L2_128B
constexpr uint32_t sb = 1024;
constexpr uint32_t S_STG = sb + NS * STAGE;
constexpr uint32_t S_CIN = S_STG + 32768;
constexpr uint32_t S_T = S_CIN + 16384;
constexpr uint32_t S_M1 = S_T + 8192;
constexpr uint32_t S_M2 = S_M1 + 4096;
constexpr uint32_t S_PAR = S_M2 + 2048;
constexpr uint32_t S_G = S_PAR + 4096;
constexpr uint32_t S_BAR = S_G + 512;
constexpr int SMEM_BYTES = S_BAR + 512 - sb;
constexpr uint32_t B_FULL = S_BAR, B_EMPTY = B_FULL + 8 * NS, B_CINF = B_EMPTY + 8 * NS,
                   B_FLG = B_CINF + 24, B_SFREE = B_FLG + 40, B_LOC = B_SFREE + 24, B_ZT = B_LOC + 24,
                   B_XT = B_ZT + 16, B_PIN = B_XT + 32, B_DUMMY = B_PIN + 32, S_EP = B_DUMMY + 8;
constexpr int SPIN_LIMIT = 1 << 21;
constexpr int F_H = 0, F_U = 64, F_Z = 80;

struct alignas(64) Maps { CUtensorMap x, bre, bim, cre, cim, u, z, x2, k, kh, v; };
struct Ptrs {
  const __nv_bfloat16 *x, *lre, *lim, *ldt, *dskip, *k, *v, *shift, *f, *ssmd, *gw, *bre, *bim, *cre, *cim;
  float* out;
  uint64_t dc1[12][NS], dc2[12][NS];
};

__device__ uint4 g_h[16 * 32 * 1024];
__device__ uint4 g_u[1024 * 256];
__device__ uint4 g_z[1024 * 256];
__device__ uint4 g_agg[2 * 16 * 256];
__device__ unsigned g_gate[8 * SEQ];
__device__ unsigned g_flag[88 * 32];
__device__ unsigned g_epoch[140];
#define TIM(i)
#define TIMC(i)

#define WG_FENCE() asm volatile("wgmma.fence.sync.aligned;" ::: "memory")
#define WG_COMMIT() asm volatile("wgmma.commit_group.sync.aligned;" ::: "memory")
#define WG_WAIT(n) asm volatile("wgmma.wait_group.sync.aligned %0;" ::"n"(n) : "memory")
#define R8(d, o) "+f"(d[o + 0]), "+f"(d[o + 1]), "+f"(d[o + 2]), "+f"(d[o + 3]), "+f"(d[o + 4]), "+f"(d[o + 5]), "+f"(d[o + 6]), "+f"(d[o + 7])
#define W8(d, o) "=f"(d[o + 0]), "=f"(d[o + 1]), "=f"(d[o + 2]), "=f"(d[o + 3]), "=f"(d[o + 4]), "=f"(d[o + 5]), "=f"(d[o + 6]), "=f"(d[o + 7])
#define L16 "%0,%1,%2,%3,%4,%5,%6,%7,%8,%9,%10,%11,%12,%13,%14,%15"
#define L64 L16 ",%16,%17,%18,%19,%20,%21,%22,%23,%24,%25,%26,%27,%28,%29,%30,%31," \
  "%32,%33,%34,%35,%36,%37,%38,%39,%40,%41,%42,%43,%44,%45,%46,%47,%48,%49,%50,%51,%52,%53,%54,%55,%56,%57,%58,%59,%60,%61,%62,%63"

template <int TA, int TB, int ACC>
__device__ __forceinline__ void wgmma_ss128(float (&d)[64], uint64_t da, uint64_t db) {
  if (ACC)
    asm volatile("wgmma.mma_async.sync.aligned.m64n128k16.f32.bf16.bf16 {" L64 "}, %64, %65, 1, 1, 1, %66, %67;"
                 : R8(d, 0), R8(d, 8), R8(d, 16), R8(d, 24), R8(d, 32), R8(d, 40), R8(d, 48), R8(d, 56)
                 : "l"(da), "l"(db), "n"(TA), "n"(TB));
  else
    asm volatile("wgmma.mma_async.sync.aligned.m64n128k16.f32.bf16.bf16 {" L64 "}, %64, %65, 0, 1, 1, %66, %67;"
                 : W8(d, 0), W8(d, 8), W8(d, 16), W8(d, 24), W8(d, 32), W8(d, 40), W8(d, 48), W8(d, 56)
                 : "l"(da), "l"(db), "n"(TA), "n"(TB));
}
template <int TA>
__device__ __forceinline__ void wgmma_ss128p(float (&d)[64], uint64_t da, uint64_t db, int acc) {
  asm volatile("{.reg .pred p; setp.ne.b32 p, %67, 0;\n"
               "wgmma.mma_async.sync.aligned.m64n128k16.f32.bf16.bf16 {" L64 "}, %64, %65, p, 1, 1, %66, 0;}"
               : R8(d, 0), R8(d, 8), R8(d, 16), R8(d, 24), R8(d, 32), R8(d, 40), R8(d, 48), R8(d, 56)
               : "l"(da), "l"(db), "n"(TA), "r"(acc));
}
template <int ACC, int TB = 0>
__device__ __forceinline__ void wgmma_rs32(float (&d)[16], uint32_t a0, uint32_t a1, uint32_t a2, uint32_t a3, uint64_t db) {
  if (ACC)
    asm volatile("wgmma.mma_async.sync.aligned.m64n32k16.f32.bf16.bf16 {" L16 "}, {%16,%17,%18,%19}, %20, 1, 1, 1, %21;"
                 : R8(d, 0), R8(d, 8) : "r"(a0), "r"(a1), "r"(a2), "r"(a3), "l"(db), "n"(TB));
  else
    asm volatile("wgmma.mma_async.sync.aligned.m64n32k16.f32.bf16.bf16 {" L16 "}, {%16,%17,%18,%19}, %20, 0, 1, 1, %21;"
                 : W8(d, 0), W8(d, 8) : "r"(a0), "r"(a1), "r"(a2), "r"(a3), "l"(db), "n"(TB));
}
template <int N>
__device__ __forceinline__ void reg_fence(float (&d)[N]) {
#pragma unroll
  for (int i = 0; i < N; i++) asm volatile("" : "+f"(d[i])::"memory");
}
__host__ __device__ __forceinline__ constexpr uint32_t dlo(uint32_t addr, uint32_t lbo) { return (addr >> 4) + ((lbo >> 4) << 16); }
__device__ __forceinline__ uint64_t mkdesc(uint32_t lo, uint32_t sbo, uint32_t mode) {
  uint64_t d;
  asm("mov.b64 %0, {%1, %2};" : "=l"(d) : "r"(lo), "r"((sbo >> 4) | (mode << 30)));
  return d;
}
template <int N>
__device__ __forceinline__ void zero(float (&d)[N]) {
#pragma unroll
  for (int i = 0; i < N; i++) d[i] = 0.f;
}
__device__ __forceinline__ void trap_if(int c) {
  asm volatile("{.reg .pred p; .reg .b64 z; setp.ne.s32 p, %0, 0; mov.b64 z, 0; @p st.global.u32 [z], %0;}" ::"r"(c) : "memory");
}
template <int K>
__device__ __forceinline__ void sched_fence() {
  asm volatile("{.reg .pred p; setp.eq.u32 p, %0, %1; @p exit;}" ::"r"(blockIdx.x), "n"(256 + K) : "memory");
}
template <int K>
__device__ __forceinline__ void sched_fence_async() {
  asm volatile("{.reg .pred p; .reg .u32 r; setp.ne.u32 p, %0, %1; @p bra.uni SFE;\n"
               "SFL: nanosleep.u32 1000; mov.u32 r, %%clock; setp.eq.u32 p, r, 0; @p bra.uni SFL;\nSFE: }" ::"r"(blockIdx.x), "n"(256 + K) : "memory");
}
__device__ __forceinline__ bool elect_one() {
  uint32_t pred;
  asm volatile("{.reg .pred p; elect.sync _|p, 0xffffffff; selp.u32 %0, 1, 0, p;}" : "=r"(pred));
  return pred;
}
__device__ __forceinline__ void mbar_init(uint32_t bar, uint32_t cnt) {
  asm volatile("mbarrier.init.shared::cta.b64 [%0], %1;" ::"r"(bar), "r"(cnt) : "memory");
}
__device__ __forceinline__ bool mbar_try(uint32_t bar, uint32_t par) {
  uint32_t ok;
  asm volatile("{.reg .pred p; mbarrier.try_wait.parity.shared::cta.b64 p, [%1], %2; selp.u32 %0, 1, 0, p;}"
               : "=r"(ok) : "r"(bar), "r"(par) : "memory");
  return ok;
}
#undef DBGV
#define DBGV ((bar - S_BAR) * 2 + par)
__device__ __forceinline__ void mbar_wait(uint32_t bar, uint32_t par) {
  if (__builtin_expect(!mbar_try(bar, par), 0)) {
    int n = SPIN_LIMIT;
    while (!mbar_try(bar, par) && --n) {}
    trap_if(n == 0);
  }
}
#define full_wait(bar, par, slot) mbar_wait(bar, par)
__device__ __forceinline__ void mbar_wait_long(uint32_t bar, uint32_t par) {
  int n = SPIN_LIMIT;
  while (!mbar_try(bar, par) && --n) __nanosleep(100);
  trap_if(n == 0);
}
#undef DBGV
#define DBGV 0
__device__ __forceinline__ void mbar_arrive(uint32_t bar) {
  asm volatile("mbarrier.arrive.shared::cta.b64 _, [%0];" ::"r"(bar) : "memory");
}
__device__ __forceinline__ void mbar_expect(uint32_t bar, uint32_t bytes) {
  asm volatile("mbarrier.arrive.expect_tx.shared::cta.b64 _, [%0], %1;" ::"r"(bar), "r"(bytes) : "memory");
}
__device__ __forceinline__ void tma2d(uint32_t dst, const CUtensorMap* m, uint32_t bar, int c0, int c1) {
  asm volatile("cp.async.bulk.tensor.2d.shared::cluster.global.mbarrier::complete_tx::bytes [%0], [%1, {%3, %4}], [%2];"
               ::"r"(dst), "l"(m), "r"(bar), "r"(c0), "r"(c1) : "memory");
}
__device__ __forceinline__ void tma3d(uint32_t dst, const CUtensorMap* m, uint32_t bar, int c0, int c1, int c2) {
  asm volatile("cp.async.bulk.tensor.3d.shared::cluster.global.mbarrier::complete_tx::bytes [%0], [%1, {%3, %4, %5}], [%2];"
               ::"r"(dst), "l"(m), "r"(bar), "r"(c0), "r"(c1), "r"(c2) : "memory");
}
__device__ __forceinline__ void tma4d(uint32_t dst, const CUtensorMap* m, uint32_t bar, int c0, int c1, int c2, int c3) {
  asm volatile("cp.async.bulk.tensor.4d.shared::cluster.global.mbarrier::complete_tx::bytes [%0], [%1, {%3, %4, %5, %6}], [%2];"
               ::"r"(dst), "l"(m), "r"(bar), "r"(c0), "r"(c1), "r"(c2), "r"(c3) : "memory");
}
__device__ __forceinline__ void tma5d(uint32_t dst, const CUtensorMap* m, uint32_t bar, int c0, int c1, int c2, int c3, int c4) {
  asm volatile("cp.async.bulk.tensor.5d.shared::cluster.global.mbarrier::complete_tx::bytes [%0], [%1, {%3, %4, %5, %6, %7}], [%2];"
               ::"r"(dst), "l"(m), "r"(bar), "r"(c0), "r"(c1), "r"(c2), "r"(c3), "r"(c4) : "memory");
}
__device__ __forceinline__ void bulk_load(uint32_t dst, const void* src, uint32_t bytes, uint32_t bar) {
  asm volatile("cp.async.bulk.shared::cluster.global.mbarrier::complete_tx::bytes [%0], [%1], %2, [%3];"
               ::"r"(dst), "l"(src), "r"(bytes), "r"(bar) : "memory");
}
__device__ __forceinline__ void l2_prefetch(const void* src, uint32_t bytes) {
  asm volatile("cp.async.bulk.prefetch.L2.global [%0], %1;" ::"l"(src), "r"(bytes) : "memory");
}
__device__ __forceinline__ void bar_sync(int id, int n) { asm volatile("bar.sync %0, %1;" ::"r"(id), "r"(n) : "memory"); }
__device__ __forceinline__ void bar_arrive(int id, int n) { asm volatile("bar.arrive %0, %1;" ::"r"(id), "r"(n) : "memory"); }
__device__ __forceinline__ void fence_async_smem() { asm volatile("fence.proxy.async.shared::cta;" ::: "memory"); }
__device__ __forceinline__ void fence_async_global() { asm volatile("fence.proxy.async.global;" ::: "memory"); }
__device__ __forceinline__ void flag_add(int f) {
  asm volatile("red.relaxed.gpu.global.add.u32 [%0], 1;" ::"l"(g_flag + f * 32) : "memory");
}
__device__ __forceinline__ void flag_release(int f) {
  asm volatile("fence.release.gpu;" ::: "memory");
  flag_add(f);
}
__device__ __forceinline__ unsigned ld_relaxed(const unsigned* p) {
  unsigned v;
  asm volatile("ld.relaxed.gpu.global.u32 %0, [%1];" : "=r"(v) : "l"(p) : "memory");
  return v;
}
__device__ __forceinline__ void wait_clock(unsigned t) {
  int d;
  while ((d = (int)(t - (unsigned)clock())) > 0) __nanosleep(d > 600 ? 200 : 40);
}
__device__ __forceinline__ uint32_t pack2(float lo, float hi) {
  uint32_t r;
  asm("cvt.rn.bf16x2.f32 %0, %1, %2;" : "=r"(r) : "f"(hi), "f"(lo));
  return r;
}
__device__ __forceinline__ float bf_lo(uint32_t v) { return __uint_as_float(v << 16); }
__device__ __forceinline__ float bf_hi(uint32_t v) { return __uint_as_float(v & 0xffff0000u); }
__device__ __forceinline__ float bf_round(float v) { return __bfloat162float(__float2bfloat16_rn(v)); }
__device__ __forceinline__ uint32_t hmul2(uint32_t a, uint32_t b) {
  uint32_t r;
  asm("mul.rn.bf16x2 %0, %1, %2;" : "=r"(r) : "r"(a), "r"(b));
  return r;
}
__device__ __forceinline__ uint32_t hadd2(uint32_t a, uint32_t b) {
  uint32_t r;
  asm("add.rn.bf16x2 %0, %1, %2;" : "=r"(r) : "r"(a), "r"(b));
  return r;
}
__device__ __forceinline__ uint32_t hsub2(uint32_t a, uint32_t b) {
  uint32_t r;
  asm("sub.rn.bf16x2 %0, %1, %2;" : "=r"(r) : "r"(a), "r"(b));
  return r;
}
__device__ __forceinline__ uint32_t hfma2(uint32_t a, uint32_t b, uint32_t c) {
  uint32_t r;
  asm("fma.rn.bf16x2 %0, %1, %2, %3;" : "=r"(r) : "r"(a), "r"(b), "r"(c));
  return r;
}
__device__ __forceinline__ uint32_t hneg2(uint32_t a) {
  uint32_t r;
  asm("neg.bf16x2 %0, %1;" : "=r"(r) : "r"(a));
  return r;
}
__device__ __forceinline__ uint4 ldg128(const void* p) {
  uint4 v;
  asm volatile("ld.global.nc" LDQ ".v4.u32 {%0,%1,%2,%3}, [%4];" : "=r"(v.x), "=r"(v.y), "=r"(v.z), "=r"(v.w) : "l"(p));
  return v;
}
__device__ __forceinline__ uint2 ldg64(const void* p) {
  uint2 v;
  asm volatile("ld.global.nc.v2.u32 {%0,%1}, [%2];" : "=r"(v.x), "=r"(v.y) : "l"(p));
  return v;
}
__device__ __forceinline__ void stg128(void* p, uint32_t a, uint32_t b, uint32_t c, uint32_t d) {
  asm volatile("st.global.v4.u32 [%0], {%1,%2,%3,%4};" ::"l"(p), "r"(a), "r"(b), "r"(c), "r"(d) : "memory");
}
__device__ __forceinline__ void sts128(uint32_t a, uint32_t x, uint32_t y, uint32_t z, uint32_t w) {
  asm volatile("st.shared.v4.u32 [%0], {%1,%2,%3,%4};" ::"r"(a), "r"(x), "r"(y), "r"(z), "r"(w) : "memory");
}
__device__ __forceinline__ uint32_t lds32(uint32_t a) {
  uint32_t v;
  asm volatile("ld.shared.u32 %0, [%1];" : "=r"(v) : "r"(a) : "memory");
  return v;
}
__device__ __forceinline__ uint4 lds128(uint32_t a) {
  uint4 v;
  asm volatile("ld.shared.v4.u32 {%0,%1,%2,%3}, [%4];" : "=r"(v.x), "=r"(v.y), "=r"(v.z), "=r"(v.w) : "r"(a) : "memory");
  return v;
}
__device__ __forceinline__ void stsm4(uint32_t a, uint32_t x, uint32_t y, uint32_t z, uint32_t w) {
  asm volatile("stmatrix.sync.aligned.m8n8.x4.shared.b16 [%0], {%1,%2,%3,%4};" ::"r"(a), "r"(x), "r"(y), "r"(z), "r"(w) : "memory");
}
__device__ __forceinline__ void stsm4t(uint32_t a, uint32_t x, uint32_t y, uint32_t z, uint32_t w) {
  asm volatile("stmatrix.sync.aligned.m8n8.x4.trans.shared.b16 [%0], {%1,%2,%3,%4};" ::"r"(a), "r"(x), "r"(y), "r"(z), "r"(w) : "memory");
}
__device__ __forceinline__ uint4 ldsm4t(uint32_t a) {
  uint4 v;
  asm volatile("ldmatrix.sync.aligned.m8n8.x4.trans.shared.b16 {%0,%1,%2,%3}, [%4];" : "=r"(v.x), "=r"(v.y), "=r"(v.z), "=r"(v.w) : "r"(a) : "memory");
  return v;
}
struct cx { float r, i; };
__device__ __forceinline__ cx cmul(cx a, cx b) { return {a.r * b.r - a.i * b.i, a.r * b.i + a.i * b.r}; }
__device__ __forceinline__ cx cfma(cx a, cx b, cx c) { return {fmaf(a.r, b.r, fmaf(-a.i, b.i, c.r)), fmaf(a.r, b.i, fmaf(a.i, b.r, c.i))}; }
__device__ __forceinline__ cx csq(cx a) { return {a.r * a.r - a.i * a.i, 2.f * a.r * a.i}; }
__device__ __forceinline__ cx unit(int num, int den) {
  int m = num & (den - 1);
  if (m >= den / 2) m -= den;
  float s, c;
  __sincosf((float)m * (-6.283185307179586f / (float)den), &s, &c);
  return {c, s};
}

__device__ __forceinline__ uint2 lds64(uint32_t a) {
  uint2 v;
  asm volatile("ld.shared.v2.u32 {%0,%1}, [%2];" : "=r"(v.x), "=r"(v.y) : "r"(a) : "memory");
  return v;
}
__device__ __forceinline__ void prep_taps(const uint4 (&sh)[2], uint32_t (&s)[2][4]) {
#pragma unroll
  for (int e = 0; e < 2; e++) {
    s[e][0] = __byte_perm(sh[e].x, sh[e].z, 0x5410); s[e][1] = __byte_perm(sh[e].x, sh[e].z, 0x7632);
    s[e][2] = __byte_perm(sh[e].y, sh[e].w, 0x5410); s[e][3] = __byte_perm(sh[e].y, sh[e].w, 0x7632);
  }
}
__device__ __forceinline__ void prep_math(const uint2 (&kk)[11], uint2 (&vv)[8], const uint32_t (&s)[2][4]) {
#pragma unroll
  for (int i = 0; i < 8; i++)
#pragma unroll
    for (int e = 0; e < 2; e++) {
      uint32_t a = hmul2((&kk[i].x)[e], s[e][3]);
      a = hfma2((&kk[i + 1].x)[e], s[e][2], a);
      a = hfma2((&kk[i + 2].x)[e], s[e][1], a);
      a = hfma2((&kk[i + 3].x)[e], s[e][0], a);
      (&vv[i].x)[e] = hmul2(a, (&vv[i].x)[e]);
    }
}
__device__ __forceinline__ void prep_store(const uint2 (&vv)[8], int d, int tb) {
  uint4* dst = g_u + (size_t)((d >> 5) * 32 + (tb >> 3)) * 256 + (d & 31) * 8 + ((tb & 7) ^ ((tb >> 3) & 1));
#pragma unroll
  for (int e = 0; e < 2; e++) {
#define U(i) (&vv[i].x)[e]
    stg128(dst + (2 * e) * 8, __byte_perm(U(0), U(1), 0x5410), __byte_perm(U(2), U(3), 0x5410),
           __byte_perm(U(4), U(5), 0x5410), __byte_perm(U(6), U(7), 0x5410));
    stg128(dst + (2 * e + 1) * 8, __byte_perm(U(0), U(1), 0x7632), __byte_perm(U(2), U(3), 0x7632),
           __byte_perm(U(4), U(5), 0x7632), __byte_perm(U(6), U(7), 0x7632));
#undef U
  }
}
template <int PG>
__device__ __forceinline__ void prep(const Ptrs& p, int ti, int pj, int w, int lane) {
  const int tb = lane & 7, chunk = 2 * w + (lane >> 4), ch = chunk * 8 + ((lane >> 3) & 1) * 4, d = pj * 128 + PG * 64 + ch;
  const uint4 sh[2] = {ldg128(p.shift + d * 4), ldg128(p.shift + d * 4 + 8)};
  uint32_t s[2][4];
  prep_taps(sh, s);
#pragma unroll 1
  for (int th = 0; th < 2; th++) {
    uint2 kk[11], vv[8];
    {
      const uint32_t in = S_STG + th * 16384 + (lane & 8);
      const uint32_t a0 = in + tb * 128 + ((chunk ^ tb) << 4);
      const uint32_t hb = tb ? in + (39 + tb) * 128 + ((chunk ^ (tb - 1)) << 4) : S_T + (PG * 2 + th) * 512 + ch * 2;
      const uint32_t hs = tb ? 1024 : 128;
      mbar_wait_long(B_PIN + 16 * PG + 8 * th, 0);
      if (th) TIM(29 + PG);
#pragma unroll
      for (int i = 0; i < 3; i++) kk[i] = lds64(hb + i * hs);
#pragma unroll
      for (int i = 0; i < 8; i++) { kk[3 + i] = lds64(a0 + i * 1024); vv[i] = lds64(a0 + 8192 + i * 1024); }
      prep_math(kk, vv, s);
      sched_fence<52 + PG>();
    }
    if (!PG) bar_arrive(th ? 11 : 3, 160);
    else if (elect_one()) mbar_arrive(B_SFREE + 8 * th);
    prep_store(vv, d, ti * 16 + th * 8 + tb);
  }
  bar_arrive(4 + PG, 160);
}

__device__ __forceinline__ void gate_finish(int ti, int tid, uint32_t tag) {
  float l;
  int n = SPIN_LIMIT;
  bool bad;
  do {
    __nanosleep(250);
    uint32_t v[8], x = 0;
#pragma unroll
    for (int j = 0; j < 8; j++) v[j] = ld_relaxed(g_gate + j * SEQ + ti * 128 + tid) ^ tag;
    l = 0.f;
#pragma unroll
    for (int j = 0; j < 8; j++) { x |= v[j]; l += __uint_as_float(v[j]); }
    bad = __any_sync(~0u, x & 3);
  } while (bad && --n);
  trap_if(n == 0);
  const float g = bf_round(__fdividef(1.f, 1.f + __expf(-bf_round(l))));
  asm volatile("st.shared.f32 [%0], %1;" ::"r"(S_G + tid * 4), "f"(g) : "memory");
}

__device__ __forceinline__ void conv_tables(int tid) {
  {
    const int s = tid >> 5, n1 = tid & 31;
    uint32_t re[4], im[4];
#pragma unroll
    for (int e = 0; e < 4; e++) {
      cx a = unit(n1 * (4 * (8 * s + 2 * e) + 1), 128), b = unit(n1 * (4 * (8 * s + 2 * e + 1) + 1), 128);
      re[e] = pack2(a.r * 0.125f, b.r * 0.125f); im[e] = pack2(a.i * 0.125f, b.i * 0.125f);
    }
    sts128(S_M1 + (2 * s) * 512 + n1 * 16, re[0], re[1], re[2], re[3]);
    sts128(S_M1 + (2 * s + 1) * 512 + n1 * 16, im[0], im[1], im[2], im[3]);
  }
  {
    const int kg = tid >> 5, n = tid & 31;
    const int pi = kg >> 1, po = n >> 4, f2 = n & 15;
    uint32_t fw[4];
#pragma unroll
    for (int e = 0; e < 4; e++) {
      int n2 = (kg & 1) * 8 + 2 * e;
      cx a = unit(n2 * f2, 16), b = unit((n2 + 1) * f2, 16);
      float sg = pi ? -1.f : 1.f;
      float x0 = (pi == po) ? a.r : sg * a.i, x1 = (pi == po) ? b.r : sg * b.i;
      fw[e] = pack2(x0, x1);
    }
    sts128(S_M2 + kg * 512 + n * 16, fw[0], fw[1], fw[2], fw[3]);
  }
  fence_async_smem();
}
__device__ __forceinline__ constexpr int jj_of(int o) { return o == 7 ? 3 : o + (o >= 3); }
__device__ __forceinline__ int conv_chan(int ti, int pj, int jj) { return pj * 128 + jj * 16 + ti; }

struct ConvCtx {
  uint32_t buf, inbar;
  int nb, n;
  int ti, pj, j;
  __device__ __forceinline__ int chan(int c) const {
    return j < 0 ? conv_chan(ti, pj, jj_of(c)) : conv_chan(((j + 12 * c) >> 3) + (((j + 12 * c) >> 3) >= KEEP), (j + 12 * c) & 7, 3);
  }
};
__device__ __forceinline__ ConvCtx conv_ctx(int spare, int wg, int ti, int pj) {
  const int j = spare < 0 ? -1 : spare * 3 + wg;
  return {wg == 2 ? S_CIN : sb + wg * 32768, wg == 2 ? B_CINF : (wg ? B_PIN : B_FULL), 4 + 4 * wg, j < 0 ? 7 + (ti == KEEP) : (j < 8 && KEEP > 15 ? 11 : 10), ti, pj, j};
}
#define CDESC(a) mkdesc(dlo(a, 512), 128, 0)
struct ConvTw { uint32_t r[2], i[2], n[2]; };

__device__ __forceinline__ void cv_tw1(float (&d)[64], uint32_t (&R)[16], uint32_t (&I)[16], const ConvTw& t, int i) {
#pragma unroll
  for (int j = 8 * (i & 1); j < 8 * (i & 1) + 8; j++) {
    if (i < 2) {
      R[j] = pack2(d[4 * j], d[4 * j + 1]); I[j] = pack2(d[4 * j + 2], d[4 * j + 3]);
    } else {
      const uint32_t xr = R[j], xi = I[j];
      R[j] = hfma2(xr, t.r[j & 1], hmul2(xi, t.n[j & 1]));
      I[j] = hfma2(xr, t.i[j & 1], hmul2(xi, t.r[j & 1]));
    }
  }
}
template <int N>
__device__ __forceinline__ void cv_pack(float (&X)[16], uint32_t (&P)[N][2][2], int q) {
#pragma unroll
  for (int k = 0; k < 2; k++)
#pragma unroll
    for (int j = 0; j < 4; j++) P[2 * q + k][j >> 1][j & 1] = pack2(X[4 * j + 2 * k], X[4 * j + 2 * k + 1]);
}
__device__ __forceinline__ void cv_overlap(uint32_t (&P)[8][2][2]) {
#pragma unroll
  for (int k = 3; k > 0; k--)
#pragma unroll
    for (int hh = 0; hh < 2; hh++) {
      P[k][0][hh] = hsub2(P[k][0][hh], P[k - 1][1][hh]);
      P[k][1][hh] = hadd2(P[k][1][hh], P[k - 1][0][hh]);
    }
}
__device__ __forceinline__ void cv_pw(uint32_t (&P)[8][2][2], uint32_t (&Q)[4][2][2]) {
#pragma unroll
  for (int jh = 0; jh < 8; jh++) {
    const int j = jh >> 1, hh = jh & 1;
    uint32_t qr = hmul2(P[4 + j][0][hh], P[0][0][hh]), qi = hmul2(P[4 + j][0][hh], P[0][1][hh]);
    qr = hfma2(hneg2(P[4 + j][1][hh]), P[0][1][hh], qr);
    qi = hfma2(P[4 + j][1][hh], P[0][0][hh], qi);
#pragma unroll
    for (int k = j - 1; k >= 0; k--) {
      qr = hfma2(P[4 + k][0][hh], P[j - k][0][hh], qr);
      qi = hfma2(P[4 + k][0][hh], P[j - k][1][hh], qi);
      qr = hfma2(hneg2(P[4 + k][1][hh]), P[j - k][1][hh], qr);
      qi = hfma2(P[4 + k][1][hh], P[j - k][0][hh], qi);
    }
    Q[j][0][hh] = qr; Q[j][1][hh] = qi;
  }
}
__device__ __forceinline__ void cv_tw2(uint32_t (&Q)[4][2][2], const ConvTw& t, int k) {
#pragma unroll
  for (int hh = 0; hh < 2; hh++) {
    const uint32_t xr = Q[k][0][hh], xi = Q[k][1][hh];
    Q[k][0][hh] = hfma2(xr, t.r[hh], hmul2(xi, t.i[hh]));
    Q[k][1][hh] = hfma2(xr, t.n[hh], hmul2(xi, t.r[hh]));
  }
}
__device__ __forceinline__ void cv_out0(float (&Y)[16], uint32_t T, int w, int lane) {
  reg_fence(Y);
  const uint32_t za = T + w * 2048 + (lane >> 4) * 256 + (lane & 7) * 32 + (((lane >> 3) ^ (lane >> 2)) & 1) * 16;
#pragma unroll
  for (int jj = 0; jj < 2; jj++)
    stsm4t(za + jj * 512, pack2(Y[8 * jj], Y[8 * jj + 1]), pack2(Y[8 * jj + 2], Y[8 * jj + 3]),
           pack2(Y[8 * jj + 4], Y[8 * jj + 5]), pack2(Y[8 * jj + 6], Y[8 * jj + 7]));
}

__device__ __forceinline__ void cv_out1(const uint4& z0, const uint4& z1, const ConvCtx& cc, uint32_t keep, uint32_t tag, int ch, int w, int lane) {
  uint4* zp = g_z + (size_t)cc.chan(ch) * 256 + w * 64 + lane;
#define TG(v) ((v & keep) | (tag & ~keep))
  asm volatile("st.relaxed.gpu.global.v4.u32 [%0], {%1,%2,%3,%4};" ::"l"(zp), "r"(TG(z0.x)), "r"(TG(z0.y)), "r"(TG(z0.z)), "r"(TG(z0.w)) : "memory");
  asm volatile("st.relaxed.gpu.global.v4.u32 [%0], {%1,%2,%3,%4};" ::"l"(zp + 32), "r"(TG(z1.x)), "r"(TG(z1.y)), "r"(TG(z1.z)), "r"(TG(z1.w)) : "memory");
#undef TG
}
template <bool FW, bool BW, int K>
__device__ __forceinline__ void conv_step(uint32_t (&Q)[4][2][2], const ConvTw& t, const ConvCtx& cc, float dl, uint32_t tag, int ch, int w, int lane) {
#define SF(n) if ((SFM >> (n)) & 1) sched_fence_async<K + (n)>()
  float d[64], X[4][16], Z[2][16], Y[16];
  uint32_t R[16], I[16];
  uint4 a[4];
  const int nx = ch + 1;
  const uint32_t T = cc.buf + 16384;
  float dv;
  TIMC(1);
  if (FW) {
    dv = __shfl_sync(~0u, dl, nx);
    mbar_wait(cc.inbar + 8 * (nx & 1), (nx >> 1) & 1);
  }
  TIMC(2);
  WG_FENCE();
  if (BW) {
#pragma unroll
    for (int q = 0; q < 2; q++) {
      wgmma_rs32<0, 1>(Z[q], Q[2 * q][0][0], Q[2 * q + 1][0][0], Q[2 * q][0][1], Q[2 * q + 1][0][1], mkdesc(dlo(S_M2, 128), 512, 0));
      wgmma_rs32<1, 1>(Z[q], Q[2 * q][1][0], Q[2 * q + 1][1][0], Q[2 * q][1][1], Q[2 * q + 1][1][1], mkdesc(dlo(S_M2 + 256, 128), 512, 0));
    }
    WG_COMMIT();
  }
  if (FW) {
    const uint32_t lo = dlo(0, 1024) + (cc.buf >> 4) + (nx & 1) * 512;
    wgmma_ss128<1, 1, 0>(d, mkdesc(dlo(S_M1, 128), 512, 0), mkdesc(lo, 256, 3));
    wgmma_ss128<1, 1, 1>(d, mkdesc(dlo(S_M1 + 256, 128), 512, 0), mkdesc(lo + 32, 256, 3));
    WG_COMMIT();
  }
  TIMC(3);
  if (BW) {
    TIMC(4);
    WG_WAIT(FW ? 1 : 0);
    TIMC(5);
    reg_fence(Z[0]); reg_fence(Z[1]);
    uint32_t V[4][2][2];
    cv_pack(Z[0], V, 0); cv_pack(Z[1], V, 1);
    SF(0);
#pragma unroll
    for (int k = 0; k < 4; k++) cv_tw2(V, t, k);
    bar_sync(cc.nb, 128);
#pragma unroll
    for (int k = 0; k < 4; k++) stsm4(T + w * 512 + lane * 16 + k * 2048, V[k][0][0], V[k][0][1], V[k][1][0], V[k][1][1]);
    SF(1);
    TIMC(6);
  }
  if (FW) {
    WG_WAIT(0);
    reg_fence(d);
    if (nx + 2 < cc.n) bar_arrive(cc.nb + 2 + (nx & 1), 160);
    cv_tw1(d, R, I, t, 0); cv_tw1(d, R, I, t, 1);
    SF(2);
    TIMC(7);
  }
  if (BW) {
    bar_sync(cc.nb, 128);
#pragma unroll
    for (int s = 0; s < 4; s++) a[s] = ldsm4t(T + (4 * w + s) * 512 + lane * 16);
  }
  if (FW) { cv_tw1(d, R, I, t, 2); cv_tw1(d, R, I, t, 3); }
  sched_fence<K + 3>();
  TIMC(8);
  WG_FENCE();
  if (BW) {
    wgmma_rs32<0>(Y, a[0].x, a[0].y, a[0].z, a[0].w, CDESC(S_M1));
#pragma unroll
    for (int i = 1; i < 4; i++) wgmma_rs32<1>(Y, a[i].x, a[i].y, a[i].z, a[i].w, CDESC(S_M1 + 1024 * i));
  }
  if (FW) {
#pragma unroll
    for (int q = 0; q < 4; q++) {
      if (q == 2) WG_COMMIT();
      wgmma_rs32<0>(X[q], R[4 * q], R[4 * q + 2], R[4 * q + 1], R[4 * q + 3], CDESC(S_M2));
      wgmma_rs32<1>(X[q], I[4 * q], I[4 * q + 2], I[4 * q + 1], I[4 * q + 3], CDESC(S_M2 + 1024));
    }
  }
  WG_COMMIT();
  TIMC(9);
  WG_WAIT(FW ? 1 : 0);
  TIMC(10);
  uint4 z0, z1;
  const uint32_t zr = T + w * 2048 + (lane ^ ((lane >> 3) & 1)) * 16;
  if (BW) {
    cv_out0(Y, T, w, lane);
    __syncwarp();
  }
  if (FW) {
    uint32_t P[8][2][2];
    reg_fence(X[0]); reg_fence(X[1]);
    cv_pack(X[0], P, 0); cv_pack(X[1], P, 1);
    cv_overlap(P);
    if (BW) { z0 = lds128(zr); z1 = lds128(zr + 512); }
    sched_fence_async<K + 7>();
    WG_WAIT(0);
    reg_fence(X[2]); reg_fence(X[3]);
    X[2][0] += dv; X[2][1] += dv; X[2][4] += dv; X[2][5] += dv;
    cv_pack(X[2], P, 2); cv_pack(X[3], P, 3);
    SF(4);
    TIMC(11);
    cv_pw(P, Q);
    SF(8);
  } else {
    z0 = lds128(zr); z1 = lds128(zr + 512);
  }
  if (BW) cv_out1(z0, z1, cc, FW && cc.j < 0 && ch < 4 ? ~0u : ~1u, tag, ch, w, lane);
  sched_fence<K + 5>();
  TIMC(13);
#undef SF
}

__device__ __forceinline__ void conv_main(const Ptrs& p, const ConvCtx& cc, int eb, int tid) {
  const int ti = cc.ti, pj = cc.pj;
  const int w = tid >> 5, lane = tid & 31;
  const unsigned ep = ld_relaxed(g_epoch + eb);
  const __nv_bfloat16 dsk = p.ssmd[cc.chan(min(lane, cc.n - 1))];
  if (cc.nb == 12) conv_tables(tid);
  if (cc.j < 0) bar_sync(12, 160); else bar_sync(0, 512);
  ConvTw t;
#pragma unroll
  for (int hh = 0; hh < 2; hh++) {
    const int n2 = 8 * hh + 2 * (lane & 3), m = 4 * (8 * w + (lane >> 2)) + 1;
    cx a = unit(n2 * m, 2048), b = unit((n2 + 1) * m, 2048);
    t.r[hh] = pack2(a.r, b.r); t.i[hh] = pack2(a.i, b.i); t.n[hh] = pack2(-a.i, -b.i);
  }
  const uint32_t tag = (ep + 1) & 3;
  const float dl = 0.125f * __bfloat162float(dsk);
  if (cc.j < 0) prep<1>(p, ti, pj, w, lane);
  {
    uint32_t P[4][2][2];
    mbar_wait_long(cc.inbar, 0);
    TIM(20);
    conv_step<true, false, 10>(P, t, cc, dl, tag, -1, w, lane);
#pragma unroll 1
    for (int ch = 0; ch < cc.n - 1; ch++) {
      conv_step<true, true, 20>(P, t, cc, dl, tag, ch, w, lane);
      if (cc.j < 0 && ch == 3) bar_arrive(0, 160);
      if (ch == 0) TIM(21);
    }
    conv_step<false, true, 30>(P, t, cc, dl, tag, cc.n - 1, w, lane);
  }
  TIM(22);
}

__device__ __forceinline__ cx csel(bool k, cx a, cx b) { return {k ? a.r : b.r, k ? a.i : b.i}; }
__device__ __forceinline__ void ld2cx(uint32_t a, cx& x, cx& y) {
  const uint4 v = lds128(a);
  x = {__uint_as_float(v.x), __uint_as_float(v.y)};
  y = {__uint_as_float(v.z), __uint_as_float(v.w)};
}
__device__ __forceinline__ cx ldcx(uint32_t a) {
  cx x;
  asm volatile("ld.shared.v2.f32 {%0,%1}, [%2];" : "=f"(x.r), "=f"(x.i) : "r"(a) : "memory");
  return x;
}

__device__ __forceinline__ void scan_epilogue(float (&aR)[64], float (&aI)[64], uint32_t last_empty, int ph, int ti, int pj, int tid) {
  const int w = tid >> 5, lane = tid & 31, r = lane >> 2, c = lane & 3;
  const uint32_t par = S_PAR + (ph * 64 + 16 * w + r) * 16;
  uint4* agg = g_agg + ph * 16 * 256 + pj * 32 + 8 * w + r;
  const uint32_t tag = (lds32(S_EP) + 1) & 3;
  cx h[2];
  {
    cx lam[2], a[2];
#pragma unroll
    for (int q = 0; q < 2; q++) { lam[q] = ldcx(par + q * 128); h[q] = ldcx(par + 2048 + q * 128); }
    WG_WAIT(0);
    if (elect_one()) mbar_arrive(last_empty);
    asm volatile("setmaxnreg.inc.sync.aligned.u32 168;");
    reg_fence(aR); reg_fence(aI);
    TIM(3 + ph * 2);
#pragma unroll
    for (int q = 0; q < 2; q++) a[q] = {aR[2 * q], aI[2 * q]};
#pragma unroll
    for (int s = 1; s < 32; s++)
#pragma unroll
      for (int q = 0; q < 2; q++) {
        const int i = 4 * (s >> 1) + 2 * q + (s & 1);
        a[q] = cfma(lam[q], a[q], {aR[i], aI[i]});
      }
    sched_fence<1>();
    cx t[2][3];
#pragma unroll
    for (int q = 0; q < 2; q++)
#pragma unroll
      for (int k = 0; k < 3; k++) t[q][k] = {__shfl_up_sync(~0u, a[q].r, k + 1, 4), __shfl_up_sync(~0u, a[q].i, k + 1, 4)};
#pragma unroll
    for (int q = 0; q < 2; q++) {
      const cx z = {0.f, 0.f};
      cx ex = cfma(h[q], csel(c >= 3, t[q][2], z), csel(c >= 2, t[q][1], z));
      ex = cfma(h[q], ex, csel(c >= 1, t[q][0], z));
      a[q] = cfma(h[q], ex, a[q]);
      const cx u = cfma(lam[q], ex, {aR[2 * q], aI[2 * q]});
      aR[2 * q] = u.r; aI[2 * q] = u.i;
    }
    if (c == 3)
      asm volatile("st.relaxed.gpu.global.v4.u32 [%0], {%1,%2,%3,%4};" ::"l"(agg + ti * 256),
                   "r"((__float_as_uint(a[0].r) & ~3u) | tag), "r"((__float_as_uint(a[0].i) & ~3u) | tag),
                   "r"((__float_as_uint(a[1].r) & ~3u) | tag), "r"((__float_as_uint(a[1].i) & ~3u) | tag) : "memory");
    TIM(8 + ph * 4);
  }
  if (ti > 0) {
    const uint2* ap = (const uint2*)(agg + (ti - 1 - (c >> 1)) * 256) + (c & 1);
    const int cnt = ti - (c >> 1);
    const cx one = {1.f, 0.f};
    const cx l128 = ldcx(par + 2048 + 8 + (c & 1) * 128), l256 = csq(l128), fa = csel(c & 2, l128, one);
#pragma unroll
    for (int q = 0; q < 2; q++) h[q] = cmul(csel(c & 1, h[q], one), csel(c & 2, csq(h[q]), one));
    uint2 v[8];
    int n = SPIN_LIMIT;
    bool bad;
    __nanosleep(AGG_NS);
    do {
      uint32_t x = 0;
#pragma unroll
      for (int j = 0; j < 8; j++) {
        v[j] = make_uint2(tag, tag);
        asm volatile("{.reg .pred p; setp.lt.s32 p, %3, %4; @p ld.relaxed.gpu.global.v2.u32 {%0,%1}, [%2];}"
                     : "+r"(v[j].x), "+r"(v[j].y) : "l"(ap - j * 1024), "r"(2 * j), "r"(cnt) : "memory");
      }
#pragma unroll
      for (int j = 0; j < 8; j++) { v[j].x ^= tag; v[j].y ^= tag; x |= v[j].x | v[j].y; }
      bad = __any_sync(~0u, x & 3);
    } while (bad && --n);
    trap_if(n == 0);
    cx a = {__uint_as_float(v[7].x), __uint_as_float(v[7].y)};
#pragma unroll
    for (int j = 6; j >= 0; j--) a = cfma(l256, a, {__uint_as_float(v[j].x), __uint_as_float(v[j].y)});
    a = cmul(a, fa);
    const cx t1 = {__shfl_xor_sync(~0u, a.r, 1), __shfl_xor_sync(~0u, a.i, 1)};
    const cx t2 = {__shfl_xor_sync(~0u, a.r, 2), __shfl_xor_sync(~0u, a.i, 2)};
    const cx t3 = {__shfl_xor_sync(~0u, a.r, 3), __shfl_xor_sync(~0u, a.i, 3)};
    const cx own = {a.r + t2.r, a.i + t2.i}, oth = {t1.r + t3.r, t1.i + t3.i};
#pragma unroll
    for (int q = 0; q < 2; q++) h[q] = cmul(csel((c & 1) == q, own, oth), h[q]);
  } else {
    h[0] = h[1] = {0.f, 0.f};
  }
  TIM(9 + ph * 4);
  cx lam[2];
  uint32_t cr[2], nci[2];
#pragma unroll
  for (int q = 0; q < 2; q++) {
    const uint4 v = lds128(par + q * 128);
    lam[q] = {__uint_as_float(v.x), __uint_as_float(v.y)};
    cr[q] = v.z; nci[q] = v.w;
  }
  uint4* hg = g_h + (size_t)(ti * 32 + ph * 16 + pj) * 1024 + w * 64 + r * 4 + (c ^ (r >> 1));
  const uint32_t hs = S_STG + w * 1024 + r * 64 + ((c ^ (r >> 1)) << 4);
  if (RE_EARLY) mbar_wait(B_SFREE + 16 * ph, 0);
  uint32_t pr[4][2][4], pi[4][2][4], re[4][2][4];
#pragma unroll
  for (int i = 0; i < 4; i++) {
#pragma unroll
    for (int s2 = 0; s2 < 4; s2++)
#pragma unroll
      for (int q = 0; q < 2; q++) {
        const int k = 4 * (4 * i + s2) + 2 * q;
        cx h0 = cfma(lam[q], h[q], {aR[k], aI[k]});
        h[q] = cfma(lam[q], h0, {aR[k + 1], aI[k + 1]});
        pr[i][q][s2] = pack2(h0.r, h[q].r);
        pi[i][q][s2] = pack2(h0.i, h[q].i);
        re[i][q][s2] = hfma2(pr[i][q][s2], cr[q], hmul2(pi[i][q][s2], nci[q]));
      }
#pragma unroll
    for (int q = 0; q < 2; q++) {
      stg128(hg + i * 256 + q * 32, re[i][q][0], re[i][q][1], re[i][q][2], re[i][q][3]);
      if (i < RE_EARLY) sts128(hs + i * 4096 + q * 512, re[i][q][0], re[i][q][1], re[i][q][2], re[i][q][3]);
    }
    if (i == 0 && (P2F & 1)) sched_fence<7>();
    if (i == 1 && (P2F & 2)) sched_fence<8>();
    if (i == 2 && (P2F & 1)) sched_fence<6>();
  }
  bar_arrive(9, 160);
  sched_fence<9>();
  TIM(10 + ph * 4);
  if (!RE_EARLY) mbar_wait(B_SFREE + 16 * ph, 0);
  if (ph == 0) mbar_wait(B_SFREE + 8, 0);
#pragma unroll
  for (int q = 0; q < 2; q++) {
    const uint32_t ncr = cr[q] ^ 0x80008000u;
#pragma unroll
    for (int i = 0; i < 4; i++) {
      uint32_t o[4];
#pragma unroll
      for (int s2 = 0; s2 < 4; s2++) o[s2] = hfma2(pi[i][q][s2], ncr, hmul2(pr[i][q][s2], nci[q]));
      if (i >= RE_EARLY) sts128(hs + i * 4096 + q * 512, re[i][q][0], re[i][q][1], re[i][q][2], re[i][q][3]);
      sts128(hs + 16384 + i * 4096 + q * 512, o[0], o[1], o[2], o[3]);
      if (IM_NS) __nanosleep(IM_NS);
      stg128(hg + 8192 + i * 256 + q * 32, o[0], o[1], o[2], o[3]);
    }
  }
  fence_async_smem();
  __syncwarp();
  if (elect_one()) mbar_arrive(B_LOC + 8 * ph);
  bar_arrive(10, 160);
  bar_sync(1 + ph, 128);
  asm volatile("setmaxnreg.dec.sync.aligned.u32 160;");
}

__device__ __forceinline__ constexpr uint32_t e_addr(int o, int mh) { return S_STG + (o * 2 + mh) * 2048; }
__device__ __forceinline__ uint32_t z_off(int w, int lane, int mh) {
  return (w & 1) * 2048 + (lane & 15) * 128 + (((4 * (lane >> 4) + 2 * mh + (w >> 1)) ^ (lane & 7)) << 4);
}
constexpr uint32_t S_ZL = sb + (59 % NS) * STAGE;
__device__ __forceinline__ void eterm(const Ptrs& p, int ti, int pj, int tid) {
  const int w = tid >> 5, lane = tid & 31, r = lane >> 2, c = lane & 3;
  const int trow = 64 * (w & 1) + 8 * (w >> 1) + r;
  const int rs = 2 * (r & 3) + (r >> 2);
  uint2 xv[2][8][2], ds[8];
  {
    uint2 gw[8];
#pragma unroll
    for (int jj = 0; jj < 8; jj++) {
      gw[jj] = ldg64(p.gw + pj * 128 + 16 * jj + 4 * c);
      ds[jj] = ldg64(p.dskip + pj * 128 + 16 * jj + 4 * c);
    }
#pragma unroll
    for (int g = 0; g < 2; g++) {
      mbar_wait(B_XT + 8 * g, 0);
#pragma unroll
      for (int i = 0; i < 4; i++)
#pragma unroll
        for (int jj = 4 * g; jj < 4 * g + 4; jj++)
          xv[i >> 1][jj][i & 1] = lds64(sb + ((48 + g) % NS) * STAGE + (trow - r + rs + 16 * (i >> 1) + 32 * (i & 1)) * 128 + (((2 * (jj & 3) + (c >> 1)) ^ rs) << 4) + (c & 1) * 8);
      fence_async_smem();
      __syncwarp();
      if (elect_one()) mbar_arrive(B_XT + 16 + 8 * g);
    }
    sched_fence<55>();
    TIM(27);
    float s[4];
#pragma unroll
    for (int i = 0; i < 4; i++) {
      s[i] = 0.f;
#pragma unroll
      for (int jj = 0; jj < 8; jj += 2) {
        const uint2 x = xv[i >> 1][jj][i & 1], y = xv[i >> 1][jj + 1][i & 1];
        const uint32_t q = hfma2(x.x, gw[jj].x, hfma2(x.y, gw[jj].y, hfma2(y.x, gw[jj + 1].x, hmul2(y.y, gw[jj + 1].y))));
        s[i] += bf_lo(q) + bf_hi(q);
      }
    }
    float u0 = (c & 1) ? s[1] : s[0], v0 = (c & 1) ? s[0] : s[1];
    float u1 = (c & 1) ? s[3] : s[2], v1 = (c & 1) ? s[2] : s[3];
    u0 += __shfl_xor_sync(~0u, v0, 1);
    u1 += __shfl_xor_sync(~0u, v1, 1);
    float u = (c & 2) ? u1 : u0;
    u += __shfl_xor_sync(~0u, (c & 2) ? u0 : u1, 2);
    const uint32_t tag = (lds32(S_EP) + 1) & 3;
    asm volatile("st.relaxed.gpu.global.u32 [%0], %1;" ::"l"(g_gate + pj * SEQ + ti * 128 + trow + 16 * (c >> 1) + 32 * (c & 1)),
                 "r"((__float_as_uint(u) & ~3u) | tag) : "memory");
    gate_finish(ti, tid, tag);
  }
  bar_sync(2, 128);
  TIM(31);
  uint32_t g2[2][2], og2[2][2];
#pragma unroll
  for (int mh = 0; mh < 2; mh++)
#pragma unroll
    for (int hf = 0; hf < 2; hf++) {
      uint32_t g;
      asm volatile("ld.shared.u32 %0, [%1];" : "=r"(g) : "r"(S_G + (trow + 16 * mh + 32 * hf) * 4) : "memory");
      g2[mh][hf] = __byte_perm(g, g, 0x3232);
      og2[mh][hf] = hsub2(0x3f803f80u, g2[mh][hf]);
    }
  mbar_wait_long(B_LOC + 16, 0);
#pragma unroll
  for (int o = 4; o < 8; o++) {
    const int jj = jj_of(o);
#pragma unroll
    for (int mh = 0; mh < 2; mh++) sts128(e_addr(o, mh) + tid * 16, xv[mh][jj][0].x, xv[mh][jj][0].y, xv[mh][jj][1].x, xv[mh][jj][1].y);
    if (tid < 4) asm volatile("st.shared.v2.u32 [%0], {%1,%2};" ::"r"(S_PAR + o * 32 + tid * 8), "r"(ds[jj].x), "r"(ds[jj].y) : "memory");
  }
  mbar_wait_long(B_ZT, 0);
#pragma unroll
  for (int mh = 0; mh < 2; mh++)
#pragma unroll
    for (int o = 0; o < 4; o++) {
      const int jj = jj_of(o);
      const uint4 z = ldsm4t(S_STG + o * 4096 + z_off(w, lane, mh));
#pragma unroll
      for (int hf = 0; hf < 2; hf++) {
        uint2& x = xv[mh][jj][hf];
        x.x = hmul2(x.x, hfma2(og2[mh][hf], hf ? z.z : z.x, hmul2(g2[mh][hf], ds[jj].x)));
        x.y = hmul2(x.y, hfma2(og2[mh][hf], hf ? z.w : z.y, hmul2(g2[mh][hf], ds[jj].y)));
      }
    }
  bar_sync(2, 128);
#pragma unroll
  for (int mh = 0; mh < 2; mh++)
#pragma unroll
    for (int o = 0; o < 4; o++) {
      const int jj = jj_of(o);
      sts128(e_addr(o, mh) + tid * 16, xv[mh][jj][0].x, xv[mh][jj][0].y, xv[mh][jj][1].x, xv[mh][jj][1].y);
    }
  bar_arrive(5, 256);
  TIM(1);
  const uint32_t tag = (lds32(S_EP) + 1) & 1;
  const int zn = tid >> 4, ck = tid & 15;
  const uint4* zp = g_z + (size_t)(pj * 128 + 4 * (zn >> 1) + (zn & 1)) * 256 + ti * 16 + ck;
  uint4 v[2][4];
#define ZLOAD(g) _Pragma("unroll") for (int i = 0; i < 4; i++) \
    asm volatile("ld.relaxed.gpu.global.v4.u32 {%0,%1,%2,%3}, [%4];" : "=r"(v[g][i].x), "=r"(v[g][i].y), "=r"(v[g][i].z), "=r"(v[g][i].w) \
                 : "l"(zp + (jj_of(4 + 2 * g + (i >> 1)) * 16 + 2 * (i & 1)) * 256) : "memory")
  mbar_wait_long(B_ZT + 8, 0);
  ZLOAD(0);
  ZLOAD(1);
#pragma unroll
  for (int g = 0; g < 2; g++) {
    int it = SPIN_LIMIT;
    while (true) {
      uint32_t x = 0;
#pragma unroll
      for (int i = 0; i < 4; i++) {
        v[g][i].x ^= tag; v[g][i].y ^= tag; v[g][i].z ^= tag; v[g][i].w ^= tag;
        x |= v[g][i].x | v[g][i].y | v[g][i].z | v[g][i].w;
      }
      if (!__any_sync(~0u, x & 1) || !--it) break;
      __nanosleep(ZL_NS);
      ZLOAD(g);
    }
    trap_if(it == 0);
#pragma unroll
    for (int i = 0; i < 4; i++)
      sts128(S_ZL + (2 * g + (i >> 1)) * 4096 + (ck >> 3) * 2048 + (8 * (i & 1) + zn) * 128 + (((ck & 7) ^ zn) << 4), v[g][i].x, v[g][i].y, v[g][i].z, v[g][i].w);
    bar_arrive(6 + g, 256);
    if (g == 0) TIM(23);
  }
#undef ZLOAD
  TIM(17);
}

__device__ __forceinline__ void store_late(float (&a)[64], float* op, int jj, const uint4& x, const uint4& z, const uint2& ds, float g0, float g1) {
#pragma unroll
  for (int hf = 0; hf < 2; hf++) {
    const float g = hf ? g1 : g0, og = bf_round(1.f - g);
    const uint32_t x0 = hf ? x.z : x.x, x1 = hf ? x.w : x.y, z0 = hf ? z.z : z.x, z1 = hf ? z.w : z.y;
    const int k = 8 * jj + 2 * hf;
    stg128(op + hf * 32 * DM + 16 * jj,
           __float_as_uint(fmaf(g, a[k], bf_lo(x0) * fmaf(og, bf_lo(z0), g * bf_lo(ds.x)))),
           __float_as_uint(fmaf(g, a[k + 1], bf_hi(x0) * fmaf(og, bf_hi(z0), g * bf_hi(ds.x)))),
           __float_as_uint(fmaf(g, a[k + 4], bf_lo(x1) * fmaf(og, bf_lo(z1), g * bf_lo(ds.y)))),
           __float_as_uint(fmaf(g, a[k + 5], bf_hi(x1) * fmaf(og, bf_hi(z1), g * bf_hi(ds.y)))));
  }
}
__device__ __forceinline__ void store_piece(float (&a)[64], float* op, int jj, const uint4& e, float g0, float g1) {
  stg128(op + 16 * jj, __float_as_uint(fmaf(g0, a[8 * jj], bf_lo(e.x))), __float_as_uint(fmaf(g0, a[8 * jj + 1], bf_hi(e.x))),
         __float_as_uint(fmaf(g0, a[8 * jj + 4], bf_lo(e.y))), __float_as_uint(fmaf(g0, a[8 * jj + 5], bf_hi(e.y))));
  stg128(op + 32 * DM + 16 * jj, __float_as_uint(fmaf(g1, a[8 * jj + 2], bf_lo(e.z))), __float_as_uint(fmaf(g1, a[8 * jj + 3], bf_hi(e.z))),
         __float_as_uint(fmaf(g1, a[8 * jj + 6], bf_lo(e.w))), __float_as_uint(fmaf(g1, a[8 * jj + 7], bf_hi(e.w))));
}

__device__ __forceinline__ void issue_g1(const Maps& m, int s, int sl, int ti, int pj) {
  const uint32_t bar = B_FULL + 8 * sl, dst = sb + sl * STAGE;
  const int k0 = (s & 15) * 64, ch = (s >> 4) * 512 + pj * 64;
  mbar_expect(bar, STAGE);
  tma4d(dst + 16384, &m.x, bar, k0, 0, 4 * ti, 0);
  tma2d(dst, &m.bre, bar, k0, ch);
  tma2d(dst + 8192, &m.bim, bar, k0, ch);
}
__device__ __forceinline__ void producer(const Maps& m, int ti, int pj) {
  uint32_t off = 0, par = 0;
#pragma unroll 1
  for (int s = NS; s < 32; s++) {
    const uint32_t bar = B_FULL + off, dst = sb + off * (STAGE / 8), p0 = par;
    const int k0 = (s & 15) * 64, ch = (s >> 4) * 512 + pj * 64;
    off += 8;
    if (off == 8 * NS) { off = 0; par ^= 1; }
    asm volatile(
        "{.reg .pred p; .reg .u32 n;\n"
        "mov.u32 n, 0;\n"
        "W: mbarrier.try_wait.parity.shared::cta.b64 p, [%0 + %12], %1;\n"
        "@p bra.uni G;\n"
        "add.u32 n, n, 1; setp.lt.u32 p, n, %13; @p bra.uni W;\n"
        "st.global.u32 [%14], n;\n"
        "G: mbarrier.arrive.expect_tx.shared::cta.b64 _, [%0], 32768;\n"
        "cp.async.bulk.tensor.4d.shared::cluster.global.mbarrier::complete_tx::bytes [%2], [%5, {%8, %11, %10, %11}], [%0];\n"
        "cp.async.bulk.tensor.2d.shared::cluster.global.mbarrier::complete_tx::bytes [%3], [%6, {%8, %9}], [%0];\n"
        "cp.async.bulk.tensor.2d.shared::cluster.global.mbarrier::complete_tx::bytes [%4], [%7, {%8, %9}], [%0];}"
        ::"r"(bar), "r"(p0), "r"(dst + 16384), "r"(dst), "r"(dst + 8192), "l"(&m.x), "l"(&m.bre), "l"(&m.bim), "r"(k0), "r"(ch),
          "r"(4 * ti), "r"(0), "n"(8 * NS), "n"(SPIN_LIMIT), "l"(0ull) : "memory");
  }
#pragma unroll 1
  for (int q = 0; q < 32; q++) {
    const uint32_t bar = B_FULL + off, dst = sb + off * (STAGE / 8), p0 = par;
    const int ph = q >> 4, u = q & 15, part = u < 2 ? u : u >= 9, i = u - 2 - 7 * part;
    const int src = u < 2 ? pj : (i < 4 ? (~pj & 4) + i : (pj & 4) + i - 4 + (i - 4 >= (pj & 3)));
    const CUtensorMap* cm = part ? &m.cim : &m.cre;
    const uint4* hp = g_h + (size_t)(ti * 32 + ph * 16 + part * 8 + src) * 1024;
    off += 8;
    if (off == 8 * NS) { off = 0; par ^= 1; }
    if (q == 16 + NS || q == 17 + NS) mbar_wait(B_XT + 8 * (q - 14 - NS), 0);
    if (i > 0) {
      asm volatile(
          "{.reg .pred p; .reg .u32 n;\n"
          "mov.u32 n, 0;\n"
          "W: mbarrier.try_wait.parity.shared::cta.b64 p, [%0 + %9], %1;\n"
          "@p bra.uni G;\n"
          "add.u32 n, n, 1; setp.lt.u32 p, n, %10; @p bra.uni W;\n"
          "st.global.u32 [%11], n;\n"
          "G: mbarrier.arrive.expect_tx.shared::cta.b64 _, [%0], 32768;\n"
          "cp.async.bulk.shared::cluster.global.mbarrier::complete_tx::bytes [%3], [%5], 16384, [%0];\n"
          "cp.async.bulk.tensor.5d.shared::cluster.global.mbarrier::complete_tx::bytes [%2], [%4, {%6, %8, %8, %8, %7}], [%0];}"
          ::"r"(bar), "r"(p0), "r"(dst + 16384), "r"(dst), "l"(cm), "l"(hp), "r"(ph * 512 + src * 64), "r"(pj * 8), "r"(0),
            "n"(8 * NS), "n"(SPIN_LIMIT), "l"(0ull) : "memory");
    } else {
      mbar_wait(bar + 8 * NS, p0);
      mbar_expect(bar, u < 2 ? 16384 : STAGE);
      tma5d(dst + 16384, cm, bar, ph * 512 + src * 64, 0, 0, 0, pj * 8);
      if (u >= 2) {
        mbar_wait(B_FLG + 8 * (2 * ph + part), 0);
        fence_async_global();
        if (part == 0 && ph == 0) TIM(24);
        bulk_load(dst, hp, 16384, bar);
      } else if (ph) {
        mbar_expect(B_XT + 8 * u, 16384);
        tma4d(dst, &m.x2, B_XT + 8 * u, pj * 128 + u * 64, 0, 0, ti * 16);
      }
    }
  }
}

__device__ __forceinline__ void poller(int ti, int pj, int lane, unsigned ep) {
  if (lane < 5) {
    const int f = lane < 4 ? F_H + lane * 16 + ti : F_Z + pj;
    const unsigned need = (ep + 1) * (lane < 4 ? 8 : 16);
    int n = SPIN_LIMIT;
    bool done = false;
    do {
      if (!done && (int)(ld_relaxed(g_flag + f * 32) - need) >= 0) {
        done = true;
        asm volatile("fence.acquire.gpu;" ::: "memory");
        mbar_arrive(B_FLG + 8 * lane);
      }
      if (POLL_NS) __nanosleep(POLL_NS);
    } while (!__all_sync(0x1fu, done) && --n);
    trap_if(n == 0);
  }
}
__device__ __forceinline__ void storer(const Maps& m, int ti, int pj) {
#pragma unroll 1
  for (int job = 0; job < 6; job++) {
    bar_sync(job < 2 ? 4 + job : 9 + (job & 1), 160);
    if (elect_one()) flag_release(job < 2 ? F_U + pj * 2 + job : F_H + (job - 2) * 16 + ti);
    __syncwarp();
    if (job == 2 || job == 4) TIM(7 + job * 2);
  }
  if (elect_one()) {
    mbar_wait_long(B_LOC + 16, 0);
    mbar_wait_long(B_FLG + 32, 0);
    fence_async_global();
    mbar_expect(B_ZT, 16384);
#pragma unroll 1
    for (int o = 0; o < 4; o++) {
      tma5d(S_STG + o * 4096, &m.z, B_ZT, ti * 128, 0, 0, 0, pj * 8 + jj_of(o));
      tma5d(S_STG + o * 4096 + 2048, &m.z, B_ZT, ti * 128 + 64, 0, 0, 0, pj * 8 + jj_of(o));
    }
  }
}

__device__ __forceinline__ void kv_loader(const Maps& m, int ti, int pj, unsigned t_start) {
  unsigned tt = t_start + KV0_AT;
#pragma unroll 1
  for (int st = 0; st < 4; st++) {
    const int d = pj * 128 + (st >> 1) * 64, tb = ti * 16 + (st & 1) * 8;
    const uint32_t bar = B_PIN + 8 * st;
    if (st >= 2) { bar_sync(st == 2 ? 3 : 11, 160); fence_async_smem(); }
    if (elect_one()) {
      mbar_expect(bar, 16384 + 384);
      if (st == 2) tt = t_start + KV1_AT;
      if ((int)(clock() - tt) > 0) tt = clock();
#pragma unroll 1
      for (int i = 0; i < 4; i++) {
        wait_clock(tt);
        tt += st >= 2 ? KV_GAP1 : KV_GAP0;
        tma3d(S_STG + (st & 1) * 16384 + i * 4096, (i & 2) ? &m.v : &m.k, bar, d, tb, (i & 1) * 4);
        if (i == 0) tma3d(S_T + st * 512, &m.kh, bar, d, tb - 1, 5);
      }
    }
    tt = __shfl_sync(~0u, tt, 0);
  }
}

__device__ __forceinline__ void conv_loader(const Maps& m, const Ptrs& p, const ConvCtx& cc, int eb, int lane, unsigned t_start) {
  const unsigned ep = ld_relaxed(g_epoch + eb);
  wait_clock(t_start + SPF_AT);
#pragma unroll 1
  for (int ch = 0; ch < cc.n; ch++) {
    const int d = cc.chan(ch);
    const uint32_t bar = cc.inbar + 8 * (ch & 1), dst = cc.buf + (ch & 1) * 8192;
    const bool first = ch == 0 || ch == (cc.j < 0 ? 3 : 1);
    if (ch >= 2) bar_sync(cc.nb + 2 + (ch & 1), 160);
    if (elect_one()) {
      mbar_expect(cc.inbar + 16, 4096);
      bulk_load(dst + 4096, p.f + (size_t)d * SEQ, 4096, cc.inbar + 16);
      if (!first) { mbar_expect(bar, 4096); tma3d(dst, &m.u, bar, 0, d & 31, d & ~31); }
      if (ch + 1 < cc.n) l2_prefetch(p.f + (size_t)cc.chan(ch + 1) * SEQ, 4096);
    }
    __syncwarp();
    const uint32_t a = dst + 4096 + 128 + (lane >> 3) * 256 + (lane & 7) * 16;
    mbar_wait(cc.inbar + 16, ch & 1);
#pragma unroll 1
    for (uint32_t i = a; i < a + 4096; i += 2048) {
      const uint4 x = lds128(i), y = lds128(i + 1024);
      __syncwarp();
      sts128(i ^ 16, x.x, x.y, x.z, x.w);
      sts128((i ^ 16) + 1024, y.x, y.y, y.z, y.w);
    }
    fence_async_smem();
    __syncwarp();
    if (elect_one()) {
      mbar_arrive(bar);
      if (first) {
        int n = SPIN_LIMIT;
        while ((int)(ld_relaxed(g_flag + (F_U + (d >> 6)) * 32) - (ep + 1) * 16) < 0 && --n) __nanosleep(POLL_NS);
        trap_if(n == 0);
        asm volatile("fence.acquire.gpu;" ::: "memory");
        fence_async_global();
        mbar_expect(bar, 4096);
        tma3d(dst, &m.u, bar, 0, d & 31, d & ~31);
      }
    }
    __syncwarp();
    if (cc.j < 0 && ch == 6) {
      bar_sync(0, 160);
      if (elect_one()) flag_release(F_Z + cc.pj);
      __syncwarp();
    }
  }
  if (cc.j >= 0 && lane == 0) g_epoch[eb] = ep + 1;
}

struct Ring { uint32_t off, par, rel; };
__device__ __forceinline__ void desc_touch(const uint64_t (&c)[12][NS]) {
  uint32_t x = 0;
#pragma unroll
  for (int i = 0; i < 12 * NS; i += 4) x |= (uint32_t)(&c[0][0])[i];
  trap_if((x | (uint32_t)c[11][NS - 1]) == 0);
}
template <int TA, bool TAB, bool LOC = false>
__device__ __forceinline__ void gemm_steps(float (&a0)[64], float (&a1)[64], Ring& r, int n, const uint64_t (&c)[12][NS], int slot) {
#pragma unroll 1
  do {
    const uint32_t off = r.off, rel = r.rel;
    full_wait(B_FULL + off, r.par, slot++);
    r.rel = off;
    r.off += 8;
    if (r.off == 8 * NS) { r.off = 0; r.par ^= 1; }
    WG_FENCE();
#define DESC(i) (*(const uint64_t*)((const char*)c[i] + off))
#pragma unroll
    for (int k = 0; k < 4; k++) {
      const uint64_t db = TAB ? DESC(3 * k) : mkdesc(off * 256 + dlo(sb + 16384 + 32 * k, 16), 1024, 1);
      if (LOC) {
        const int acc = k || rel != B_DUMMY - B_EMPTY;
        wgmma_ss128p<TA>(a0, mkdesc(dlo(S_STG + 32768 + 1024 * k, 4096) - n * 1024, 512, 2), db, acc);
        wgmma_ss128p<TA>(a1, mkdesc(dlo(S_STG + 32768 + 8192 + 1024 * k, 4096) - n * 1024, 512, 2), db, acc);
      } else {
        wgmma_ss128<TA, 0, 1>(a0, TAB ? DESC(3 * k + 1) : mkdesc(off * 256 + dlo(sb + 32 * k, 16), 1024, 1), db);
        wgmma_ss128<TA, 0, 1>(a1, TAB ? DESC(3 * k + 2) : mkdesc(off * 256 + dlo(sb + 8192 + 32 * k, 16), 1024, 1), db);
      }
      if (k == RELK) {
        WG_COMMIT();
        WG_WAIT(1);
        if (elect_one()) mbar_arrive(B_EMPTY + rel);
      }
    }
#undef DESC
    if (RELK < 3) WG_COMMIT();
  } while (--n);
}

template <int I>
__device__ __forceinline__ void tail_steps(float (&a0)[64], float (&a1)[64], const Ptrs& p, float* op, const float (&g)[4], uint4& e, uint4& e0, int tid) {
  constexpr int sl = (64 - WIN + I / 2) % NS, k = 2 * (I & 1), J = I - TOFF;
  if (I == 0) WG_FENCE();
  wgmma_ss128<1, 0, 1>(a1, p.dc2[3 * k + 2][sl], p.dc2[3 * k][sl]);
  wgmma_ss128<1, 0, 1>(a1, p.dc2[3 * k + 5][sl], p.dc2[3 * k + 3][sl]);
  WG_COMMIT();
  if (J == 0) { WG_WAIT(TOFF + 1); reg_fence(a0); }
  if (RES == NS && I == (WIN == NS ? 3 : 0)) { WG_WAIT(WIN == NS ? 2 : 1); if (elect_one()) mbar_arrive(B_ZT + 8); }
  if (J >= 0 && J < 2 * NPB) {
    sched_fence_async<70 + 2 * I>();
    constexpr int o = J >= 0 ? J / 2 : 0, jj = jj_of(o), hf = J & 1;
    if (hf == 0) { e0 = e; e = lds128(e_addr(o + 1 < NPB ? o + 1 : 0, o + 1 == NPB) + tid * 16); }
    const uint32_t ex = hf ? e0.z : e0.x, ey = hf ? e0.w : e0.y;
    stg128(op + hf * 32 * DM + 16 * jj, __float_as_uint(fmaf(g[hf], a0[8 * jj + 2 * hf], bf_lo(ex))), __float_as_uint(fmaf(g[hf], a0[8 * jj + 2 * hf + 1], bf_hi(ex))),
           __float_as_uint(fmaf(g[hf], a0[8 * jj + 2 * hf + 4], bf_lo(ey))), __float_as_uint(fmaf(g[hf], a0[8 * jj + 2 * hf + 5], bf_hi(ey))));
    sched_fence_async<71 + 2 * I>();
  }
  if constexpr (I + 1 < 2 * WIN) tail_steps<I + 1>(a0, a1, p, op, g, e, e0, tid);
}

template <bool BY_SM>
__global__ void __launch_bounds__(512, 1) fused_kernel(const __grid_constant__ Maps m, const __grid_constant__ Ptrs p) {
  extern __shared__ __align__(1024) uint8_t smem_raw[];
  if (threadIdx.x == W0 * 32) {
    asm volatile("prefetch.tensormap [%0];" ::"l"(&m.x) : "memory");
    asm volatile("prefetch.tensormap [%0];" ::"l"(&m.bre) : "memory");
    asm volatile("prefetch.tensormap [%0];" ::"l"(&m.bim) : "memory");
  }
  int b = blockIdx.x;
  if (BY_SM) {
    int sm;
    asm("mov.u32 %0, %%smid;" : "=r"(sm));
    const int tp = sm >> 1, q = (tp * 37 - 1184) >> 8;
    const int lo = (tp & 7) * 8 + (tp >> 3), mid = (tp - 31 - 7 * q) * 8 + 4 + q, hi = tp + (tp < 62 ? 4 : -58);
    b = (tp < 32 ? lo : (tp < 60 ? mid : hi)) * 2 + (sm & 1);
  }
  const int spare = b - 128;
  const int ti = ((b >> 5) << 2) | (b & 3), pj = (((b >> 4) & 1) << 2) | ((b >> 2) & 3);
  const int wid = __shfl_sync(~0u, threadIdx.x >> 5, 0), wg = wid >> 2, tid = threadIdx.x & 127, lane = threadIdx.x & 31;
  if (wg == 0) TIM(0);
  const unsigned t_start = clock();
  if (wid == W0) {
    if (elect_one()) {
#pragma unroll
      for (int i = 0; i < NS; i++) mbar_init(B_FULL + 8 * i, (i < 2 && spare >= 0) ? 2 : 1);
    }
    __syncwarp();
    bar_arrive(1, 160);
    if (spare < 0 && elect_one()) {
      unsigned t = clock();
#pragma unroll 1
      for (int s = 0; s < NS; s++) {
        issue_g1(m, s, s, ti, pj);
        t += FILL;
        while ((int)(clock() - t) < 0) {}
      }
    }
  } else if (wid == 13) {
    if (elect_one()) {
      trap_if((uint32_t)__cvta_generic_to_shared(smem_raw) != sb);
#pragma unroll
      for (uint32_t bar = B_EMPTY; bar < S_EP; bar += 8) mbar_init(bar, (bar < B_CINF || (bar >= B_SFREE && bar < B_ZT) || bar == B_ZT + 8 || bar == B_XT + 16 || bar == B_XT + 24) ? 4 :
                           (bar < B_CINF + 16 || ((bar == B_PIN || bar == B_PIN + 8) && spare >= 0)) ? 2 : 1);
    }
  }
  __syncwarp();
  if (wg == 3) {
    asm volatile("setmaxnreg.dec.sync.aligned.u32 %0;" ::"n"(RV == 2 ? 32 : 24));
    bar_sync(1, 160);
    if (spare < 0) {
      if (wid == 13) { bar_arrive(2, 160); bar_arrive(12, 160); }
      bar_arrive(0, 256);
    } else {
      bar_arrive(0, 512);
    }
    if (wid == 13) {
      if (spare < 0) {
        const unsigned ep = ld_relaxed(g_epoch + b);
        kv_loader(m, ti, pj, t_start);
        poller(ti, pj, lane, ep);
      }
    } else if (wid == 15 || spare >= 0) {
      const ConvCtx cc = conv_ctx(spare, wid == 12 ? 0 : wid - 13, ti, pj);
      conv_loader(m, p, cc, spare < 0 ? b : 128 + cc.j, lane, t_start);
    } else if (wid == 12) {
      if (elect_one()) producer(m, ti, pj);
    } else {
      storer(m, ti, pj);
    }
  } else if (wg == 2 || spare >= 0) {
    asm volatile("setmaxnreg.inc.sync.aligned.u32 160;");
    if (HOLD) wait_clock(t_start + HOLD);
    conv_main(p, conv_ctx(spare, wg, ti, pj), spare < 0 ? b : 128 + spare * 3 + wg, tid);
  } else {
    asm volatile("setmaxnreg.inc.sync.aligned.u32 %0;" ::"n"(RV == 3 ? 168 : 160));
    if (wg == 1) {
      if (HOLD) wait_clock(t_start + HOLD);
      const int ch = (tid >> 6) * 512 + pj * 64 + (tid & 63);
      const unsigned ep = ld_relaxed(g_epoch + b);
      const float lr = __bfloat162float(p.lre[ch]), li = __bfloat162float(p.lim[ch]);
      const float dt = bf_round(expf(__bfloat162float(p.ldt[ch])));
      float sn, cs;
      sincosf(dt * li, &sn, &cs);
      const float ex = expf(dt * lr);
      const float ar = ex * cs, ai = ex * sn;
      const float inv = 2.f / (lr * lr + li * li);
      const float cr = ((ar - 1.f) * lr + ai * li) * inv, ci = (ai * lr - (ar - 1.f) * li) * inv;
      sts128(S_PAR + tid * 16, __float_as_uint(ar), __float_as_uint(ai), pack2(cr, cr), pack2(-ci, -ci));
      const cx l32 = csq(csq(csq(csq(csq({ar, ai}))))), l128 = csq(csq(l32));
      sts128(S_PAR + 2048 + tid * 16, __float_as_uint(l32.r), __float_as_uint(l32.i), __float_as_uint(l128.r), __float_as_uint(l128.i));
      if (tid == 0) asm volatile("st.shared.u32 [%0], %1;" ::"r"(S_EP), "r"(ep) : "memory");
      bar_arrive(6, 256);
      bar_sync(2, 160);
      desc_touch(p.dc1);
      desc_touch(p.dc2);
      prep<0>(p, ti, pj, wid & 3, lane);
    }
    float a0[64], a1[64];
    Ring ring = {8u * wg * (16 % NS), wg * ((16u / NS) & 1), B_DUMMY - B_EMPTY};
    zero(a0); zero(a1);
    reg_fence(a0); reg_fence(a1);
    sched_fence<61>();
    bar_sync(wg * 7, 256);
    TIM(2 + wg * 2);
    if (wg == 0) gemm_steps<0, false>(a0, a1, ring, 15, p.dc1, 0);
    else gemm_steps<0, true>(a0, a1, ring, 15, p.dc1, 16);
    bar_arrive(7 + wg, 256);
    gemm_steps<0, false>(a0, a1, ring, 1, p.dc1, wg * 16 + 15);
    if (wg == 0) bar_sync(6, 256);
    scan_epilogue(a0, a1, B_EMPTY + ring.rel, wg, ti, pj, tid);
    if (wg == 1) {
      eterm(p, ti, pj, tid);
    } else {
      ring = {8 * (32 % NS), (32 / NS) & 1, B_DUMMY - B_EMPTY};
#pragma unroll
      for (int i = 0; i < 64; i++) asm volatile("" : "=f"(a0[i]), "=f"(a1[i]));
      bar_sync(8, 256);
      TIM(6);
#pragma unroll 1
      for (int o = 0; o < 4; o++) {
        if (!(o & 1)) {
          if (o) TIM(18);
          full_wait(B_LOC + 4 * o, 0, 32 + 8 * o);
          gemm_steps<1, true, true>(a0, a1, ring, 2, p.dc2, 32 + 8 * o);
        }
        gemm_steps<1, true>(a0, a1, ring, (o & 1) ? (o == 1 ? 13 : 13 - RES) : 1, p.dc2, 34 + 16 * (o >> 1) + (o & 1));
        if (!(o & 1) && elect_one()) {
          mbar_arrive(o ? B_LOC + 16 : B_SFREE + 16);
        }
      }
      TIM(28);
      const int w = tid >> 5, trow = 64 * (w & 1) + 8 * (w >> 1) + (lane >> 2);
      float* op = p.out + (size_t)(ti * 128 + trow) * DM + pj * 128 + 4 * (lane & 3);
      float g[4];
      uint4 e;
#pragma unroll
      for (int i = 0; i < RES; i++) {
        const int sl = (64 - RES + i) % NS;
        full_wait(B_FULL + 8 * sl, ((64 - RES + i) / NS) & 1, 64 - RES + i);
        WG_FENCE();
#pragma unroll
        for (int k = 0; k < 4; k++) {
          wgmma_ss128<1, 0, 1>(a0, p.dc2[3 * k + 1][sl], p.dc2[3 * k][sl]);
          if (i == 0 && k == 1) { WG_COMMIT(); WG_WAIT(1); if (elect_one()) mbar_arrive(RES == NS ? B_EMPTY + ring.rel : B_ZT + 8); }
        }
        if (i >= WIN - 1 && i < RES - 1) {
          const int s1 = (64 - RES + i - WIN + 1) % NS;
#pragma unroll
          for (int k = 0; k < 4; k++) wgmma_ss128<1, 0, 1>(a1, p.dc2[3 * k + 2][s1], p.dc2[3 * k][s1]);
        }
        WG_COMMIT();
      }
      TIM(25);
      bar_sync(5, 256);
#pragma unroll
      for (int q = 0; q < 4; q++) g[q] = __uint_as_float(lds32(S_G + (trow + 16 * (q >> 1) + 32 * (q & 1)) * 4));
      e = lds128(e_addr(0, NPB == 0) + tid * 16);
      uint4 e0;
      tail_steps<0>(a0, a1, p, op, g, e, e0, tid);
      TIM(26);
      WG_WAIT(0);
      reg_fence(a1);
      TIM(7);
      uint4 ee[4], x[8], z[8];
      uint2 ds[4];
#pragma unroll
      for (int o = 1; o < 4; o++) ee[o] = lds128(e_addr(o, 1) + tid * 16);
      if (NPB < 4) ee[0] = lds128(e_addr(3, 0) + tid * 16);
      store_piece(a1, op + 16 * DM, jj_of(0), e, g[2], g[3]);
      store_piece(a1, op + 16 * DM, jj_of(1), ee[1], g[2], g[3]);
#define LATE_LOAD(h) { \
        sched_fence<90 + h>(); \
        bar_sync(6 + h, 256); \
        _Pragma("unroll") for (int i = 4 * h; i < 4 * h + 4; i++) { \
          x[i] = lds128(e_addr(4 + (i >> 1), i & 1) + tid * 16); \
          z[i] = ldsm4t(S_ZL + (i >> 1) * 4096 + z_off(w, lane, i & 1)); \
          if (i & 1) ds[i >> 1] = lds64(S_PAR + (4 + (i >> 1)) * 32 + (lane & 3) * 8); \
        } }
#define LATE_STORE(o) { store_late(a0, op, jj_of(4 + o), x[2 * o], z[2 * o], ds[o], g[0], g[1]); \
                        store_late(a1, op + 16 * DM, jj_of(4 + o), x[2 * o + 1], z[2 * o + 1], ds[o], g[2], g[3]); }
      LATE_LOAD(0);
      store_piece(a1, op + 16 * DM, jj_of(2), ee[2], g[2], g[3]);
      store_piece(a1, op + 16 * DM, jj_of(3), ee[3], g[2], g[3]);
      if (NPB < 4) store_piece(a0, op, jj_of(3), ee[0], g[0], g[1]);
      LATE_STORE(0);
      LATE_LOAD(1);
      LATE_STORE(1);
      sched_fence<92>();
      LATE_STORE(2);
      LATE_STORE(3);
#undef LATE_LOAD
#undef LATE_STORE
      if (tid == 0) g_epoch[b] = lds32(S_EP) + 1;
      TIM(19);
    }
  }
}

typedef CUresult (*EncFn)(CUtensorMap*, CUtensorMapDataType, cuuint32_t, void*, const cuuint64_t*, const cuuint64_t*,
                          const cuuint32_t*, const cuuint32_t*, CUtensorMapInterleave, CUtensorMapSwizzle,
                          CUtensorMapL2promotion, CUtensorMapFloatOOBfill);

void encode(EncFn enc, CUtensorMap* m, const void* ptr, int rank, const cuuint64_t* dims, const cuuint64_t* strides,
            const cuuint32_t* box, CUtensorMapSwizzle sw) {
  cuuint32_t es[5] = {1, 1, 1, 1, 1};
  enc(m, CU_TENSOR_MAP_DATA_TYPE_BFLOAT16, rank, const_cast<void*>(ptr), dims, strides, box, es, CU_TENSOR_MAP_INTERLEAVE_NONE,
      sw, PROMO, CU_TENSOR_MAP_FLOAT_OOB_FILL_NONE);
}

}

extern "C" void kernel_launch(void* const* d_in, const int* in_sizes, int n_in, void* d_out, int out_size) {
  typedef const __nv_bfloat16* bp;
  Ptrs p;
  p.x = (bp)d_in[0]; p.lre = (bp)d_in[1]; p.lim = (bp)d_in[2]; p.bre = (bp)d_in[3]; p.bim = (bp)d_in[4];
  p.cre = (bp)d_in[5]; p.cim = (bp)d_in[6]; p.ldt = (bp)d_in[7]; p.dskip = (bp)d_in[8];
  p.k = (bp)d_in[10]; p.v = (bp)d_in[11]; p.shift = (bp)d_in[12]; p.f = (bp)d_in[13]; p.ssmd = (bp)d_in[14];
  p.gw = (bp)d_in[15]; p.out = (float*)d_out;

  for (int sl = 0; sl < NS; sl++)
    for (int k = 0; k < 4; k++) {
      const uint64_t h128 = (uint64_t)(64u | (1u << 30)) << 32, h64 = (uint64_t)(32u | (2u << 30)) << 32;
      const uint32_t st = sb + sl * STAGE;
      p.dc1[3 * k][sl] = p.dc2[3 * k][sl] = h128 | dlo(st + 16384 + 32 * k, 16);
      p.dc1[3 * k + 1][sl] = h128 | dlo(st + 32 * k, 16);
      p.dc1[3 * k + 2][sl] = h128 | dlo(st + 8192 + 32 * k, 16);
      p.dc2[3 * k + 1][sl] = h64 | dlo(st + 1024 * k, 4096);
      p.dc2[3 * k + 2][sl] = h64 | dlo(st + 8192 + 1024 * k, 4096);
    }
  EncFn enc = nullptr;
  cudaDriverEntryPointQueryResult qr;
  cudaGetDriverEntryPoint("cuTensorMapEncodeTiled", (void**)&enc, cudaEnableDefault, &qr);
  void *zptr = nullptr, *uptr = nullptr;
  cudaGetSymbolAddress(&zptr, g_z);
  cudaGetSymbolAddress(&uptr, g_u);

  Maps m;
  {
    cuuint64_t d[4] = {1024, 2, 64, 16}, s[3] = {2048, 65536, 4096};
    cuuint32_t bx[4] = {64, 2, 4, 16};
    encode(enc, &m.x, p.x, 4, d, s, bx, CU_TENSOR_MAP_SWIZZLE_128B);
  }
  {
    cuuint64_t d[2] = {1024, 1024}, s[1] = {2048};
    cuuint32_t bx[2] = {64, 64};
    encode(enc, &m.bre, p.bre, 2, d, s, bx, CU_TENSOR_MAP_SWIZZLE_128B);
    encode(enc, &m.bim, p.bim, 2, d, s, bx, CU_TENSOR_MAP_SWIZZLE_128B);
  }
  {
    cuuint64_t d[5] = {1024, 2, 4, 2, 64}, s[4] = {2048, 8192, 4096, 32768};
    cuuint32_t bx[5] = {64, 2, 4, 2, 8};
    encode(enc, &m.cre, p.cre, 5, d, s, bx, CU_TENSOR_MAP_SWIZZLE_128B);
    encode(enc, &m.cim, p.cim, 5, d, s, bx, CU_TENSOR_MAP_SWIZZLE_128B);
  }
  {
    cuuint64_t d[3] = {64, 32, 1024}, s[2] = {128, 4096};
    cuuint32_t bx[3] = {64, 1, 32};
    encode(enc, &m.u, uptr, 3, d, s, bx, CU_TENSOR_MAP_SWIZZLE_NONE);
  }
  {
    cuuint64_t d[3] = {1024, 256, 8}, s[2] = {16384, 2048};
    cuuint32_t bx[3] = {64, 8, 4}, bh[3] = {64, 1, 3};
    encode(enc, &m.k, p.k, 3, d, s, bx, CU_TENSOR_MAP_SWIZZLE_128B);
    encode(enc, &m.kh, p.k, 3, d, s, bh, CU_TENSOR_MAP_SWIZZLE_NONE);
    encode(enc, &m.v, p.v, 3, d, s, bx, CU_TENSOR_MAP_SWIZZLE_128B);
  }
  {
    cuuint64_t d[5] = {2048, 2, 4, 2, 64}, s[4] = {4096, 16384, 8192, 65536};
    cuuint32_t bx[5] = {64, 2, 4, 2, 1};
    encode(enc, &m.z, zptr, 5, d, s, bx, CU_TENSOR_MAP_SWIZZLE_128B);
  }
  {
    cuuint64_t d[4] = {1024, 2, 4, 256}, s[3] = {8192, 2048, 16384};
    cuuint32_t bx[4] = {64, 2, 4, 16};
    encode(enc, &m.x2, p.x, 4, d, s, bx, CU_TENSOR_MAP_SWIZZLE_128B);
  }
  int dev = 0, nsm = 0;
  cudaGetDevice(&dev);
  cudaDeviceGetAttribute(&nsm, cudaDevAttrMultiProcessorCount, dev);
  auto kern = nsm == 132 ? fused_kernel<true> : fused_kernel<false>;
  cudaFuncSetAttribute(kern, cudaFuncAttributeMaxDynamicSharedMemorySize, SMEM_BYTES);
  kern<<<132, 512, SMEM_BYTES, cudaStreamPerThread>>>(m, p);
}
```

```cpp
#include <cuda_runtime.h>
#include <cuda_bf16.h>
#include <cuda.h>
#include <stdint.h>

namespace {

constexpr int SEQ = 2048, DM = 1024;
#define NSV 5
constexpr int NS = NSV;
constexpr int STAGE = 32768;
#define KV0_AT 300
#define KV_GAP0 600
#define KV1_AT 8200
#define KV_GAP1 450
#define SFM 0
#define RV 1
#define POLL_NS 60
#define IM_NS 40
#define SPF_AT 7000
#define RELK 0
#define RES 4
#define AGG_NS 200
#define ZL_NS 60
#define P2F 3
#define KEEP 16
#define IM_LATE 1
#define MAP 0
#define WIN 4
#define NPB 3
#define TOFF 1
#define W0 8
#define HOLD 1200
#define FILL 450
#define GATE_NS 250
#define POLL_AT 17000
#define LD_GAP 400
#define LDQ ""
#define PROMO CU_TENSOR_MAP_L2_PROMOTION_L2_128B
constexpr uint32_t sb = 1024;
constexpr uint32_t S_STG = sb + NS * STAGE;
constexpr uint32_t S_CIN = S_STG + 32768;
constexpr uint32_t S_T = S_CIN + 16384;
constexpr uint32_t S_M1 = S_T + 8192;
constexpr uint32_t S_M2 = S_M1 + 4096;
constexpr uint32_t S_PAR = S_M2 + 2048;
constexpr uint32_t S_G = S_PAR + 4096;
constexpr uint32_t S_BAR = S_G + 512;
constexpr int SMEM_BYTES = S_BAR + 512 - sb;
constexpr uint32_t B_FULL = S_BAR, B_EMPTY = B_FULL + 8 * NS, B_CINF = B_EMPTY + 8 * NS,
                   B_FLG = B_CINF + 24, B_SFREE = B_FLG + 72, B_LOC = B_SFREE + 24, B_ZT = B_LOC + 24,
                   B_XT = B_ZT + 16, B_PIN = B_XT + 24, B_DUMMY = B_PIN + 32, S_EP = B_DUMMY + 8;
constexpr int SPIN_LIMIT = 1 << 21;
constexpr int F_H = 0, F_U = 128, F_Z = 144;

struct alignas(64) Maps { CUtensorMap x, b, cre, cim, u, z, x2, k, kh, v; };
struct Ptrs {
  uint32_t bsw, pad;
  const __nv_bfloat16 *x, *lre, *lim, *ldt, *dskip, *k, *v, *shift, *f, *ssmd, *gw, *bre, *bim, *cre, *cim;
  float* out;
  uint64_t dc1[12][NS], dc2[12][NS];
};

__device__ uint4 g_h[16 * 32 * 1024];
__device__ uint4 g_u[1024 * 256];
__device__ uint4 g_z[1024 * 256];
__device__ uint4 g_agg[2 * 16 * 256];
__device__ unsigned g_gate[8 * SEQ];
__device__ unsigned g_flag[152 * 32];
__device__ unsigned g_epoch[140];
#define TIM(i)
#define TIMC(i)

#define WG_FENCE() asm volatile("wgmma.fence.sync.aligned;" ::: "memory")
#define WG_COMMIT() asm volatile("wgmma.commit_group.sync.aligned;" ::: "memory")
#define WG_WAIT(n) asm volatile("wgmma.wait_group.sync.aligned %0;" ::"n"(n) : "memory")
#define R8(d, o) "+f"(d[o + 0]), "+f"(d[o + 1]), "+f"(d[o + 2]), "+f"(d[o + 3]), "+f"(d[o + 4]), "+f"(d[o + 5]), "+f"(d[o + 6]), "+f"(d[o + 7])
#define W8(d, o) "=f"(d[o + 0]), "=f"(d[o + 1]), "=f"(d[o + 2]), "=f"(d[o + 3]), "=f"(d[o + 4]), "=f"(d[o + 5]), "=f"(d[o + 6]), "=f"(d[o + 7])
#define L16 "%0,%1,%2,%3,%4,%5,%6,%7,%8,%9,%10,%11,%12,%13,%14,%15"
#define L64 L16 ",%16,%17,%18,%19,%20,%21,%22,%23,%24,%25,%26,%27,%28,%29,%30,%31," \
  "%32,%33,%34,%35,%36,%37,%38,%39,%40,%41,%42,%43,%44,%45,%46,%47,%48,%49,%50,%51,%52,%53,%54,%55,%56,%57,%58,%59,%60,%61,%62,%63"

template <int TA, int TB, int ACC>
__device__ __forceinline__ void wgmma_ss128(float (&d)[64], uint64_t da, uint64_t db) {
  if (ACC)
    asm volatile("wgmma.mma_async.sync.aligned.m64n128k16.f32.bf16.bf16 {" L64 "}, %64, %65, 1, 1, 1, %66, %67;"
                 : R8(d, 0), R8(d, 8), R8(d, 16), R8(d, 24), R8(d, 32), R8(d, 40), R8(d, 48), R8(d, 56)
                 : "l"(da), "l"(db), "n"(TA), "n"(TB));
  else
    asm volatile("wgmma.mma_async.sync.aligned.m64n128k16.f32.bf16.bf16 {" L64 "}, %64, %65, 0, 1, 1, %66, %67;"
                 : W8(d, 0), W8(d, 8), W8(d, 16), W8(d, 24), W8(d, 32), W8(d, 40), W8(d, 48), W8(d, 56)
                 : "l"(da), "l"(db), "n"(TA), "n"(TB));
}
template <int TA>
__device__ __forceinline__ void wgmma_ss128p(float (&d)[64], uint64_t da, uint64_t db, int acc) {
  asm volatile("{.reg .pred p; setp.ne.b32 p, %67, 0;\n"
               "wgmma.mma_async.sync.aligned.m64n128k16.f32.bf16.bf16 {" L64 "}, %64, %65, p, 1, 1, %66, 0;}"
               : R8(d, 0), R8(d, 8), R8(d, 16), R8(d, 24), R8(d, 32), R8(d, 40), R8(d, 48), R8(d, 56)
               : "l"(da), "l"(db), "n"(TA), "r"(acc));
}
template <int ACC, int TB = 0>
__device__ __forceinline__ void wgmma_rs32(float (&d)[16], uint32_t a0, uint32_t a1, uint32_t a2, uint32_t a3, uint64_t db) {
  if (ACC)
    asm volatile("wgmma.mma_async.sync.aligned.m64n32k16.f32.bf16.bf16 {" L16 "}, {%16,%17,%18,%19}, %20, 1, 1, 1, %21;"
                 : R8(d, 0), R8(d, 8) : "r"(a0), "r"(a1), "r"(a2), "r"(a3), "l"(db), "n"(TB));
  else
    asm volatile("wgmma.mma_async.sync.aligned.m64n32k16.f32.bf16.bf16 {" L16 "}, {%16,%17,%18,%19}, %20, 0, 1, 1, %21;"
                 : W8(d, 0), W8(d, 8) : "r"(a0), "r"(a1), "r"(a2), "r"(a3), "l"(db), "n"(TB));
}
template <int N>
__device__ __forceinline__ void reg_fence(float (&d)[N]) {
#pragma unroll
  for (int i = 0; i < N; i++) asm volatile("" : "+f"(d[i])::"memory");
}
__host__ __device__ __forceinline__ constexpr uint32_t dlo(uint32_t addr, uint32_t lbo) { return (addr >> 4) + ((lbo >> 4) << 16); }
__device__ __forceinline__ uint64_t mkdesc(uint32_t lo, uint32_t sbo, uint32_t mode) {
  uint64_t d;
  asm("mov.b64 %0, {%1, %2};" : "=l"(d) : "r"(lo), "r"((sbo >> 4) | (mode << 30)));
  return d;
}
template <int N>
__device__ __forceinline__ void zero(float (&d)[N]) {
#pragma unroll
  for (int i = 0; i < N; i++) d[i] = 0.f;
}
__device__ __forceinline__ void trap_if(int c) {
  asm volatile("{.reg .pred p; .reg .b64 z; setp.ne.s32 p, %0, 0; mov.b64 z, 0; @p st.global.u32 [z], %0;}" ::"r"(c) : "memory");
}
template <int K>
__device__ __forceinline__ void sched_fence() {
  asm volatile("{.reg .pred p; setp.eq.u32 p, %0, %1; @p exit;}" ::"r"(blockIdx.x), "n"(256 + K) : "memory");
}
template <int K>
__device__ __forceinline__ void sched_fence_async() {
  asm volatile("{.reg .pred p; .reg .u32 r; setp.ne.u32 p, %0, %1; @p bra.uni SFE;\n"
               "SFL: nanosleep.u32 1000; mov.u32 r, %%clock; setp.eq.u32 p, r, 0; @p bra.uni SFL;\nSFE: }" ::"r"(blockIdx.x), "n"(256 + K) : "memory");
}
__device__ __forceinline__ bool elect_one() {
  uint32_t pred;
  asm volatile("{.reg .pred p; elect.sync _|p, 0xffffffff; selp.u32 %0, 1, 0, p;}" : "=r"(pred));
  return pred;
}
__device__ __forceinline__ void mbar_init(uint32_t bar, uint32_t cnt) {
  asm volatile("mbarrier.init.shared::cta.b64 [%0], %1;" ::"r"(bar), "r"(cnt) : "memory");
}
__device__ __forceinline__ bool mbar_try(uint32_t bar, uint32_t par) {
  uint32_t ok;
  asm volatile("{.reg .pred p; mbarrier.try_wait.parity.shared::cta.b64 p, [%1], %2; selp.u32 %0, 1, 0, p;}"
               : "=r"(ok) : "r"(bar), "r"(par) : "memory");
  return ok;
}
#undef DBGV
#define DBGV ((bar - S_BAR) * 2 + par)
__device__ __forceinline__ void mbar_wait(uint32_t bar, uint32_t par) {
  if (__builtin_expect(!mbar_try(bar, par), 0)) {
    int n = SPIN_LIMIT;
    while (!mbar_try(bar, par) && --n) {}
    trap_if(n == 0);
  }
}
#define full_wait(bar, par, slot) mbar_wait(bar, par)
__device__ __forceinline__ void mbar_wait_long(uint32_t bar, uint32_t par) {
  int n = SPIN_LIMIT;
  while (!mbar_try(bar, par) && --n) __nanosleep(100);
  trap_if(n == 0);
}
#undef DBGV
#define DBGV 0
__device__ __forceinline__ void mbar_arrive(uint32_t bar) {
  asm volatile("mbarrier.arrive.shared::cta.b64 _, [%0];" ::"r"(bar) : "memory");
}
__device__ __forceinline__ void mbar_expect(uint32_t bar, uint32_t bytes) {
  asm volatile("mbarrier.arrive.expect_tx.shared::cta.b64 _, [%0], %1;" ::"r"(bar), "r"(bytes) : "memory");
}
__device__ __forceinline__ void tma2d(uint32_t dst, const CUtensorMap* m, uint32_t bar, int c0, int c1) {
  asm volatile("cp.async.bulk.tensor.2d.shared::cluster.global.mbarrier::complete_tx::bytes [%0], [%1, {%3, %4}], [%2];"
               ::"r"(dst), "l"(m), "r"(bar), "r"(c0), "r"(c1) : "memory");
}
__device__ __forceinline__ void tma3d(uint32_t dst, const CUtensorMap* m, uint32_t bar, int c0, int c1, int c2) {
  asm volatile("cp.async.bulk.tensor.3d.shared::cluster.global.mbarrier::complete_tx::bytes [%0], [%1, {%3, %4, %5}], [%2];"
               ::"r"(dst), "l"(m), "r"(bar), "r"(c0), "r"(c1), "r"(c2) : "memory");
}
__device__ __forceinline__ void tma4d(uint32_t dst, const CUtensorMap* m, uint32_t bar, int c0, int c1, int c2, int c3) {
  asm volatile("cp.async.bulk.tensor.4d.shared::cluster.global.mbarrier::complete_tx::bytes [%0], [%1, {%3, %4, %5, %6}], [%2];"
               ::"r"(dst), "l"(m), "r"(bar), "r"(c0), "r"(c1), "r"(c2), "r"(c3) : "memory");
}
__device__ __forceinline__ void tma5d(uint32_t dst, const CUtensorMap* m, uint32_t bar, int c0, int c1, int c2, int c3, int c4) {
  asm volatile("cp.async.bulk.tensor.5d.shared::cluster.global.mbarrier::complete_tx::bytes [%0], [%1, {%3, %4, %5, %6, %7}], [%2];"
               ::"r"(dst), "l"(m), "r"(bar), "r"(c0), "r"(c1), "r"(c2), "r"(c3), "r"(c4) : "memory");
}
__device__ __forceinline__ void bulk_load(uint32_t dst, const void* src, uint32_t bytes, uint32_t bar) {
  asm volatile("cp.async.bulk.shared::cluster.global.mbarrier::complete_tx::bytes [%0], [%1], %2, [%3];"
               ::"r"(dst), "l"(src), "r"(bytes), "r"(bar) : "memory");
}
__device__ __forceinline__ void l2_prefetch(const void* src, uint32_t bytes) {
  asm volatile("cp.async.bulk.prefetch.L2.global [%0], %1;" ::"l"(src), "r"(bytes) : "memory");
}
__device__ __forceinline__ void bar_sync(int id, int n) { asm volatile("bar.sync %0, %1;" ::"r"(id), "r"(n) : "memory"); }
__device__ __forceinline__ void bar_arrive(int id, int n) { asm volatile("bar.arrive %0, %1;" ::"r"(id), "r"(n) : "memory"); }
__device__ __forceinline__ void fence_async_smem() { asm volatile("fence.proxy.async.shared::cta;" ::: "memory"); }
__device__ __forceinline__ void fence_async_global() { asm volatile("fence.proxy.async.global;" ::: "memory"); }
__device__ __forceinline__ void flag_add(int f) {
  asm volatile("red.relaxed.gpu.global.add.u32 [%0], 1;" ::"l"(g_flag + f * 32) : "memory");
}
__device__ __forceinline__ void flag_release(int f) {
  asm volatile("fence.release.gpu;" ::: "memory");
  flag_add(f);
}
__device__ __forceinline__ unsigned ld_relaxed(const unsigned* p) {
  unsigned v;
  asm volatile("ld.relaxed.gpu.global.u32 %0, [%1];" : "=r"(v) : "l"(p) : "memory");
  return v;
}
__device__ __forceinline__ void wait_clock(unsigned t) {
  int d;
  while ((d = (int)(t - (unsigned)clock())) > 0) __nanosleep(d > 600 ? 200 : 40);
}
__device__ __forceinline__ uint32_t pack2(float lo, float hi) {
  uint32_t r;
  asm("cvt.rn.bf16x2.f32 %0, %1, %2;" : "=r"(r) : "f"(hi), "f"(lo));
  return r;
}
__device__ __forceinline__ float bf_lo(uint32_t v) { return __uint_as_float(v << 16); }
__device__ __forceinline__ float bf_hi(uint32_t v) { return __uint_as_float(v & 0xffff0000u); }
__device__ __forceinline__ float bf_round(float v) { return __bfloat162float(__float2bfloat16_rn(v)); }
__device__ __forceinline__ uint32_t hmul2(uint32_t a, uint32_t b) {
  uint32_t r;
  asm("mul.rn.bf16x2 %0, %1, %2;" : "=r"(r) : "r"(a), "r"(b));
  return r;
}
__device__ __forceinline__ uint32_t hadd2(uint32_t a, uint32_t b) {
  uint32_t r;
  asm("add.rn.bf16x2 %0, %1, %2;" : "=r"(r) : "r"(a), "r"(b));
  return r;
}
__device__ __forceinline__ uint32_t hsub2(uint32_t a, uint32_t b) {
  uint32_t r;
  asm("sub.rn.bf16x2 %0, %1, %2;" : "=r"(r) : "r"(a), "r"(b));
  return r;
}
__device__ __forceinline__ uint32_t hfma2(uint32_t a, uint32_t b, uint32_t c) {
  uint32_t r;
  asm("fma.rn.bf16x2 %0, %1, %2, %3;" : "=r"(r) : "r"(a), "r"(b), "r"(c));
  return r;
}
__device__ __forceinline__ uint32_t hneg2(uint32_t a) {
  uint32_t r;
  asm("neg.bf16x2 %0, %1;" : "=r"(r) : "r"(a));
  return r;
}
__device__ __forceinline__ uint4 ldg128(const void* p) {
  uint4 v;
  asm volatile("ld.global.nc" LDQ ".v4.u32 {%0,%1,%2,%3}, [%4];" : "=r"(v.x), "=r"(v.y), "=r"(v.z), "=r"(v.w) : "l"(p));
  return v;
}
__device__ __forceinline__ uint2 ldg64(const void* p) {
  uint2 v;
  asm volatile("ld.global.nc.v2.u32 {%0,%1}, [%2];" : "=r"(v.x), "=r"(v.y) : "l"(p));
  return v;
}
__device__ __forceinline__ void stg128(void* p, uint32_t a, uint32_t b, uint32_t c, uint32_t d) {
  asm volatile("st.global.v4.u32 [%0], {%1,%2,%3,%4};" ::"l"(p), "r"(a), "r"(b), "r"(c), "r"(d) : "memory");
}
__device__ __forceinline__ void sts128(uint32_t a, uint32_t x, uint32_t y, uint32_t z, uint32_t w) {
  asm volatile("st.shared.v4.u32 [%0], {%1,%2,%3,%4};" ::"r"(a), "r"(x), "r"(y), "r"(z), "r"(w) : "memory");
}
__device__ __forceinline__ uint32_t lds32(uint32_t a) {
  uint32_t v;
  asm volatile("ld.shared.u32 %0, [%1];" : "=r"(v) : "r"(a) : "memory");
  return v;
}
__device__ __forceinline__ uint4 lds128(uint32_t a) {
  uint4 v;
  asm volatile("ld.shared.v4.u32 {%0,%1,%2,%3}, [%4];" : "=r"(v.x), "=r"(v.y), "=r"(v.z), "=r"(v.w) : "r"(a) : "memory");
  return v;
}
__device__ __forceinline__ void stsm4(uint32_t a, uint32_t x, uint32_t y, uint32_t z, uint32_t w) {
  asm volatile("stmatrix.sync.aligned.m8n8.x4.shared.b16 [%0], {%1,%2,%3,%4};" ::"r"(a), "r"(x), "r"(y), "r"(z), "r"(w) : "memory");
}
__device__ __forceinline__ void stsm4t(uint32_t a, uint32_t x, uint32_t y, uint32_t z, uint32_t w) {
  asm volatile("stmatrix.sync.aligned.m8n8.x4.trans.shared.b16 [%0], {%1,%2,%3,%4};" ::"r"(a), "r"(x), "r"(y), "r"(z), "r"(w) : "memory");
}
__device__ __forceinline__ uint4 ldsm4t(uint32_t a) {
  uint4 v;
  asm volatile("ldmatrix.sync.aligned.m8n8.x4.trans.shared.b16 {%0,%1,%2,%3}, [%4];" : "=r"(v.x), "=r"(v.y), "=r"(v.z), "=r"(v.w) : "r"(a) : "memory");
  return v;
}
struct cx { float r, i; };
__device__ __forceinline__ cx cmul(cx a, cx b) { return {a.r * b.r - a.i * b.i, a.r * b.i + a.i * b.r}; }
__device__ __forceinline__ cx cfma(cx a, cx b, cx c) { return {fmaf(a.r, b.r, fmaf(-a.i, b.i, c.r)), fmaf(a.r, b.i, fmaf(a.i, b.r, c.i))}; }
__device__ __forceinline__ cx csq(cx a) { return {a.r * a.r - a.i * a.i, 2.f * a.r * a.i}; }
__device__ __forceinline__ cx unit(int num, int den) {
  int m = num & (den - 1);
  if (m >= den / 2) m -= den;
  float s, c;
  __sincosf((float)m * (-6.283185307179586f / (float)den), &s, &c);
  return {c, s};
}

__device__ __forceinline__ uint2 lds64(uint32_t a) {
  uint2 v;
  asm volatile("ld.shared.v2.u32 {%0,%1}, [%2];" : "=r"(v.x), "=r"(v.y) : "r"(a) : "memory");
  return v;
}
__device__ __forceinline__ void prep_taps(const uint4 (&sh)[2], uint32_t (&s)[2][4]) {
#pragma unroll
  for (int e = 0; e < 2; e++) {
    s[e][0] = __byte_perm(sh[e].x, sh[e].z, 0x5410); s[e][1] = __byte_perm(sh[e].x, sh[e].z, 0x7632);
    s[e][2] = __byte_perm(sh[e].y, sh[e].w, 0x5410); s[e][3] = __byte_perm(sh[e].y, sh[e].w, 0x7632);
  }
}
__device__ __forceinline__ void prep_math(const uint2 (&kk)[11], uint2 (&vv)[8], const uint32_t (&s)[2][4]) {
#pragma unroll
  for (int i = 0; i < 8; i++)
#pragma unroll
    for (int e = 0; e < 2; e++) {
      uint32_t a = hmul2((&kk[i].x)[e], s[e][3]);
      a = hfma2((&kk[i + 1].x)[e], s[e][2], a);
      a = hfma2((&kk[i + 2].x)[e], s[e][1], a);
      a = hfma2((&kk[i + 3].x)[e], s[e][0], a);
      (&vv[i].x)[e] = hmul2(a, (&vv[i].x)[e]);
    }
}
__device__ __forceinline__ void prep_store(const uint2 (&vv)[8], int d, int tb) {
  uint4* dst = g_u + (size_t)((d >> 5) * 32 + (tb >> 3)) * 256 + (d & 31) * 8 + ((tb & 7) ^ ((tb >> 3) & 1));
#pragma unroll
  for (int e = 0; e < 2; e++) {
#define U(i) (&vv[i].x)[e]
    stg128(dst + (2 * e) * 8, __byte_perm(U(0), U(1), 0x5410), __byte_perm(U(2), U(3), 0x5410),
           __byte_perm(U(4), U(5), 0x5410), __byte_perm(U(6), U(7), 0x5410));
    stg128(dst + (2 * e + 1) * 8, __byte_perm(U(0), U(1), 0x7632), __byte_perm(U(2), U(3), 0x7632),
           __byte_perm(U(4), U(5), 0x7632), __byte_perm(U(6), U(7), 0x7632));
#undef U
  }
}
template <int PG>
__device__ __forceinline__ void prep(const Ptrs& p, int ti, int pj, int w, int lane) {
  const int tb = lane & 7, chunk = 2 * w + (lane >> 4), ch = chunk * 8 + ((lane >> 3) & 1) * 4, d = pj * 128 + PG * 64 + ch;
  const uint4 sh[2] = {ldg128(p.shift + d * 4), ldg128(p.shift + d * 4 + 8)};
  uint32_t s[2][4];
  prep_taps(sh, s);
#pragma unroll 1
  for (int th = 0; th < 2; th++) {
    uint2 kk[11], vv[8];
    {
      const uint32_t in = S_STG + th * 16384 + (lane & 8);
      const uint32_t a0 = in + tb * 128 + ((chunk ^ tb) << 4);
      const uint32_t hb = tb ? in + (39 + tb) * 128 + ((chunk ^ (tb - 1)) << 4) : S_T + (PG * 2 + th) * 512 + ch * 2;
      const uint32_t hs = tb ? 1024 : 128;
      mbar_wait_long(B_PIN + 16 * PG + 8 * th, 0);
      if (th) TIM(29 + PG);
#pragma unroll
      for (int i = 0; i < 3; i++) kk[i] = lds64(hb + i * hs);
#pragma unroll
      for (int i = 0; i < 8; i++) { kk[3 + i] = lds64(a0 + i * 1024); vv[i] = lds64(a0 + 8192 + i * 1024); }
      prep_math(kk, vv, s);
      sched_fence<52 + PG>();
    }
    if (!PG) bar_arrive(th ? 11 : 3, 160);
    else if (elect_one()) mbar_arrive(B_SFREE + 8 * th);
    prep_store(vv, d, ti * 16 + th * 8 + tb);
  }
  bar_arrive(4 + PG, 160);
}

__device__ __forceinline__ void gate_finish(int ti, int tid, uint32_t tag) {
  float l;
  int n = SPIN_LIMIT;
  bool bad;
  do {
    __nanosleep(GATE_NS);
    uint32_t v[8], x = 0;
#pragma unroll
    for (int j = 0; j < 8; j++) v[j] = ld_relaxed(g_gate + j * SEQ + ti * 128 + tid) ^ tag;
    l = 0.f;
#pragma unroll
    for (int j = 0; j < 8; j++) { x |= v[j]; l += __uint_as_float(v[j]); }
    bad = __any_sync(~0u, x & 3);
  } while (bad && --n);
  trap_if(n == 0);
  const float g = bf_round(__fdividef(1.f, 1.f + __expf(-bf_round(l))));
  asm volatile("st.shared.f32 [%0], %1;" ::"r"(S_G + tid * 4), "f"(g) : "memory");
}

__device__ __forceinline__ void conv_tables(int tid) {
  {
    const int s = tid >> 5, n1 = tid & 31;
    uint32_t re[4], im[4];
#pragma unroll
    for (int e = 0; e < 4; e++) {
      cx a = unit(n1 * (4 * (8 * s + 2 * e) + 1), 128), b = unit(n1 * (4 * (8 * s + 2 * e + 1) + 1), 128);
      re[e] = pack2(a.r * 0.125f, b.r * 0.125f); im[e] = pack2(a.i * 0.125f, b.i * 0.125f);
    }
    sts128(S_M1 + (2 * s) * 512 + n1 * 16, re[0], re[1], re[2], re[3]);
    sts128(S_M1 + (2 * s + 1) * 512 + n1 * 16, im[0], im[1], im[2], im[3]);
  }
  {
    const int kg = tid >> 5, n = tid & 31;
    const int pi = kg >> 1, po = n >> 4, f2 = n & 15;
    uint32_t fw[4];
#pragma unroll
    for (int e = 0; e < 4; e++) {
      int n2 = (kg & 1) * 8 + 2 * e;
      cx a = unit(n2 * f2, 16), b = unit((n2 + 1) * f2, 16);
      float sg = pi ? -1.f : 1.f;
      float x0 = (pi == po) ? a.r : sg * a.i, x1 = (pi == po) ? b.r : sg * b.i;
      fw[e] = pack2(x0, x1);
    }
    sts128(S_M2 + kg * 512 + n * 16, fw[0], fw[1], fw[2], fw[3]);
  }
  fence_async_smem();
}
__device__ __forceinline__ constexpr int jj_of(int o) { return o == 7 ? 3 : o + (o >= 3); }
__device__ __forceinline__ int conv_chan(int ti, int pj, int jj) { return pj * 128 + jj * 16 + ti; }

struct ConvCtx {
  uint32_t buf, inbar;
  int nb, n;
  int ti, pj, j;
  __device__ __forceinline__ int chan(int c) const {
    return j < 0 ? conv_chan(ti, pj, jj_of(c)) : conv_chan(((j + 12 * c) >> 3) + (((j + 12 * c) >> 3) >= KEEP), (j + 12 * c) & 7, 3);
  }
};
__device__ __forceinline__ ConvCtx conv_ctx(int spare, int wg, int ti, int pj) {
  const int j = spare < 0 ? -1 : spare * 3 + wg;
  return {wg == 2 ? S_CIN : sb + wg * 32768, wg == 2 ? B_CINF : (wg ? B_PIN : B_FULL), 4 + 4 * wg, j < 0 ? 7 + (ti == KEEP) : (j < 8 && KEEP > 15 ? 11 : 10), ti, pj, j};
}
#define CDESC(a) mkdesc(dlo(a, 512), 128, 0)
struct ConvTw { uint32_t r[2], i[2], n[2]; };

__device__ __forceinline__ void cv_tw1(float (&d)[64], uint32_t (&R)[16], uint32_t (&I)[16], const ConvTw& t, int i) {
#pragma unroll
  for (int j = 8 * (i & 1); j < 8 * (i & 1) + 8; j++) {
    if (i < 2) {
      R[j] = pack2(d[4 * j], d[4 * j + 1]); I[j] = pack2(d[4 * j + 2], d[4 * j + 3]);
    } else {
      const uint32_t xr = R[j], xi = I[j];
      R[j] = hfma2(xr, t.r[j & 1], hmul2(xi, t.n[j & 1]));
      I[j] = hfma2(xr, t.i[j & 1], hmul2(xi, t.r[j & 1]));
    }
  }
}
template <int N>
__device__ __forceinline__ void cv_pack(float (&X)[16], uint32_t (&P)[N][2][2], int q) {
#pragma unroll
  for (int k = 0; k < 2; k++)
#pragma unroll
    for (int j = 0; j < 4; j++) P[2 * q + k][j >> 1][j & 1] = pack2(X[4 * j + 2 * k], X[4 * j + 2 * k + 1]);
}
__device__ __forceinline__ void cv_overlap(uint32_t (&P)[8][2][2]) {
#pragma unroll
  for (int k = 3; k > 0; k--)
#pragma unroll
    for (int hh = 0; hh < 2; hh++) {
      P[k][0][hh] = hsub2(P[k][0][hh], P[k - 1][1][hh]);
      P[k][1][hh] = hadd2(P[k][1][hh], P[k - 1][0][hh]);
    }
}
__device__ __forceinline__ void cv_pw(uint32_t (&P)[8][2][2], uint32_t (&Q)[4][2][2]) {
#pragma unroll
  for (int jh = 0; jh < 8; jh++) {
    const int j = jh >> 1, hh = jh & 1;
    uint32_t qr = hmul2(P[4 + j][0][hh], P[0][0][hh]), qi = hmul2(P[4 + j][0][hh], P[0][1][hh]);
    qr = hfma2(hneg2(P[4 + j][1][hh]), P[0][1][hh], qr);
    qi = hfma2(P[4 + j][1][hh], P[0][0][hh], qi);
#pragma unroll
    for (int k = j - 1; k >= 0; k--) {
      qr = hfma2(P[4 + k][0][hh], P[j - k][0][hh], qr);
      qi = hfma2(P[4 + k][0][hh], P[j - k][1][hh], qi);
      qr = hfma2(hneg2(P[4 + k][1][hh]), P[j - k][1][hh], qr);
      qi = hfma2(P[4 + k][1][hh], P[j - k][0][hh], qi);
    }
    Q[j][0][hh] = qr; Q[j][1][hh] = qi;
  }
}
__device__ __forceinline__ void cv_tw2(uint32_t (&Q)[4][2][2], const ConvTw& t, int k) {
#pragma unroll
  for (int hh = 0; hh < 2; hh++) {
    const uint32_t xr = Q[k][0][hh], xi = Q[k][1][hh];
    Q[k][0][hh] = hfma2(xr, t.r[hh], hmul2(xi, t.i[hh]));
    Q[k][1][hh] = hfma2(xr, t.n[hh], hmul2(xi, t.r[hh]));
  }
}
__device__ __forceinline__ void cv_out0(float (&Y)[16], uint32_t T, int w, int lane) {
  reg_fence(Y);
  const uint32_t za = T + w * 2048 + (lane >> 4) * 256 + (lane & 7) * 32 + (((lane >> 3) ^ (lane >> 2)) & 1) * 16;
#pragma unroll
  for (int jj = 0; jj < 2; jj++)
    stsm4t(za + jj * 512, pack2(Y[8 * jj], Y[8 * jj + 1]), pack2(Y[8 * jj + 2], Y[8 * jj + 3]),
           pack2(Y[8 * jj + 4], Y[8 * jj + 5]), pack2(Y[8 * jj + 6], Y[8 * jj + 7]));
}

__device__ __forceinline__ void cv_out1(const uint4& z0, const uint4& z1, const ConvCtx& cc, uint32_t keep, uint32_t tag, int ch, int w, int lane) {
  uint4* zp = g_z + (size_t)cc.chan(ch) * 256 + w * 64 + lane;
#define TG(v) ((v & keep) | (tag & ~keep))
  asm volatile("st.relaxed.gpu.global.v4.u32 [%0], {%1,%2,%3,%4};" ::"l"(zp), "r"(TG(z0.x)), "r"(TG(z0.y)), "r"(TG(z0.z)), "r"(TG(z0.w)) : "memory");
  asm volatile("st.relaxed.gpu.global.v4.u32 [%0], {%1,%2,%3,%4};" ::"l"(zp + 32), "r"(TG(z1.x)), "r"(TG(z1.y)), "r"(TG(z1.z)), "r"(TG(z1.w)) : "memory");
#undef TG
}
template <bool FW, bool BW, int K>
__device__ __forceinline__ void conv_step(uint32_t (&Q)[4][2][2], const ConvTw& t, const ConvCtx& cc, float dl, uint32_t tag, int ch, int w, int lane) {
#define SF(n) if ((SFM >> (n)) & 1) sched_fence_async<K + (n)>()
  float d[64], X[4][16], Z[2][16], Y[16];
  uint32_t R[16], I[16];
  uint4 a[4];
  const int nx = ch + 1;
  const uint32_t T = cc.buf + 16384;
  float dv;
  TIMC(1);
  if (FW) {
    dv = __shfl_sync(~0u, dl, nx);
    mbar_wait(cc.inbar + 8 * (nx & 1), (nx >> 1) & 1);
  }
  TIMC(2);
  WG_FENCE();
  if (BW) {
#pragma unroll
    for (int q = 0; q < 2; q++) {
      wgmma_rs32<0, 1>(Z[q], Q[2 * q][0][0], Q[2 * q + 1][0][0], Q[2 * q][0][1], Q[2 * q + 1][0][1], mkdesc(dlo(S_M2, 128), 512, 0));
      wgmma_rs32<1, 1>(Z[q], Q[2 * q][1][0], Q[2 * q + 1][1][0], Q[2 * q][1][1], Q[2 * q + 1][1][1], mkdesc(dlo(S_M2 + 256, 128), 512, 0));
    }
    WG_COMMIT();
  }
  if (FW) {
    const uint32_t lo = dlo(0, 1024) + (cc.buf >> 4) + (nx & 1) * 512;
    wgmma_ss128<1, 1, 0>(d, mkdesc(dlo(S_M1, 128), 512, 0), mkdesc(lo, 256, 3));
    wgmma_ss128<1, 1, 1>(d, mkdesc(dlo(S_M1 + 256, 128), 512, 0), mkdesc(lo + 32, 256, 3));
    WG_COMMIT();
  }
  TIMC(3);
  if (BW) {
    TIMC(4);
    WG_WAIT(FW ? 1 : 0);
    TIMC(5);
    reg_fence(Z[0]); reg_fence(Z[1]);
    uint32_t V[4][2][2];
    cv_pack(Z[0], V, 0); cv_pack(Z[1], V, 1);
    SF(0);
#pragma unroll
    for (int k = 0; k < 4; k++) cv_tw2(V, t, k);
    bar_sync(cc.nb, 128);
#pragma unroll
    for (int k = 0; k < 4; k++) stsm4(T + w * 512 + lane * 16 + k * 2048, V[k][0][0], V[k][0][1], V[k][1][0], V[k][1][1]);
    SF(1);
    TIMC(6);
  }
  if (FW) {
    WG_WAIT(0);
    reg_fence(d);
    if (nx + 2 < cc.n) bar_arrive(cc.nb + 2 + (nx & 1), 160);
    cv_tw1(d, R, I, t, 0); cv_tw1(d, R, I, t, 1);
    SF(2);
    TIMC(7);
  }
  if (BW) {
    bar_sync(cc.nb, 128);
#pragma unroll
    for (int s = 0; s < 4; s++) a[s] = ldsm4t(T + (4 * w + s) * 512 + lane * 16);
  }
  if (FW) { cv_tw1(d, R, I, t, 2); cv_tw1(d, R, I, t, 3); }
  sched_fence<K + 3>();
  TIMC(8);
  WG_FENCE();
  if (BW) {
    wgmma_rs32<0>(Y, a[0].x, a[0].y, a[0].z, a[0].w, CDESC(S_M1));
#pragma unroll
    for (int i = 1; i < 4; i++) wgmma_rs32<1>(Y, a[i].x, a[i].y, a[i].z, a[i].w, CDESC(S_M1 + 1024 * i));
  }
  if (FW) {
#pragma unroll
    for (int q = 0; q < 4; q++) {
      if (q == 2) WG_COMMIT();
      wgmma_rs32<0>(X[q], R[4 * q], R[4 * q + 2], R[4 * q + 1], R[4 * q + 3], CDESC(S_M2));
      wgmma_rs32<1>(X[q], I[4 * q], I[4 * q + 2], I[4 * q + 1], I[4 * q + 3], CDESC(S_M2 + 1024));
    }
  }
  WG_COMMIT();
  TIMC(9);
  WG_WAIT(FW ? 1 : 0);
  TIMC(10);
  uint4 z0, z1;
  const uint32_t zr = T + w * 2048 + (lane ^ ((lane >> 3) & 1)) * 16;
  if (BW) {
    cv_out0(Y, T, w, lane);
    __syncwarp();
  }
  if (FW) {
    uint32_t P[8][2][2];
    reg_fence(X[0]); reg_fence(X[1]);
    cv_pack(X[0], P, 0); cv_pack(X[1], P, 1);
    cv_overlap(P);
    if (BW) { z0 = lds128(zr); z1 = lds128(zr + 512); }
    sched_fence_async<K + 7>();
    WG_WAIT(0);
    reg_fence(X[2]); reg_fence(X[3]);
    X[2][0] += dv; X[2][1] += dv; X[2][4] += dv; X[2][5] += dv;
    cv_pack(X[2], P, 2); cv_pack(X[3], P, 3);
    SF(4);
    TIMC(11);
    cv_pw(P, Q);
    SF(8);
  } else {
    z0 = lds128(zr); z1 = lds128(zr + 512);
  }
  if (BW) cv_out1(z0, z1, cc, FW && cc.j < 0 && ch < 4 ? ~0u : ~1u, tag, ch, w, lane);
  sched_fence<K + 5>();
  TIMC(13);
#undef SF
}

__device__ __forceinline__ void conv_main(const Ptrs& p, const ConvCtx& cc, int eb, int tid) {
  const int ti = cc.ti, pj = cc.pj;
  const int w = tid >> 5, lane = tid & 31;
  const unsigned ep = ld_relaxed(g_epoch + eb);
  const __nv_bfloat16 dsk = p.ssmd[cc.chan(min(lane, cc.n - 1))];
  if (cc.nb == 12) conv_tables(tid);
  if (cc.j < 0) bar_sync(12, 160); else bar_sync(0, 512);
  ConvTw t;
#pragma unroll
  for (int hh = 0; hh < 2; hh++) {
    const int n2 = 8 * hh + 2 * (lane & 3), m = 4 * (8 * w + (lane >> 2)) + 1;
    cx a = unit(n2 * m, 2048), b = unit((n2 + 1) * m, 2048);
    t.r[hh] = pack2(a.r, b.r); t.i[hh] = pack2(a.i, b.i); t.n[hh] = pack2(-a.i, -b.i);
  }
  const uint32_t tag = (ep + 1) & 3;
  const float dl = 0.125f * __bfloat162float(dsk);
  if (cc.j < 0) prep<1>(p, ti, pj, w, lane);
  {
    uint32_t P[4][2][2];
    mbar_wait_long(cc.inbar, 0);
    TIM(20);
    conv_step<true, false, 10>(P, t, cc, dl, tag, -1, w, lane);
#pragma unroll 1
    for (int ch = 0; ch < cc.n - 1; ch++) {
      conv_step<true, true, 20>(P, t, cc, dl, tag, ch, w, lane);
      if (cc.j < 0 && ch == 3) bar_arrive(0, 160);
      if (ch == 0) TIM(21);
    }
    conv_step<false, true, 30>(P, t, cc, dl, tag, cc.n - 1, w, lane);
  }
  TIM(22);
}

__device__ __forceinline__ cx csel(bool k, cx a, cx b) { return {k ? a.r : b.r, k ? a.i : b.i}; }
__device__ __forceinline__ void ld2cx(uint32_t a, cx& x, cx& y) {
  const uint4 v = lds128(a);
  x = {__uint_as_float(v.x), __uint_as_float(v.y)};
  y = {__uint_as_float(v.z), __uint_as_float(v.w)};
}
__device__ __forceinline__ cx ldcx(uint32_t a) {
  cx x;
  asm volatile("ld.shared.v2.f32 {%0,%1}, [%2];" : "=f"(x.r), "=f"(x.i) : "r"(a) : "memory");
  return x;
}

__device__ __forceinline__ void scan_epilogue(float (&aR)[64], float (&aI)[64], uint32_t last_empty, int ph, int ti, int pj, int tid) {
  const int w = tid >> 5, lane = tid & 31, r = lane >> 2, c = lane & 3;
  const uint32_t par = S_PAR + (ph * 64 + 16 * w + r) * 16;
  uint4* agg = g_agg + ph * 16 * 256 + pj * 32 + 8 * w + r;
  const uint32_t tag = (lds32(S_EP) + 1) & 3;
  cx h[2];
  {
    cx lam[2], a[2];
#pragma unroll
    for (int q = 0; q < 2; q++) { lam[q] = ldcx(par + q * 128); h[q] = ldcx(par + 2048 + q * 128); }
    WG_WAIT(0);
    if (elect_one()) mbar_arrive(last_empty);
    asm volatile("setmaxnreg.inc.sync.aligned.u32 168;");
    reg_fence(aR); reg_fence(aI);
    TIM(3 + ph * 2);
#pragma unroll
    for (int q = 0; q < 2; q++) a[q] = {aR[2 * q], aI[2 * q]};
#pragma unroll
    for (int s = 1; s < 32; s++)
#pragma unroll
      for (int q = 0; q < 2; q++) {
        const int i = 4 * (s >> 1) + 2 * q + (s & 1);
        a[q] = cfma(lam[q], a[q], {aR[i], aI[i]});
      }
    sched_fence<1>();
    cx t[2][3];
#pragma unroll
    for (int q = 0; q < 2; q++)
#pragma unroll
      for (int k = 0; k < 3; k++) t[q][k] = {__shfl_up_sync(~0u, a[q].r, k + 1, 4), __shfl_up_sync(~0u, a[q].i, k + 1, 4)};
#pragma unroll
    for (int q = 0; q < 2; q++) {
      const cx z = {0.f, 0.f};
      cx ex = cfma(h[q], csel(c >= 3, t[q][2], z), csel(c >= 2, t[q][1], z));
      ex = cfma(h[q], ex, csel(c >= 1, t[q][0], z));
      a[q] = cfma(h[q], ex, a[q]);
      const cx u = cfma(lam[q], ex, {aR[2 * q], aI[2 * q]});
      aR[2 * q] = u.r; aI[2 * q] = u.i;
    }
    if (c == 3)
      asm volatile("st.relaxed.gpu.global.v4.u32 [%0], {%1,%2,%3,%4};" ::"l"(agg + ti * 256),
                   "r"((__float_as_uint(a[0].r) & ~3u) | tag), "r"((__float_as_uint(a[0].i) & ~3u) | tag),
                   "r"((__float_as_uint(a[1].r) & ~3u) | tag), "r"((__float_as_uint(a[1].i) & ~3u) | tag) : "memory");
    TIM(8 + ph * 4);
  }
  if (ti > 0) {
    const uint2* ap = (const uint2*)(agg + (ti - 1 - (c >> 1)) * 256) + (c & 1);
    const int cnt = ti - (c >> 1);
    const cx one = {1.f, 0.f};
    const cx l128 = ldcx(par + 2048 + 8 + (c & 1) * 128), l256 = csq(l128), fa = csel(c & 2, l128, one);
#pragma unroll
    for (int q = 0; q < 2; q++) h[q] = cmul(csel(c & 1, h[q], one), csel(c & 2, csq(h[q]), one));
    uint2 v[8];
    int n = SPIN_LIMIT;
    bool bad;
    __nanosleep(AGG_NS);
    do {
      uint32_t x = 0;
#pragma unroll
      for (int j = 0; j < 8; j++) {
        v[j] = make_uint2(tag, tag);
        asm volatile("{.reg .pred p; setp.lt.s32 p, %3, %4; @p ld.relaxed.gpu.global.v2.u32 {%0,%1}, [%2];}"
                     : "+r"(v[j].x), "+r"(v[j].y) : "l"(ap - j * 1024), "r"(2 * j), "r"(cnt) : "memory");
      }
#pragma unroll
      for (int j = 0; j < 8; j++) { v[j].x ^= tag; v[j].y ^= tag; x |= v[j].x | v[j].y; }
      bad = __any_sync(~0u, x & 3);
    } while (bad && --n);
    trap_if(n == 0);
    cx a = {__uint_as_float(v[7].x), __uint_as_float(v[7].y)};
#pragma unroll
    for (int j = 6; j >= 0; j--) a = cfma(l256, a, {__uint_as_float(v[j].x), __uint_as_float(v[j].y)});
    a = cmul(a, fa);
    const cx t1 = {__shfl_xor_sync(~0u, a.r, 1), __shfl_xor_sync(~0u, a.i, 1)};
    const cx t2 = {__shfl_xor_sync(~0u, a.r, 2), __shfl_xor_sync(~0u, a.i, 2)};
    const cx t3 = {__shfl_xor_sync(~0u, a.r, 3), __shfl_xor_sync(~0u, a.i, 3)};
    const cx own = {a.r + t2.r, a.i + t2.i}, oth = {t1.r + t3.r, t1.i + t3.i};
#pragma unroll
    for (int q = 0; q < 2; q++) h[q] = cmul(csel((c & 1) == q, own, oth), h[q]);
  } else {
    h[0] = h[1] = {0.f, 0.f};
  }
  TIM(9 + ph * 4);
  cx lam[2];
  uint32_t cr[2], nci[2];
#pragma unroll
  for (int q = 0; q < 2; q++) {
    const uint4 v = lds128(par + q * 128);
    lam[q] = {__uint_as_float(v.x), __uint_as_float(v.y)};
    cr[q] = v.z; nci[q] = v.w;
  }
  uint4* hg = g_h + (size_t)(ti * 32 + ph * 16 + pj) * 1024 + w * 64 + r * 4 + (c ^ (r >> 1));
  const uint32_t hs = S_STG + w * 1024 + r * 64 + ((c ^ (r >> 1)) << 4);
  uint32_t pr[4][2][4], pi[4][2][4], re[4][2][4];
#pragma unroll
  for (int i = 0; i < 4; i++) {
#pragma unroll
    for (int s2 = 0; s2 < 4; s2++)
#pragma unroll
      for (int q = 0; q < 2; q++) {
        const int k = 4 * (4 * i + s2) + 2 * q;
        cx h0 = cfma(lam[q], h[q], {aR[k], aI[k]});
        h[q] = cfma(lam[q], h0, {aR[k + 1], aI[k + 1]});
        pr[i][q][s2] = pack2(h0.r, h[q].r);
        pi[i][q][s2] = pack2(h0.i, h[q].i);
        re[i][q][s2] = hfma2(pr[i][q][s2], cr[q], hmul2(pi[i][q][s2], nci[q]));
      }
#pragma unroll
    for (int q = 0; q < 2; q++) {
      stg128(hg + i * 256 + q * 32, re[i][q][0], re[i][q][1], re[i][q][2], re[i][q][3]);
    }
    if (i == 0 && (P2F & 1)) sched_fence<7>();
    if (i == 1 && (P2F & 2)) sched_fence<8>();
    if (i == 2 && (P2F & 1)) sched_fence<6>();
  }
  bar_arrive(9, 160);
  sched_fence<9>();
  TIM(10 + ph * 4);
  mbar_wait(B_SFREE + 16 * ph, 0);
  if (ph == 0) mbar_wait(B_SFREE + 8, 0);
#pragma unroll
  for (int q = 0; q < 2; q++) {
    const uint32_t ncr = cr[q] ^ 0x80008000u;
#pragma unroll
    for (int i = 0; i < 4; i++) {
#pragma unroll
      for (int s2 = 0; s2 < 4; s2++) pi[i][q][s2] = hfma2(pi[i][q][s2], ncr, hmul2(pr[i][q][s2], nci[q]));
      sts128(hs + i * 4096 + q * 512, re[i][q][0], re[i][q][1], re[i][q][2], re[i][q][3]);
      sts128(hs + 16384 + i * 4096 + q * 512, pi[i][q][0], pi[i][q][1], pi[i][q][2], pi[i][q][3]);
      if (!IM_LATE) {
        if (IM_NS) __nanosleep(IM_NS);
        stg128(hg + 8192 + i * 256 + q * 32, pi[i][q][0], pi[i][q][1], pi[i][q][2], pi[i][q][3]);
      }
    }
  }
  fence_async_smem();
  __syncwarp();
  if (elect_one()) mbar_arrive(B_LOC + 8 * ph);
  if (IM_LATE) {
#pragma unroll
    for (int i = 0; i < 8; i++) {
      stg128(hg + 8192 + (i >> 1) * 256 + (i & 1) * 32, pi[i >> 1][i & 1][0], pi[i >> 1][i & 1][1], pi[i >> 1][i & 1][2], pi[i >> 1][i & 1][3]);
      if (IM_NS) __nanosleep(IM_NS);
    }
  }
  bar_arrive(10, 160);
  bar_sync(1 + ph, 128);
  asm volatile("setmaxnreg.dec.sync.aligned.u32 160;");
}

__device__ __forceinline__ constexpr uint32_t e_addr(int o, int mh) { return S_STG + (o * 2 + mh) * 2048; }
__device__ __forceinline__ uint32_t z_off(int w, int lane, int mh) {
  return (w & 1) * 2048 + (lane & 15) * 128 + (((4 * (lane >> 4) + 2 * mh + (w >> 1)) ^ (lane & 7)) << 4);
}
constexpr uint32_t S_ZL = sb + (59 % NS) * STAGE;
__device__ __forceinline__ void eterm(const Ptrs& p, int ti, int pj, int tid) {
  const int w = tid >> 5, lane = tid & 31, r = lane >> 2, c = lane & 3;
  const int trow = 64 * (w & 1) + 8 * (w >> 1) + r;
  const int rs = 2 * (r & 3) + (r >> 2);
  uint2 xv[2][8][2], ds[8];
  {
    uint2 gw[8];
#pragma unroll
    for (int jj = 0; jj < 8; jj++) {
      gw[jj] = ldg64(p.gw + pj * 128 + 16 * jj + 4 * c);
      ds[jj] = ldg64(p.dskip + pj * 128 + 16 * jj + 4 * c);
    }
#pragma unroll
    for (int g = 0; g < 2; g++) {
      mbar_wait(B_XT + 8 * g, 0);
#pragma unroll
      for (int i = 0; i < 4; i++)
#pragma unroll
        for (int jj = 4 * g; jj < 4 * g + 4; jj++)
          xv[i >> 1][jj][i & 1] = lds64(sb + ((48 + g) % NS) * STAGE + (trow - r + rs + 16 * (i >> 1) + 32 * (i & 1)) * 128 + (((2 * (jj & 3) + (c >> 1)) ^ rs) << 4) + (c & 1) * 8);
    }
    fence_async_smem();
    __syncwarp();
    if (elect_one()) mbar_arrive(B_XT + 16);
    sched_fence<55>();
    TIM(27);
    float s[4];
#pragma unroll
    for (int i = 0; i < 4; i++) {
      s[i] = 0.f;
#pragma unroll
      for (int jj = 0; jj < 8; jj += 2) {
        const uint2 x = xv[i >> 1][jj][i & 1], y = xv[i >> 1][jj + 1][i & 1];
        const uint32_t q = hfma2(x.x, gw[jj].x, hfma2(x.y, gw[jj].y, hfma2(y.x, gw[jj + 1].x, hmul2(y.y, gw[jj + 1].y))));
        s[i] += bf_lo(q) + bf_hi(q);
      }
    }
    float u0 = (c & 1) ? s[1] : s[0], v0 = (c & 1) ? s[0] : s[1];
    float u1 = (c & 1) ? s[3] : s[2], v1 = (c & 1) ? s[2] : s[3];
    u0 += __shfl_xor_sync(~0u, v0, 1);
    u1 += __shfl_xor_sync(~0u, v1, 1);
    float u = (c & 2) ? u1 : u0;
    u += __shfl_xor_sync(~0u, (c & 2) ? u0 : u1, 2);
    const uint32_t tag = (lds32(S_EP) + 1) & 3;
    asm volatile("st.relaxed.gpu.global.u32 [%0], %1;" ::"l"(g_gate + pj * SEQ + ti * 128 + trow + 16 * (c >> 1) + 32 * (c & 1)),
                 "r"((__float_as_uint(u) & ~3u) | tag) : "memory");
    gate_finish(ti, tid, tag);
  }
  bar_sync(2, 128);
  TIM(31);
  uint32_t g2[2][2], og2[2][2];
#pragma unroll
  for (int mh = 0; mh < 2; mh++)
#pragma unroll
    for (int hf = 0; hf < 2; hf++) {
      uint32_t g;
      asm volatile("ld.shared.u32 %0, [%1];" : "=r"(g) : "r"(S_G + (trow + 16 * mh + 32 * hf) * 4) : "memory");
      g2[mh][hf] = __byte_perm(g, g, 0x3232);
      og2[mh][hf] = hsub2(0x3f803f80u, g2[mh][hf]);
    }
  mbar_wait_long(B_LOC + 16, 0);
#pragma unroll
  for (int o = 4; o < 8; o++) {
    const int jj = jj_of(o);
#pragma unroll
    for (int mh = 0; mh < 2; mh++) sts128(e_addr(o, mh) + tid * 16, xv[mh][jj][0].x, xv[mh][jj][0].y, xv[mh][jj][1].x, xv[mh][jj][1].y);
    if (tid < 4) asm volatile("st.shared.v2.u32 [%0], {%1,%2};" ::"r"(S_PAR + o * 32 + tid * 8), "r"(ds[jj].x), "r"(ds[jj].y) : "memory");
  }
  mbar_wait_long(B_ZT, 0);
#pragma unroll
  for (int mh = 0; mh < 2; mh++)
#pragma unroll
    for (int o = 0; o < 4; o++) {
      const int jj = jj_of(o);
      const uint4 z = ldsm4t(S_STG + o * 4096 + z_off(w, lane, mh));
#pragma unroll
      for (int hf = 0; hf < 2; hf++) {
        uint2& x = xv[mh][jj][hf];
        x.x = hmul2(x.x, hfma2(og2[mh][hf], hf ? z.z : z.x, hmul2(g2[mh][hf], ds[jj].x)));
        x.y = hmul2(x.y, hfma2(og2[mh][hf], hf ? z.w : z.y, hmul2(g2[mh][hf], ds[jj].y)));
      }
    }
  bar_sync(2, 128);
#pragma unroll
  for (int mh = 0; mh < 2; mh++)
#pragma unroll
    for (int o = 0; o < 4; o++) {
      const int jj = jj_of(o);
      sts128(e_addr(o, mh) + tid * 16, xv[mh][jj][0].x, xv[mh][jj][0].y, xv[mh][jj][1].x, xv[mh][jj][1].y);
    }
  bar_arrive(5, 256);
  TIM(1);
  const uint32_t tag = (lds32(S_EP) + 1) & 1;
  const int zn = tid >> 4, ck = tid & 15;
  const uint4* zp = g_z + (size_t)(pj * 128 + 4 * (zn >> 1) + (zn & 1)) * 256 + ti * 16 + ck;
  uint4 v[2][4];
#define ZLOAD(g) _Pragma("unroll") for (int i = 0; i < 4; i++) \
    asm volatile("ld.relaxed.gpu.global.v4.u32 {%0,%1,%2,%3}, [%4];" : "=r"(v[g][i].x), "=r"(v[g][i].y), "=r"(v[g][i].z), "=r"(v[g][i].w) \
                 : "l"(zp + (jj_of(4 + 2 * g + (i >> 1)) * 16 + 2 * (i & 1)) * 256) : "memory")
  mbar_wait_long(B_ZT + 8, 0);
  ZLOAD(0);
  ZLOAD(1);
#pragma unroll
  for (int g = 0; g < 2; g++) {
    int it = SPIN_LIMIT;
    while (true) {
      uint32_t x = 0;
#pragma unroll
      for (int i = 0; i < 4; i++) {
        v[g][i].x ^= tag; v[g][i].y ^= tag; v[g][i].z ^= tag; v[g][i].w ^= tag;
        x |= v[g][i].x | v[g][i].y | v[g][i].z | v[g][i].w;
      }
      if (!__any_sync(~0u, x & 1) || !--it) break;
      __nanosleep(ZL_NS);
      ZLOAD(g);
    }
    trap_if(it == 0);
#pragma unroll
    for (int i = 0; i < 4; i++)
      sts128(S_ZL + (2 * g + (i >> 1)) * 4096 + (ck >> 3) * 2048 + (8 * (i & 1) + zn) * 128 + (((ck & 7) ^ zn) << 4), v[g][i].x, v[g][i].y, v[g][i].z, v[g][i].w);
    bar_arrive(6 + g, 256);
    if (g == 0) TIM(23);
  }
#undef ZLOAD
  TIM(17);
}

__device__ __forceinline__ void store_late(float (&a)[64], float* op, int jj, const uint4& x, const uint4& z, const uint2& ds, float g0, float g1) {
#pragma unroll
  for (int hf = 0; hf < 2; hf++) {
    const float g = hf ? g1 : g0, og = bf_round(1.f - g);
    const uint32_t x0 = hf ? x.z : x.x, x1 = hf ? x.w : x.y, z0 = hf ? z.z : z.x, z1 = hf ? z.w : z.y;
    const int k = 8 * jj + 2 * hf;
    stg128(op + hf * 32 * DM + 16 * jj,
           __float_as_uint(fmaf(g, a[k], bf_lo(x0) * fmaf(og, bf_lo(z0), g * bf_lo(ds.x)))),
           __float_as_uint(fmaf(g, a[k + 1], bf_hi(x0) * fmaf(og, bf_hi(z0), g * bf_hi(ds.x)))),
           __float_as_uint(fmaf(g, a[k + 4], bf_lo(x1) * fmaf(og, bf_lo(z1), g * bf_lo(ds.y)))),
           __float_as_uint(fmaf(g, a[k + 5], bf_hi(x1) * fmaf(og, bf_hi(z1), g * bf_hi(ds.y)))));
  }
}
__device__ __forceinline__ void store_piece(float (&a)[64], float* op, int jj, const uint4& e, float g0, float g1) {
  stg128(op + 16 * jj, __float_as_uint(fmaf(g0, a[8 * jj], bf_lo(e.x))), __float_as_uint(fmaf(g0, a[8 * jj + 1], bf_hi(e.x))),
         __float_as_uint(fmaf(g0, a[8 * jj + 4], bf_lo(e.y))), __float_as_uint(fmaf(g0, a[8 * jj + 5], bf_hi(e.y))));
  stg128(op + 32 * DM + 16 * jj, __float_as_uint(fmaf(g1, a[8 * jj + 2], bf_lo(e.z))), __float_as_uint(fmaf(g1, a[8 * jj + 3], bf_hi(e.z))),
         __float_as_uint(fmaf(g1, a[8 * jj + 6], bf_lo(e.w))), __float_as_uint(fmaf(g1, a[8 * jj + 7], bf_hi(e.w))));
}

__device__ __forceinline__ void issue_g1(const Maps& m, int s, int sl, int ti, int pj) {
  const uint32_t bar = B_FULL + 8 * sl, dst = sb + sl * STAGE;
  const int k0 = (s & 15) * 64, ch = (s >> 4) * 512 + pj * 64;
  mbar_expect(bar, STAGE);
  tma4d(dst + 16384, &m.x, bar, k0, 0, 4 * ti, 0);
  tma3d(dst, &m.b, bar, k0, ch, 0);
}
#define SLOT_WAIT "{.reg .pred p; .reg .u32 n; .reg .b64 z;\n mov.u32 n, 0;\n" \
    "W: mbarrier.try_wait.parity.shared::cta.b64 p, [%0 + %2], %1;\n @p bra.uni G;\n" \
    "add.u32 n, n, 1; setp.lt.u32 p, n, %3; @p bra.uni W;\n mov.b64 z, 0; st.global.u32 [z], n;\n" \
    "G: mbarrier.arrive.expect_tx.shared::cta.b64 _, [%0], 32768;\n"
__device__ __forceinline__ void producer(const Maps& m, int ti, int pj) {
  uint32_t bar = B_FULL, par = 0;
#define NEXT_SLOT() const uint32_t b0 = bar, p0 = par, dst = (bar - B_FULL) * (STAGE / 8) + sb; \
    bar += 8; if (bar == B_FULL + 8 * NS) { bar = B_FULL; par ^= 1; }
#pragma unroll 1
  for (int ph = 0; ph < 2; ph++)
#pragma unroll 1
    for (int k0 = ph ? 0 : NS * 64; k0 < 1024; k0 += 64) {
      NEXT_SLOT();
      asm volatile(SLOT_WAIT
          "cp.async.bulk.tensor.4d.shared::cluster.global.mbarrier::complete_tx::bytes [%4], [%6, {%8, %11, %10, %11}], [%0];\n"
          "cp.async.bulk.tensor.3d.shared::cluster.global.mbarrier::complete_tx::bytes [%5], [%7, {%8, %9, %11}], [%0];}"
          ::"r"(b0), "r"(p0), "n"(8 * NS), "n"(SPIN_LIMIT), "r"(dst + 16384), "r"(dst), "l"(&m.x), "l"(&m.b), "r"(k0),
            "r"(ph * 512 + pj * 64), "r"(4 * ti), "r"(0) : "memory");
    }
#pragma unroll 1
  for (int seg = 0; seg < 8; seg++) {
    const int ph = seg >> 2, part = (seg >> 1) & 1;
    if ((seg & 3) == 0) {
#pragma unroll 1
      for (int u = 0; u < 2; u++) {
        NEXT_SLOT();
        mbar_wait(b0 + 8 * NS, p0);
        mbar_expect(b0, 16384);
        tma5d(dst + 16384, u ? &m.cim : &m.cre, b0, ph * 512 + pj * 64, 0, 0, 0, pj * 8);
        if (ph) {
          mbar_expect(B_XT + 8 * u, 16384);
          tma4d(dst, &m.x2, B_XT + 8 * u, pj * 128 + u * 64, 0, 0, ti * 16);
        }
      }
    }
    const CUtensorMap* cm = part ? &m.cim : &m.cre;
    const uint4* hp = g_h + (size_t)(ti * 4 + (seg >> 1)) * 8192;
    const int s0 = (pj ^ (seg << 2)) & 4;
    mbar_wait(B_FLG + 8 * seg, 0);
    fence_async_global();
    if (seg == 4) TIM(24);
    if (seg == 5) mbar_wait(B_XT + 16, 0);
#pragma unroll 1
    for (int src = s0; src < s0 + 4; src++) {
      if (src == pj) continue;
      NEXT_SLOT();
      asm volatile(SLOT_WAIT
          "cp.async.bulk.shared::cluster.global.mbarrier::complete_tx::bytes [%5], [%7], 16384, [%0];\n"
          "cp.async.bulk.tensor.5d.shared::cluster.global.mbarrier::complete_tx::bytes [%4], [%6, {%8, %10, %10, %10, %9}], [%0];}"
          ::"r"(b0), "r"(p0), "n"(8 * NS), "n"(SPIN_LIMIT), "r"(dst + 16384), "r"(dst), "l"(cm), "l"(hp + src * 1024),
            "r"(ph * 512 + src * 64), "r"(pj * 8), "r"(0) : "memory");
    }
  }
#undef NEXT_SLOT
}

__device__ __forceinline__ void poller(int ti, int pj, int lane, unsigned ep) {
  if (lane < 9) {
    const int f = lane < 8 ? F_H + ((lane >> 1) * 16 + ti) * 2 + ((pj >> 2) ^ (lane & 1)) : F_Z + pj;
    const unsigned need = (ep + 1) * (lane < 8 ? 4 : 16);
    int n = SPIN_LIMIT;
    unsigned todo = 0x1ffu;
    do {
      const unsigned hit = __ballot_sync(0x1ffu, (int)(ld_relaxed(g_flag + f * 32) - need) >= 0) & todo;
      if (hit) {
        asm volatile("fence.acquire.gpu;" ::: "memory");
        if ((hit >> lane) & 1) mbar_arrive(B_FLG + 8 * lane);
        todo ^= hit;
        if (!todo) break;
      }
      if (POLL_NS) __nanosleep(POLL_NS);
    } while (--n);
    trap_if(n == 0);
  }
}
__device__ __forceinline__ void storer(const Maps& m, int ti, int pj) {
#pragma unroll 1
  for (int job = 0; job < 6; job++) {
    bar_sync(job < 2 ? 4 + job : 9 + (job & 1), 160);
    if (elect_one()) flag_release(job < 2 ? F_U + pj * 2 + job : F_H + ((job - 2) * 16 + ti) * 2 + (pj >> 2));
    __syncwarp();
    if (job == 2 || job == 4) TIM(7 + job * 2);
  }
  if (elect_one()) {
    mbar_wait_long(B_LOC + 16, 0);
    mbar_wait_long(B_FLG + 64, 0);
    fence_async_global();
    mbar_expect(B_ZT, 16384);
#pragma unroll 1
    for (int o = 0; o < 4; o++) {
      tma5d(S_STG + o * 4096, &m.z, B_ZT, ti * 128, 0, 0, 0, pj * 8 + jj_of(o));
      tma5d(S_STG + o * 4096 + 2048, &m.z, B_ZT, ti * 128 + 64, 0, 0, 0, pj * 8 + jj_of(o));
    }
  }
}

__device__ __forceinline__ void kv_loader(const Maps& m, int ti, int pj, unsigned t_start) {
  unsigned tt = t_start + KV0_AT;
#pragma unroll 1
  for (int st = 0; st < 4; st++) {
    const int d = pj * 128 + (st >> 1) * 64, tb = ti * 16 + (st & 1) * 8;
    const uint32_t bar = B_PIN + 8 * st;
    if (st >= 2) { bar_sync(st == 2 ? 3 : 11, 160); fence_async_smem(); }
    if (elect_one()) {
      mbar_expect(bar, 16384 + 384);
      if (st == 2) tt = t_start + KV1_AT;
      if ((int)(clock() - tt) > 0) tt = clock();
#pragma unroll 1
      for (int i = 0; i < 4; i++) {
        wait_clock(tt);
        tt += st >= 2 ? KV_GAP1 : KV_GAP0;
        tma3d(S_STG + (st & 1) * 16384 + i * 4096, (i & 2) ? &m.v : &m.k, bar, d, tb, (i & 1) * 4);
        if (i == 0) tma3d(S_T + st * 512, &m.kh, bar, d, tb - 1, 5);
      }
    }
    tt = __shfl_sync(~0u, tt, 0);
  }
}

__device__ __forceinline__ void conv_loader(const Maps& m, const Ptrs& p, const ConvCtx& cc, int eb, int lane, unsigned t_start) {
  const unsigned ep = ld_relaxed(g_epoch + eb);
  wait_clock(t_start + SPF_AT);
#pragma unroll 1
  for (int ch = 0; ch < cc.n; ch++) {
    const int d = cc.chan(ch);
    const uint32_t bar = cc.inbar + 8 * (ch & 1), dst = cc.buf + (ch & 1) * 8192;
    const bool first = ch == 0 || ch == (cc.j < 0 ? 3 : 1);
    if (ch >= 2) bar_sync(cc.nb + 2 + (ch & 1), 160);
    if (elect_one()) {
      mbar_expect(cc.inbar + 16, 4096);
      bulk_load(dst + 4096, p.f + (size_t)d * SEQ, 4096, cc.inbar + 16);
      if (!first) { mbar_expect(bar, 4096); tma3d(dst, &m.u, bar, 0, d & 31, d & ~31); }
      if (ch + 1 < cc.n) l2_prefetch(p.f + (size_t)cc.chan(ch + 1) * SEQ, 4096);
    }
    __syncwarp();
    const uint32_t a = dst + 4096 + 128 + (lane >> 3) * 256 + (lane & 7) * 16;
    mbar_wait(cc.inbar + 16, ch & 1);
#pragma unroll 1
    for (uint32_t i = a; i < a + 4096; i += 2048) {
      const uint4 x = lds128(i), y = lds128(i + 1024);
      __syncwarp();
      sts128(i ^ 16, x.x, x.y, x.z, x.w);
      sts128((i ^ 16) + 1024, y.x, y.y, y.z, y.w);
    }
    fence_async_smem();
    __syncwarp();
    if (elect_one()) {
      mbar_arrive(bar);
      if (first) {
        int n = SPIN_LIMIT;
        while ((int)(ld_relaxed(g_flag + (F_U + (d >> 6)) * 32) - (ep + 1) * 16) < 0 && --n) __nanosleep(POLL_NS);
        trap_if(n == 0);
        asm volatile("fence.acquire.gpu;" ::: "memory");
        fence_async_global();
        mbar_expect(bar, 4096);
        tma3d(dst, &m.u, bar, 0, d & 31, d & ~31);
      }
    }
    __syncwarp();
    if (cc.j < 0 && ch == 6) {
      bar_sync(0, 160);
      if (elect_one()) flag_release(F_Z + cc.pj);
      __syncwarp();
    }
  }
  if (cc.j >= 0 && lane == 0) g_epoch[eb] = ep + 1;
}

struct Ring { uint32_t off, par, rel; };
__device__ __forceinline__ void desc_touch(const uint64_t (&c)[12][NS]) {
  uint32_t x = 0;
#pragma unroll
  for (int i = 0; i < 12 * NS; i += 4) x |= (uint32_t)(&c[0][0])[i];
  trap_if((x | (uint32_t)c[11][NS - 1]) == 0);
}
template <int TA, bool TAB, bool LOC = false>
__device__ __forceinline__ void gemm_steps(float (&a0)[64], float (&a1)[64], Ring& r, int n, const uint64_t (&c)[12][NS], int slot, uint32_t bsw = 0) {
#pragma unroll 1
  do {
    const uint32_t off = r.off, rel = r.rel;
    full_wait(B_FULL + off, r.par, slot++);
    r.rel = off;
    r.off += 8;
    if (r.off == 8 * NS) { r.off = 0; r.par ^= 1; }
    WG_FENCE();
#define DESC(i) (*(const uint64_t*)((const char*)c[i] + off))
#pragma unroll
    for (int k = 0; k < 4; k++) {
      const uint64_t db = TAB ? DESC(3 * k) : mkdesc(off * 256 + dlo(sb + 16384 + 32 * k, 16), 1024, 1);
      if (LOC) {
        const int acc = k || rel != B_DUMMY - B_EMPTY;
        wgmma_ss128p<TA>(a0, mkdesc(dlo(S_STG + 32768 + 1024 * k, 4096) - n * 1024, 512, 2), db, acc);
        wgmma_ss128p<TA>(a1, mkdesc(dlo(S_STG + 32768 + 8192 + 1024 * k, 4096) - n * 1024, 512, 2), db, acc);
      } else {
        wgmma_ss128<TA, 0, 1>(a0, TAB ? DESC(3 * k + 1) : mkdesc(off * 256 + bsw + dlo(sb + 32 * k, 16), 1024, 1), db);
        wgmma_ss128<TA, 0, 1>(a1, TAB ? DESC(3 * k + 2) : mkdesc(off * 256 - bsw + dlo(sb + 8192 + 32 * k, 16), 1024, 1), db);
      }
      if (k == RELK) {
        WG_COMMIT();
        WG_WAIT(1);
        if (elect_one()) mbar_arrive(B_EMPTY + rel);
      }
    }
#undef DESC
    if (RELK < 3) WG_COMMIT();
  } while (--n);
}

template <int I>
__device__ __forceinline__ void tail_steps(float (&a0)[64], float (&a1)[64], const Ptrs& p, float* op, const float (&g)[4], uint4& e, uint4& e0, int tid) {
  constexpr int sl = (64 - WIN + I / 2) % NS, k = 2 * (I & 1), J = I - TOFF;
  if (I == 0) WG_FENCE();
  wgmma_ss128<1, 0, 1>(a1, p.dc2[3 * k + 2][sl], p.dc2[3 * k][sl]);
  wgmma_ss128<1, 0, 1>(a1, p.dc2[3 * k + 5][sl], p.dc2[3 * k + 3][sl]);
  WG_COMMIT();
  if (J == 0) { WG_WAIT(TOFF + 1); reg_fence(a0); }
  if (RES == NS && I == (WIN == NS ? 3 : 0)) { WG_WAIT(WIN == NS ? 2 : 1); if (elect_one()) mbar_arrive(B_ZT + 8); }
  if (J >= 0 && J < 2 * NPB) {
    sched_fence_async<70 + 2 * I>();
    constexpr int o = J >= 0 ? J / 2 : 0, jj = jj_of(o), hf = J & 1;
    if (hf == 0) { e0 = e; e = lds128(e_addr(o + 1 < NPB ? o + 1 : 0, o + 1 == NPB) + tid * 16); }
    const uint32_t ex = hf ? e0.z : e0.x, ey = hf ? e0.w : e0.y;
    stg128(op + hf * 32 * DM + 16 * jj, __float_as_uint(fmaf(g[hf], a0[8 * jj + 2 * hf], bf_lo(ex))), __float_as_uint(fmaf(g[hf], a0[8 * jj + 2 * hf + 1], bf_hi(ex))),
           __float_as_uint(fmaf(g[hf], a0[8 * jj + 2 * hf + 4], bf_lo(ey))), __float_as_uint(fmaf(g[hf], a0[8 * jj + 2 * hf + 5], bf_hi(ey))));
    sched_fence_async<71 + 2 * I>();
  }
  if constexpr (I + 1 < 2 * WIN) tail_steps<I + 1>(a0, a1, p, op, g, e, e0, tid);
}

template <bool BY_SM>
__global__ void __launch_bounds__(512, 1) fused_kernel(const __grid_constant__ Maps m, const __grid_constant__ Ptrs p) {
  extern __shared__ __align__(1024) uint8_t smem_raw[];
  if (threadIdx.x == W0 * 32) {
    asm volatile("prefetch.tensormap [%0];" ::"l"(&m.x) : "memory");
    asm volatile("prefetch.tensormap [%0];" ::"l"(&m.b) : "memory");
  }
  int b = blockIdx.x;
  if (BY_SM) {
    int sm;
    asm("mov.u32 %0, %%smid;" : "=r"(sm));
    const int tp = sm >> 1, q = (tp * 37 - 1184) >> 8;
    const int lo = (tp & 7) * 8 + (tp >> 3), mid = (tp - 31 - 7 * q) * 8 + 4 + q, hi = tp + (tp < 62 ? 4 : -58);
    b = (tp < 32 ? lo : (tp < 60 ? mid : hi)) * 2 + (sm & 1);
  }
  const int spare = b - 128;
  const int ti = ((b >> 5) << 2) | (b & 3), pj = (((b >> 4) & 1) << 2) | ((b >> 2) & 3);
  const int wid = __shfl_sync(~0u, threadIdx.x >> 5, 0), wg = wid >> 2, tid = threadIdx.x & 127, lane = threadIdx.x & 31;
  if (wg == 0) TIM(0);
  const unsigned t_start = clock();
  if (wid == W0) {
    if (elect_one()) {
#pragma unroll
      for (int i = 0; i < NS; i++) mbar_init(B_FULL + 8 * i, (i < 2 && spare >= 0) ? 2 : 1);
    }
    __syncwarp();
    bar_arrive(1, 160);
    if (spare < 0 && elect_one()) {
      unsigned t = clock();
#pragma unroll 1
      for (int s = 0; s < NS; s++) {
        issue_g1(m, s, s, ti, pj);
        t += FILL;
        while ((int)(clock() - t) < 0) {}
      }
    }
  } else if (wid == 13) {
    if (elect_one()) {
      trap_if((uint32_t)__cvta_generic_to_shared(smem_raw) != sb);
#pragma unroll
      for (uint32_t bar = B_EMPTY; bar < S_EP; bar += 8) mbar_init(bar, (bar < B_CINF || (bar >= B_SFREE && bar < B_ZT) || bar == B_ZT + 8 || bar == B_XT + 16) ? 4 :
                           (bar < B_CINF + 16 || ((bar == B_PIN || bar == B_PIN + 8) && spare >= 0)) ? 2 : 1);
    }
  }
  __syncwarp();
  if (wg == 3) {
    asm volatile("setmaxnreg.dec.sync.aligned.u32 %0;" ::"n"(RV == 2 ? 32 : 24));
    bar_sync(1, 160);
    if (spare < 0) {
      if (wid == 13) { bar_arrive(2, 160); bar_arrive(12, 160); }
      bar_arrive(0, 256);
    } else {
      bar_arrive(0, 512);
    }
    if (wid == 13) {
      if (spare < 0) {
        const unsigned ep = ld_relaxed(g_epoch + b);
        kv_loader(m, ti, pj, t_start);
        wait_clock(t_start + POLL_AT);
        poller(ti, pj, lane, ep);
      }
    } else if (wid == 15 || spare >= 0) {
      const ConvCtx cc = conv_ctx(spare, wid == 12 ? 0 : wid - 13, ti, pj);
      conv_loader(m, p, cc, spare < 0 ? b : 128 + cc.j, lane, t_start);
    } else if (wid == 12) {
      if (elect_one()) producer(m, ti, pj);
    } else {
      storer(m, ti, pj);
    }
  } else if (wg == 2 || spare >= 0) {
    asm volatile("setmaxnreg.inc.sync.aligned.u32 160;");
    if (HOLD) wait_clock(t_start + HOLD);
    conv_main(p, conv_ctx(spare, wg, ti, pj), spare < 0 ? b : 128 + spare * 3 + wg, tid);
  } else {
    asm volatile("setmaxnreg.inc.sync.aligned.u32 %0;" ::"n"(RV == 3 ? 168 : 160));
    if (wg == 1) {
      if (HOLD) wait_clock(t_start + HOLD);
      const int ch = (tid >> 6) * 512 + pj * 64 + (tid & 63);
      const unsigned ep = ld_relaxed(g_epoch + b);
      const float lr = __bfloat162float(p.lre[ch]), li = __bfloat162float(p.lim[ch]);
      const float dt = bf_round(expf(__bfloat162float(p.ldt[ch])));
      float sn, cs;
      sincosf(dt * li, &sn, &cs);
      const float ex = expf(dt * lr);
      const float ar = ex * cs, ai = ex * sn;
      const float inv = 2.f / (lr * lr + li * li);
      const float cr = ((ar - 1.f) * lr + ai * li) * inv, ci = (ai * lr - (ar - 1.f) * li) * inv;
      sts128(S_PAR + tid * 16, __float_as_uint(ar), __float_as_uint(ai), pack2(cr, cr), pack2(-ci, -ci));
      const cx l32 = csq(csq(csq(csq(csq({ar, ai}))))), l128 = csq(csq(l32));
      sts128(S_PAR + 2048 + tid * 16, __float_as_uint(l32.r), __float_as_uint(l32.i), __float_as_uint(l128.r), __float_as_uint(l128.i));
      if (tid == 0) asm volatile("st.shared.u32 [%0], %1;" ::"r"(S_EP), "r"(ep) : "memory");
      if (tid < 64)
        asm volatile("st.relaxed.gpu.global.v4.u32 [%0], {%1,%1,%1,%1};" ::"l"(g_agg + ((tid >> 5) * 16 + ti) * 256 + pj * 32 + lane), "r"(ep & 3) : "memory");
      asm volatile("st.relaxed.gpu.global.u32 [%0], %1;" ::"l"(g_gate + pj * SEQ + ti * 128 + tid), "r"(ep & 3) : "memory");
      bar_arrive(6, 256);
      bar_sync(2, 160);
      desc_touch(p.dc1);
      desc_touch(p.dc2);
      prep<0>(p, ti, pj, wid & 3, lane);
    }
    uint32_t bsw = p.bsw;
    asm volatile("" : "+r"(bsw));
    float a0[64], a1[64];
    Ring ring = {8u * wg * (16 % NS), wg * ((16u / NS) & 1), B_DUMMY - B_EMPTY};
    zero(a0); zero(a1);
    reg_fence(a0); reg_fence(a1);
    sched_fence<61>();
    bar_sync(wg * 7, 256);
    TIM(2 + wg * 2);
    if (wg == 0) gemm_steps<0, false>(a0, a1, ring, 15, p.dc1, 0, bsw);
    else gemm_steps<0, true>(a0, a1, ring, 15, p.dc1, 16);
    bar_arrive(7 + wg, 256);
    gemm_steps<0, true>(a0, a1, ring, 1, p.dc1, wg * 16 + 15);
    if (wg == 0) bar_sync(6, 256);
    scan_epilogue(a0, a1, B_EMPTY + ring.rel, wg, ti, pj, tid);
    if (wg == 1) {
      eterm(p, ti, pj, tid);
    } else {
      ring = {8 * (32 % NS), (32 / NS) & 1, B_DUMMY - B_EMPTY};
#pragma unroll
      for (int i = 0; i < 64; i++) asm volatile("" : "=f"(a0[i]), "=f"(a1[i]));
      bar_sync(8, 256);
      TIM(6);
#pragma unroll 1
      for (int o = 0; o < 4; o++) {
        if (!(o & 1)) {
          if (o) TIM(18);
          full_wait(B_LOC + 4 * o, 0, 32 + 8 * o);
          gemm_steps<1, true, true>(a0, a1, ring, 2, p.dc2, 32 + 8 * o);
        }
        gemm_steps<1, true>(a0, a1, ring, (o & 1) ? (o == 1 ? 13 : 13 - RES) : 1, p.dc2, 34 + 16 * (o >> 1) + (o & 1));
        if (!(o & 1) && elect_one()) {
          mbar_arrive(o ? B_LOC + 16 : B_SFREE + 16);
        }
      }
      TIM(28);
      const int w = tid >> 5, trow = 64 * (w & 1) + 8 * (w >> 1) + (lane >> 2);
      float* op = p.out + (size_t)(ti * 128 + trow) * DM + pj * 128 + 4 * (lane & 3);
      float g[4];
      uint4 e;
#pragma unroll
      for (int i = 0; i < RES; i++) {
        const int sl = (64 - RES + i) % NS;
        full_wait(B_FULL + 8 * sl, ((64 - RES + i) / NS) & 1, 64 - RES + i);
        WG_FENCE();
#pragma unroll
        for (int k = 0; k < 4; k++) {
          wgmma_ss128<1, 0, 1>(a0, p.dc2[3 * k + 1][sl], p.dc2[3 * k][sl]);
          if (i == 0 && k == 1) { WG_COMMIT(); WG_WAIT(1); if (elect_one()) mbar_arrive(RES == NS ? B_EMPTY + ring.rel : B_ZT + 8); }
        }
        if (i >= WIN - 1 && i < RES - 1) {
          const int s1 = (64 - RES + i - WIN + 1) % NS;
#pragma unroll
          for (int k = 0; k < 4; k++) wgmma_ss128<1, 0, 1>(a1, p.dc2[3 * k + 2][s1], p.dc2[3 * k][s1]);
        }
        WG_COMMIT();
      }
      TIM(25);
      bar_sync(5, 256);
#pragma unroll
      for (int q = 0; q < 4; q++) g[q] = __uint_as_float(lds32(S_G + (trow + 16 * (q >> 1) + 32 * (q & 1)) * 4));
      e = lds128(e_addr(0, NPB == 0) + tid * 16);
      uint4 e0;
      tail_steps<0>(a0, a1, p, op, g, e, e0, tid);
      TIM(26);
      WG_WAIT(0);
      reg_fence(a1);
      TIM(7);
      uint4 ee[4], x[8], z[8];
      uint2 ds[4];
#pragma unroll
      for (int o = 1; o < 4; o++) ee[o] = lds128(e_addr(o, 1) + tid * 16);
      if (NPB < 4) ee[0] = lds128(e_addr(3, 0) + tid * 16);
      store_piece(a1, op + 16 * DM, jj_of(0), e, g[2], g[3]);
      store_piece(a1, op + 16 * DM, jj_of(1), ee[1], g[2], g[3]);
#define LATE_LOAD(h) { \
        sched_fence<90 + h>(); \
        bar_sync(6 + h, 256); \
        _Pragma("unroll") for (int i = 4 * h; i < 4 * h + 4; i++) { \
          x[i] = lds128(e_addr(4 + (i >> 1), i & 1) + tid * 16); \
          z[i] = ldsm4t(S_ZL + (i >> 1) * 4096 + z_off(w, lane, i & 1)); \
          if (i & 1) ds[i >> 1] = lds64(S_PAR + (4 + (i >> 1)) * 32 + (lane & 3) * 8); \
        } }
#define LATE_STORE(o) { store_late(a0, op, jj_of(4 + o), x[2 * o], z[2 * o], ds[o], g[0], g[1]); \
                        store_late(a1, op + 16 * DM, jj_of(4 + o), x[2 * o + 1], z[2 * o + 1], ds[o], g[2], g[3]); }
      LATE_LOAD(0);
      store_piece(a1, op + 16 * DM, jj_of(2), ee[2], g[2], g[3]);
      store_piece(a1, op + 16 * DM, jj_of(3), ee[3], g[2], g[3]);
      if (NPB < 4) { store_piece(a0, op, jj_of(3), ee[0], g[0], g[1]); }
      LATE_STORE(0);
      LATE_LOAD(1);
      LATE_STORE(1);
      sched_fence<92>();
      LATE_STORE(2);
      LATE_STORE(3);
#undef LATE_LOAD
#undef LATE_STORE
      if (tid == 0) g_epoch[b] = lds32(S_EP) + 1;
      TIM(19);
    }
  }
}

typedef CUresult (*EncFn)(CUtensorMap*, CUtensorMapDataType, cuuint32_t, void*, const cuuint64_t*, const cuuint64_t*,
                          const cuuint32_t*, const cuuint32_t*, CUtensorMapInterleave, CUtensorMapSwizzle,
                          CUtensorMapL2promotion, CUtensorMapFloatOOBfill);

void encode(EncFn enc, CUtensorMap* m, const void* ptr, int rank, const cuuint64_t* dims, const cuuint64_t* strides,
            const cuuint32_t* box, CUtensorMapSwizzle sw) {
  cuuint32_t es[5] = {1, 1, 1, 1, 1};
  enc(m, CU_TENSOR_MAP_DATA_TYPE_BFLOAT16, rank, const_cast<void*>(ptr), dims, strides, box, es, CU_TENSOR_MAP_INTERLEAVE_NONE,
      sw, PROMO, CU_TENSOR_MAP_FLOAT_OOB_FILL_NONE);
}

}

extern "C" void kernel_launch(void* const* d_in, const int* in_sizes, int n_in, void* d_out, int out_size) {
  typedef const __nv_bfloat16* bp;
  Ptrs p;
  p.x = (bp)d_in[0]; p.lre = (bp)d_in[1]; p.lim = (bp)d_in[2]; p.bre = (bp)d_in[3]; p.bim = (bp)d_in[4];
  p.cre = (bp)d_in[5]; p.cim = (bp)d_in[6]; p.ldt = (bp)d_in[7]; p.dskip = (bp)d_in[8];
  p.k = (bp)d_in[10]; p.v = (bp)d_in[11]; p.shift = (bp)d_in[12]; p.f = (bp)d_in[13]; p.ssmd = (bp)d_in[14];
  p.gw = (bp)d_in[15]; p.out = (float*)d_out;

  const uint32_t bsw = p.bim < p.bre;
  p.bsw = bsw * 512;
  for (int sl = 0; sl < NS; sl++)
    for (int k = 0; k < 4; k++) {
      const uint64_t h128 = (uint64_t)(64u | (1u << 30)) << 32, h64 = (uint64_t)(32u | (2u << 30)) << 32;
      const uint32_t st = sb + sl * STAGE;
      p.dc1[3 * k][sl] = p.dc2[3 * k][sl] = h128 | dlo(st + 16384 + 32 * k, 16);
      p.dc1[3 * k + 1][sl] = h128 | dlo(st + bsw * 8192 + 32 * k, 16);
      p.dc1[3 * k + 2][sl] = h128 | dlo(st + (1 - bsw) * 8192 + 32 * k, 16);
      p.dc2[3 * k + 1][sl] = h64 | dlo(st + 1024 * k, 4096);
      p.dc2[3 * k + 2][sl] = h64 | dlo(st + 8192 + 1024 * k, 4096);
    }
  EncFn enc = nullptr;
  cudaDriverEntryPointQueryResult qr;
  cudaGetDriverEntryPoint("cuTensorMapEncodeTiled", (void**)&enc, cudaEnableDefault, &qr);
  void *zptr = nullptr, *uptr = nullptr;
  cudaGetSymbolAddress(&zptr, g_z);
  cudaGetSymbolAddress(&uptr, g_u);

  Maps m;
  {
    cuuint64_t d[4] = {1024, 2, 64, 16}, s[3] = {2048, 65536, 4096};
    cuuint32_t bx[4] = {64, 2, 4, 16};
    encode(enc, &m.x, p.x, 4, d, s, bx, CU_TENSOR_MAP_SWIZZLE_128B);
  }
  {
    cuuint64_t d[3] = {1024, 1024, 2}, s[2] = {2048, (cuuint64_t)(bsw ? p.bre - p.bim : p.bim - p.bre) * 2};
    cuuint32_t bx[3] = {64, 64, 2};
    encode(enc, &m.b, bsw ? p.bim : p.bre, 3, d, s, bx, CU_TENSOR_MAP_SWIZZLE_128B);
  }
  {
    cuuint64_t d[5] = {1024, 2, 4, 2, 64}, s[4] = {2048, 8192, 4096, 32768};
    cuuint32_t bx[5] = {64, 2, 4, 2, 8};
    encode(enc, &m.cre, p.cre, 5, d, s, bx, CU_TENSOR_MAP_SWIZZLE_128B);
    encode(enc, &m.cim, p.cim, 5, d, s, bx, CU_TENSOR_MAP_SWIZZLE_128B);
  }
  {
    cuuint64_t d[3] = {64, 32, 1024}, s[2] = {128, 4096};
    cuuint32_t bx[3] = {64, 1, 32};
    encode(enc, &m.u, uptr, 3, d, s, bx, CU_TENSOR_MAP_SWIZZLE_NONE);
  }
  {
    cuuint64_t d[3] = {1024, 256, 8}, s[2] = {16384, 2048};
    cuuint32_t bx[3] = {64, 8, 4}, bh[3] = {64, 1, 3};
    encode(enc, &m.k, p.k, 3, d, s, bx, CU_TENSOR_MAP_SWIZZLE_128B);
    encode(enc, &m.kh, p.k, 3, d, s, bh, CU_TENSOR_MAP_SWIZZLE_NONE);
    encode(enc, &m.v, p.v, 3, d, s, bx, CU_TENSOR_MAP_SWIZZLE_128B);
  }
  {
    cuuint64_t d[5] = {2048, 2, 4, 2, 64}, s[4] = {4096, 16384, 8192, 65536};
    cuuint32_t bx[5] = {64, 2, 4, 2, 1};
    encode(enc, &m.z, zptr, 5, d, s, bx, CU_TENSOR_MAP_SWIZZLE_128B);
  }
  {
    cuuint64_t d[4] = {1024, 2, 4, 256}, s[3] = {8192, 2048, 16384};
    cuuint32_t bx[4] = {64, 2, 4, 16};
    encode(enc, &m.x2, p.x, 4, d, s, bx, CU_TENSOR_MAP_SWIZZLE_128B);
  }
  int dev = 0, nsm = 0;
  cudaGetDevice(&dev);
  cudaDeviceGetAttribute(&nsm, cudaDevAttrMultiProcessorCount, dev);
  auto kern = nsm == 132 ? fused_kernel<true> : fused_kernel<false>;
  cudaFuncSetAttribute(kern, cudaFuncAttributeMaxDynamicSharedMemorySize, SMEM_BYTES);
  kern<<<132, 512, SMEM_BYTES, cudaStreamPerThread>>>(m, p);
}
```

```cpp
#include <cuda_runtime.h>
#include <cuda_bf16.h>
#include <cuda.h>
#include <stdint.h>

namespace {

constexpr int SEQ = 2048, DM = 1024;
#define NSV 5
constexpr int NS = NSV;
constexpr int STAGE = 32768;
#define KV0_AT 300
#define KV_GAP0 600
#define KV1_AT 8200
#define KV_GAP1 450
#define SFM 0
#define RV 1
#define POLL_NS 60
#define IM_NS 40
#define SPF_AT 7000
#define RELK 0
#define RES 4
#define AGG_NS 200
#define ZL_NS 60
#define P2F 3
#define KEEP 16
#define IM_LATE 1
#define MAP 0
#define WIN 4
#define NPB 3
#define TOFF 1
#define W0 8
#define HOLD 1200
#define FILL 450
#define GATE_NS 250
#define POLL_AT 17000
#define LD_GAP 400
#define LDQ ""
#define PROMO CU_TENSOR_MAP_L2_PROMOTION_L2_128B
constexpr uint32_t sb = 1024;
constexpr uint32_t S_STG = sb + NS * STAGE;
constexpr uint32_t S_CIN = S_STG + 32768;
constexpr uint32_t S_T = S_CIN + 16384;
constexpr uint32_t S_M1 = S_T + 8192;
constexpr uint32_t S_M2 = S_M1 + 4096;
constexpr uint32_t S_PAR = S_M2 + 2048;
constexpr uint32_t S_G = S_PAR + 4096;
constexpr uint32_t S_BAR = S_G + 512;
constexpr int SMEM_BYTES = S_BAR + 512 - sb;
constexpr uint32_t B_FULL = S_BAR, B_EMPTY = B_FULL + 8 * NS, B_CINF = B_EMPTY + 8 * NS,
                   B_FLG = B_CINF + 24, B_SFREE = B_FLG + 72, B_LOC = B_SFREE + 24, B_ZT = B_LOC + 24,
                   B_XT = B_ZT + 16, B_PIN = B_XT + 24, B_DUMMY = B_PIN + 32, S_EP = B_DUMMY + 8;
constexpr int SPIN_LIMIT = 1 << 21;
constexpr int F_H = 0, F_U = 128, F_Z = 144;

struct alignas(64) Maps { CUtensorMap x, b, cre, cim, u, z, x2, k, kh, v; };
struct Ptrs {
  uint32_t bsw, pad;
  const __nv_bfloat16 *x, *lre, *lim, *ldt, *dskip, *k, *v, *shift, *f, *ssmd, *gw, *bre, *bim, *cre, *cim;
  float* out;
  uint64_t dc1[12][NS], dc2[12][NS];
};

__device__ uint4 g_h[16 * 32 * 1024];
__device__ uint4 g_u[1024 * 256];
__device__ uint4 g_z[1024 * 256];
__device__ uint4 g_agg[2 * 32 * 256];
__device__ unsigned g_gate[8 * SEQ];
__device__ unsigned g_flag[152 * 32];
__device__ unsigned g_epoch[140];
#define TIM(i)
#define TIMC(i)

#define WG_FENCE() asm volatile("wgmma.fence.sync.aligned;" ::: "memory")
#define WG_COMMIT() asm volatile("wgmma.commit_group.sync.aligned;" ::: "memory")
#define WG_WAIT(n) asm volatile("wgmma.wait_group.sync.aligned %0;" ::"n"(n) : "memory")
#define R8(d, o) "+f"(d[o + 0]), "+f"(d[o + 1]), "+f"(d[o + 2]), "+f"(d[o + 3]), "+f"(d[o + 4]), "+f"(d[o + 5]), "+f"(d[o + 6]), "+f"(d[o + 7])
#define W8(d, o) "=f"(d[o + 0]), "=f"(d[o + 1]), "=f"(d[o + 2]), "=f"(d[o + 3]), "=f"(d[o + 4]), "=f"(d[o + 5]), "=f"(d[o + 6]), "=f"(d[o + 7])
#define L16 "%0,%1,%2,%3,%4,%5,%6,%7,%8,%9,%10,%11,%12,%13,%14,%15"
#define L64 L16 ",%16,%17,%18,%19,%20,%21,%22,%23,%24,%25,%26,%27,%28,%29,%30,%31," \
  "%32,%33,%34,%35,%36,%37,%38,%39,%40,%41,%42,%43,%44,%45,%46,%47,%48,%49,%50,%51,%52,%53,%54,%55,%56,%57,%58,%59,%60,%61,%62,%63"

template <int TA, int TB, int ACC>
__device__ __forceinline__ void wgmma_ss128(float (&d)[64], uint64_t da, uint64_t db) {
  if (ACC)
    asm volatile("wgmma.mma_async.sync.aligned.m64n128k16.f32.bf16.bf16 {" L64 "}, %64, %65, 1, 1, 1, %66, %67;"
                 : R8(d, 0), R8(d, 8), R8(d, 16), R8(d, 24), R8(d, 32), R8(d, 40), R8(d, 48), R8(d, 56)
                 : "l"(da), "l"(db), "n"(TA), "n"(TB));
  else
    asm volatile("wgmma.mma_async.sync.aligned.m64n128k16.f32.bf16.bf16 {" L64 "}, %64, %65, 0, 1, 1, %66, %67;"
                 : W8(d, 0), W8(d, 8), W8(d, 16), W8(d, 24), W8(d, 32), W8(d, 40), W8(d, 48), W8(d, 56)
                 : "l"(da), "l"(db), "n"(TA), "n"(TB));
}
template <int TA>
__device__ __forceinline__ void wgmma_ss128p(float (&d)[64], uint64_t da, uint64_t db, int acc) {
  asm volatile("{.reg .pred p; setp.ne.b32 p, %67, 0;\n"
               "wgmma.mma_async.sync.aligned.m64n128k16.f32.bf16.bf16 {" L64 "}, %64, %65, p, 1, 1, %66, 0;}"
               : R8(d, 0), R8(d, 8), R8(d, 16), R8(d, 24), R8(d, 32), R8(d, 40), R8(d, 48), R8(d, 56)
               : "l"(da), "l"(db), "n"(TA), "r"(acc));
}
template <int ACC, int TB = 0>
__device__ __forceinline__ void wgmma_rs32(float (&d)[16], uint32_t a0, uint32_t a1, uint32_t a2, uint32_t a3, uint64_t db) {
  if (ACC)
    asm volatile("wgmma.mma_async.sync.aligned.m64n32k16.f32.bf16.bf16 {" L16 "}, {%16,%17,%18,%19}, %20, 1, 1, 1, %21;"
                 : R8(d, 0), R8(d, 8) : "r"(a0), "r"(a1), "r"(a2), "r"(a3), "l"(db), "n"(TB));
  else
    asm volatile("wgmma.mma_async.sync.aligned.m64n32k16.f32.bf16.bf16 {" L16 "}, {%16,%17,%18,%19}, %20, 0, 1, 1, %21;"
                 : W8(d, 0), W8(d, 8) : "r"(a0), "r"(a1), "r"(a2), "r"(a3), "l"(db), "n"(TB));
}
template <int N>
__device__ __forceinline__ void reg_fence(float (&d)[N]) {
#pragma unroll
  for (int i = 0; i < N; i++) asm volatile("" : "+f"(d[i])::"memory");
}
__host__ __device__ __forceinline__ constexpr uint32_t dlo(uint32_t addr, uint32_t lbo) { return (addr >> 4) + ((lbo >> 4) << 16); }
__device__ __forceinline__ uint64_t mkdesc(uint32_t lo, uint32_t sbo, uint32_t mode) {
  uint64_t d;
  asm("mov.b64 %0, {%1, %2};" : "=l"(d) : "r"(lo), "r"((sbo >> 4) | (mode << 30)));
  return d;
}
template <int N>
__device__ __forceinline__ void zero(float (&d)[N]) {
#pragma unroll
  for (int i = 0; i < N; i++) d[i] = 0.f;
}
__device__ __forceinline__ void trap_if(int c) {
  asm volatile("{.reg .pred p; .reg .b64 z; setp.ne.s32 p, %0, 0; mov.b64 z, 0; @p st.global.u32 [z], %0;}" ::"r"(c) : "memory");
}
template <int K>
__device__ __forceinline__ void sched_fence() {
  asm volatile("{.reg .pred p; setp.eq.u32 p, %0, %1; @p exit;}" ::"r"(blockIdx.x), "n"(256 + K) : "memory");
}
template <int K>
__device__ __forceinline__ void sched_fence_async() {
  asm volatile("{.reg .pred p; .reg .u32 r; setp.ne.u32 p, %0, %1; @p bra.uni SFE;\n"
               "SFL: nanosleep.u32 1000; mov.u32 r, %%clock; setp.eq.u32 p, r, 0; @p bra.uni SFL;\nSFE: }" ::"r"(blockIdx.x), "n"(256 + K) : "memory");
}
__device__ __forceinline__ bool elect_one() {
  uint32_t pred;
  asm volatile("{.reg .pred p; elect.sync _|p, 0xffffffff; selp.u32 %0, 1, 0, p;}" : "=r"(pred));
  return pred;
}
__device__ __forceinline__ void mbar_init(uint32_t bar, uint32_t cnt) {
  asm volatile("mbarrier.init.shared::cta.b64 [%0], %1;" ::"r"(bar), "r"(cnt) : "memory");
}
__device__ __forceinline__ bool mbar_try(uint32_t bar, uint32_t par) {
  uint32_t ok;
  asm volatile("{.reg .pred p; mbarrier.try_wait.parity.shared::cta.b64 p, [%1], %2; selp.u32 %0, 1, 0, p;}"
               : "=r"(ok) : "r"(bar), "r"(par) : "memory");
  return ok;
}
__device__ __forceinline__ bool mbar_test(uint32_t bar, uint32_t par) {
  uint32_t ok;
  asm volatile("{.reg .pred p; mbarrier.test_wait.parity.shared::cta.b64 p, [%1], %2; selp.u32 %0, 1, 0, p;}"
               : "=r"(ok) : "r"(bar), "r"(par) : "memory");
  return ok;
}
#undef DBGV
#define DBGV ((bar - S_BAR) * 2 + par)
__device__ __forceinline__ void mbar_wait(uint32_t bar, uint32_t par) {
  if (__builtin_expect(!mbar_try(bar, par), 0)) {
    int n = SPIN_LIMIT;
    while (!mbar_try(bar, par) && --n) {}
    trap_if(n == 0);
  }
}
#define full_wait(bar, par, slot) mbar_wait(bar, par)
__device__ __forceinline__ void mbar_wait_long(uint32_t bar, uint32_t par) {
  int n = SPIN_LIMIT;
  while (!mbar_try(bar, par) && --n) __nanosleep(100);
  trap_if(n == 0);
}
#undef DBGV
#define DBGV 0
__device__ __forceinline__ void mbar_arrive(uint32_t bar) {
  asm volatile("mbarrier.arrive.shared::cta.b64 _, [%0];" ::"r"(bar) : "memory");
}
__device__ __forceinline__ void mbar_expect(uint32_t bar, uint32_t bytes) {
  asm volatile("mbarrier.arrive.expect_tx.shared::cta.b64 _, [%0], %1;" ::"r"(bar), "r"(bytes) : "memory");
}
__device__ __forceinline__ void tma2d(uint32_t dst, const CUtensorMap* m, uint32_t bar, int c0, int c1) {
  asm volatile("cp.async.bulk.tensor.2d.shared::cluster.global.mbarrier::complete_tx::bytes [%0], [%1, {%3, %4}], [%2];"
               ::"r"(dst), "l"(m), "r"(bar), "r"(c0), "r"(c1) : "memory");
}
__device__ __forceinline__ void tma3d(uint32_t dst, const CUtensorMap* m, uint32_t bar, int c0, int c1, int c2) {
  asm volatile("cp.async.bulk.tensor.3d.shared::cluster.global.mbarrier::complete_tx::bytes [%0], [%1, {%3, %4, %5}], [%2];"
               ::"r"(dst), "l"(m), "r"(bar), "r"(c0), "r"(c1), "r"(c2) : "memory");
}
__device__ __forceinline__ void tma4d(uint32_t dst, const CUtensorMap* m, uint32_t bar, int c0, int c1, int c2, int c3) {
  asm volatile("cp.async.bulk.tensor.4d.shared::cluster.global.mbarrier::complete_tx::bytes [%0], [%1, {%3, %4, %5, %6}], [%2];"
               ::"r"(dst), "l"(m), "r"(bar), "r"(c0), "r"(c1), "r"(c2), "r"(c3) : "memory");
}
__device__ __forceinline__ void tma5d(uint32_t dst, const CUtensorMap* m, uint32_t bar, int c0, int c1, int c2, int c3, int c4) {
  asm volatile("cp.async.bulk.tensor.5d.shared::cluster.global.mbarrier::complete_tx::bytes [%0], [%1, {%3, %4, %5, %6, %7}], [%2];"
               ::"r"(dst), "l"(m), "r"(bar), "r"(c0), "r"(c1), "r"(c2), "r"(c3), "r"(c4) : "memory");
}
__device__ __forceinline__ void bulk_load(uint32_t dst, const void* src, uint32_t bytes, uint32_t bar) {
  asm volatile("cp.async.bulk.shared::cluster.global.mbarrier::complete_tx::bytes [%0], [%1], %2, [%3];"
               ::"r"(dst), "l"(src), "r"(bytes), "r"(bar) : "memory");
}
__device__ __forceinline__ void l2_prefetch(const void* src, uint32_t bytes) {
  asm volatile("cp.async.bulk.prefetch.L2.global [%0], %1;" ::"l"(src), "r"(bytes) : "memory");
}
__device__ __forceinline__ void bar_sync(int id, int n) { asm volatile("bar.sync %0, %1;" ::"r"(id), "r"(n) : "memory"); }
__device__ __forceinline__ void bar_arrive(int id, int n) { asm volatile("bar.arrive %0, %1;" ::"r"(id), "r"(n) : "memory"); }
__device__ __forceinline__ void fence_async_smem() { asm volatile("fence.proxy.async.shared::cta;" ::: "memory"); }
__device__ __forceinline__ void fence_async_global() { asm volatile("fence.proxy.async.global;" ::: "memory"); }
__device__ __forceinline__ void flag_add(int f) {
  asm volatile("red.relaxed.gpu.global.add.u32 [%0], 1;" ::"l"(g_flag + f * 32) : "memory");
}
__device__ __forceinline__ void flag_release(int f) {
  asm volatile("fence.release.gpu;" ::: "memory");
  flag_add(f);
}
__device__ __forceinline__ unsigned ld_relaxed(const unsigned* p) {
  unsigned v;
  asm volatile("ld.relaxed.gpu.global.u32 %0, [%1];" : "=r"(v) : "l"(p) : "memory");
  return v;
}
__device__ __forceinline__ void wait_clock(unsigned t) {
  int d;
  while ((d = (int)(t - (unsigned)clock())) > 0) __nanosleep(d > 600 ? 200 : 40);
}
__device__ __forceinline__ uint32_t pack2(float lo, float hi) {
  uint32_t r;
  asm("cvt.rn.bf16x2.f32 %0, %1, %2;" : "=r"(r) : "f"(hi), "f"(lo));
  return r;
}
__device__ __forceinline__ float bf_lo(uint32_t v) { return __uint_as_float(v << 16); }
__device__ __forceinline__ float bf_hi(uint32_t v) { return __uint_as_float(v & 0xffff0000u); }
__device__ __forceinline__ float bf_round(float v) { return __bfloat162float(__float2bfloat16_rn(v)); }
__device__ __forceinline__ uint32_t hmul2(uint32_t a, uint32_t b) {
  uint32_t r;
  asm("mul.rn.bf16x2 %0, %1, %2;" : "=r"(r) : "r"(a), "r"(b));
  return r;
}
__device__ __forceinline__ uint32_t hadd2(uint32_t a, uint32_t b) {
  uint32_t r;
  asm("add.rn.bf16x2 %0, %1, %2;" : "=r"(r) : "r"(a), "r"(b));
  return r;
}
__device__ __forceinline__ uint32_t hsub2(uint32_t a, uint32_t b) {
  uint32_t r;
  asm("sub.rn.bf16x2 %0, %1, %2;" : "=r"(r) : "r"(a), "r"(b));
  return r;
}
__device__ __forceinline__ uint32_t hfma2(uint32_t a, uint32_t b, uint32_t c) {
  uint32_t r;
  asm("fma.rn.bf16x2 %0, %1, %2, %3;" : "=r"(r) : "r"(a), "r"(b), "r"(c));
  return r;
}
__device__ __forceinline__ uint32_t hneg2(uint32_t a) {
  uint32_t r;
  asm("neg.bf16x2 %0, %1;" : "=r"(r) : "r"(a));
  return r;
}
__device__ __forceinline__ uint4 ldg128(const void* p) {
  uint4 v;
  asm volatile("ld.global.nc" LDQ ".v4.u32 {%0,%1,%2,%3}, [%4];" : "=r"(v.x), "=r"(v.y), "=r"(v.z), "=r"(v.w) : "l"(p));
  return v;
}
__device__ __forceinline__ uint2 ldg64(const void* p) {
  uint2 v;
  asm volatile("ld.global.nc.v2.u32 {%0,%1}, [%2];" : "=r"(v.x), "=r"(v.y) : "l"(p));
  return v;
}
__device__ __forceinline__ void stg128(void* p, uint32_t a, uint32_t b, uint32_t c, uint32_t d) {
  asm volatile("st.global.v4.u32 [%0], {%1,%2,%3,%4};" ::"l"(p), "r"(a), "r"(b), "r"(c), "r"(d) : "memory");
}
__device__ __forceinline__ void sts128(uint32_t a, uint32_t x, uint32_t y, uint32_t z, uint32_t w) {
  asm volatile("st.shared.v4.u32 [%0], {%1,%2,%3,%4};" ::"r"(a), "r"(x), "r"(y), "r"(z), "r"(w) : "memory");
}
__device__ __forceinline__ uint32_t lds32(uint32_t a) {
  uint32_t v;
  asm volatile("ld.shared.u32 %0, [%1];" : "=r"(v) : "r"(a) : "memory");
  return v;
}
__device__ __forceinline__ uint4 lds128(uint32_t a) {
  uint4 v;
  asm volatile("ld.shared.v4.u32 {%0,%1,%2,%3}, [%4];" : "=r"(v.x), "=r"(v.y), "=r"(v.z), "=r"(v.w) : "r"(a) : "memory");
  return v;
}
__device__ __forceinline__ void stsm4(uint32_t a, uint32_t x, uint32_t y, uint32_t z, uint32_t w) {
  asm volatile("stmatrix.sync.aligned.m8n8.x4.shared.b16 [%0], {%1,%2,%3,%4};" ::"r"(a), "r"(x), "r"(y), "r"(z), "r"(w) : "memory");
}
__device__ __forceinline__ void stsm4t(uint32_t a, uint32_t x, uint32_t y, uint32_t z, uint32_t w) {
  asm volatile("stmatrix.sync.aligned.m8n8.x4.trans.shared.b16 [%0], {%1,%2,%3,%4};" ::"r"(a), "r"(x), "r"(y), "r"(z), "r"(w) : "memory");
}
__device__ __forceinline__ uint4 ldsm4t(uint32_t a) {
  uint4 v;
  asm volatile("ldmatrix.sync.aligned.m8n8.x4.trans.shared.b16 {%0,%1,%2,%3}, [%4];" : "=r"(v.x), "=r"(v.y), "=r"(v.z), "=r"(v.w) : "r"(a) : "memory");
  return v;
}
struct cx { float r, i; };
__device__ __forceinline__ cx cmul(cx a, cx b) { return {a.r * b.r - a.i * b.i, a.r * b.i + a.i * b.r}; }
__device__ __forceinline__ cx cfma(cx a, cx b, cx c) { return {fmaf(a.r, b.r, fmaf(-a.i, b.i, c.r)), fmaf(a.r, b.i, fmaf(a.i, b.r, c.i))}; }
__device__ __forceinline__ cx csq(cx a) { return {a.r * a.r - a.i * a.i, 2.f * a.r * a.i}; }
__device__ __forceinline__ cx unit(int num, int den) {
  int m = num & (den - 1);
  if (m >= den / 2) m -= den;
  float s, c;
  __sincosf((float)m * (-6.283185307179586f / (float)den), &s, &c);
  return {c, s};
}

__device__ __forceinline__ uint2 lds64(uint32_t a) {
  uint2 v;
  asm volatile("ld.shared.v2.u32 {%0,%1}, [%2];" : "=r"(v.x), "=r"(v.y) : "r"(a) : "memory");
  return v;
}
__device__ __forceinline__ void prep_taps(const uint4 (&sh)[2], uint32_t (&s)[2][4]) {
#pragma unroll
  for (int e = 0; e < 2; e++) {
    s[e][0] = __byte_perm(sh[e].x, sh[e].z, 0x5410); s[e][1] = __byte_perm(sh[e].x, sh[e].z, 0x7632);
    s[e][2] = __byte_perm(sh[e].y, sh[e].w, 0x5410); s[e][3] = __byte_perm(sh[e].y, sh[e].w, 0x7632);
  }
}
__device__ __forceinline__ void prep_math(const uint2 (&kk)[11], uint2 (&vv)[8], const uint32_t (&s)[2][4]) {
#pragma unroll
  for (int i = 0; i < 8; i++)
#pragma unroll
    for (int e = 0; e < 2; e++) {
      uint32_t a = hmul2((&kk[i].x)[e], s[e][3]);
      a = hfma2((&kk[i + 1].x)[e], s[e][2], a);
      a = hfma2((&kk[i + 2].x)[e], s[e][1], a);
      a = hfma2((&kk[i + 3].x)[e], s[e][0], a);
      (&vv[i].x)[e] = hmul2(a, (&vv[i].x)[e]);
    }
}
__device__ __forceinline__ void prep_store(const uint2 (&vv)[8], int d, int tb) {
  uint4* dst = g_u + (size_t)((d >> 5) * 32 + (tb >> 3)) * 256 + (d & 31) * 8 + ((tb & 7) ^ ((tb >> 3) & 1));
#pragma unroll
  for (int e = 0; e < 2; e++) {
#define U(i) (&vv[i].x)[e]
    stg128(dst + (2 * e) * 8, __byte_perm(U(0), U(1), 0x5410), __byte_perm(U(2), U(3), 0x5410),
           __byte_perm(U(4), U(5), 0x5410), __byte_perm(U(6), U(7), 0x5410));
    stg128(dst + (2 * e + 1) * 8, __byte_perm(U(0), U(1), 0x7632), __byte_perm(U(2), U(3), 0x7632),
           __byte_perm(U(4), U(5), 0x7632), __byte_perm(U(6), U(7), 0x7632));
#undef U
  }
}
template <int PG>
__device__ __forceinline__ void prep(const Ptrs& p, int ti, int pj, int w, int lane) {
  const int tb = lane & 7, chunk = 2 * w + (lane >> 4), ch = chunk * 8 + ((lane >> 3) & 1) * 4, d = pj * 128 + PG * 64 + ch;
  const uint4 sh[2] = {ldg128(p.shift + d * 4), ldg128(p.shift + d * 4 + 8)};
  uint32_t s[2][4];
  prep_taps(sh, s);
#pragma unroll 1
  for (int th = 0; th < 2; th++) {
    uint2 kk[11], vv[8];
    {
      const uint32_t in = S_STG + th * 16384 + (lane & 8);
      const uint32_t a0 = in + tb * 128 + ((chunk ^ tb) << 4);
      const uint32_t hb = tb ? in + (39 + tb) * 128 + ((chunk ^ (tb - 1)) << 4) : S_T + (PG * 2 + th) * 512 + ch * 2;
      const uint32_t hs = tb ? 1024 : 128;
      mbar_wait_long(B_PIN + 16 * PG + 8 * th, 0);
      if (th) TIM(29 + PG);
#pragma unroll
      for (int i = 0; i < 3; i++) kk[i] = lds64(hb + i * hs);
#pragma unroll
      for (int i = 0; i < 8; i++) { kk[3 + i] = lds64(a0 + i * 1024); vv[i] = lds64(a0 + 8192 + i * 1024); }
      prep_math(kk, vv, s);
      sched_fence<52 + PG>();
    }
    if (!PG) bar_arrive(th ? 11 : 3, 160);
    else if (elect_one()) mbar_arrive(B_SFREE + 8 * th);
    prep_store(vv, d, ti * 16 + th * 8 + tb);
  }
  bar_arrive(4 + PG, 160);
}

__device__ __forceinline__ void gate_finish(int ti, int tid, uint32_t tag) {
  float l;
  int n = SPIN_LIMIT;
  bool bad;
  do {
    __nanosleep(GATE_NS);
    uint32_t v[8], x = 0;
#pragma unroll
    for (int j = 0; j < 8; j++) v[j] = ld_relaxed(g_gate + j * SEQ + ti * 128 + tid) ^ tag;
    l = 0.f;
#pragma unroll
    for (int j = 0; j < 8; j++) { x |= v[j]; l += __uint_as_float(v[j]); }
    bad = __any_sync(~0u, x & 3);
  } while (bad && --n);
  trap_if(n == 0);
  const float g = bf_round(__fdividef(1.f, 1.f + __expf(-bf_round(l))));
  asm volatile("st.shared.f32 [%0], %1;" ::"r"(S_G + tid * 4), "f"(g) : "memory");
}

__device__ __forceinline__ void conv_tables(int tid) {
  {
    const int s = tid >> 5, n1 = tid & 31;
    uint32_t re[4], im[4];
#pragma unroll
    for (int e = 0; e < 4; e++) {
      cx a = unit(n1 * (4 * (8 * s + 2 * e) + 1), 128), b = unit(n1 * (4 * (8 * s + 2 * e + 1) + 1), 128);
      re[e] = pack2(a.r * 0.125f, b.r * 0.125f); im[e] = pack2(a.i * 0.125f, b.i * 0.125f);
    }
    sts128(S_M1 + (2 * s) * 512 + n1 * 16, re[0], re[1], re[2], re[3]);
    sts128(S_M1 + (2 * s + 1) * 512 + n1 * 16, im[0], im[1], im[2], im[3]);
  }
  {
    const int kg = tid >> 5, n = tid & 31;
    const int pi = kg >> 1, po = n >> 4, f2 = n & 15;
    uint32_t fw[4];
#pragma unroll
    for (int e = 0; e < 4; e++) {
      int n2 = (kg & 1) * 8 + 2 * e;
      cx a = unit(n2 * f2, 16), b = unit((n2 + 1) * f2, 16);
      float sg = pi ? -1.f : 1.f;
      float x0 = (pi == po) ? a.r : sg * a.i, x1 = (pi == po) ? b.r : sg * b.i;
      fw[e] = pack2(x0, x1);
    }
    sts128(S_M2 + kg * 512 + n * 16, fw[0], fw[1], fw[2], fw[3]);
  }
  fence_async_smem();
}
__device__ __forceinline__ constexpr int jj_of(int o) { return o == 7 ? 3 : o + (o >= 3); }
__device__ __forceinline__ int conv_chan(int ti, int pj, int jj) { return pj * 128 + jj * 16 + ti; }

struct ConvCtx {
  uint32_t buf, inbar;
  int nb, n;
  int ti, pj, j;
  __device__ __forceinline__ int chan(int c) const {
    return j < 0 ? conv_chan(ti, pj, jj_of(c)) : conv_chan(((j + 12 * c) >> 3) + (((j + 12 * c) >> 3) >= KEEP), (j + 12 * c) & 7, 3);
  }
};
__device__ __forceinline__ ConvCtx conv_ctx(int spare, int wg, int ti, int pj) {
  const int j = spare < 0 ? -1 : spare * 3 + wg;
  return {wg == 2 ? S_CIN : sb + wg * 32768, wg == 2 ? B_CINF : (wg ? B_PIN : B_FULL), 4 + 4 * wg, j < 0 ? 7 + (ti == KEEP) : (j < 8 && KEEP > 15 ? 11 : 10), ti, pj, j};
}
#define CDESC(a) mkdesc(dlo(a, 512), 128, 0)
struct ConvTw { uint32_t r[2], i[2], n[2]; };

__device__ __forceinline__ void cv_tw1(float (&d)[64], uint32_t (&R)[16], uint32_t (&I)[16], const ConvTw& t, int i) {
#pragma unroll
  for (int j = 8 * (i & 1); j < 8 * (i & 1) + 8; j++) {
    if (i < 2) {
      R[j] = pack2(d[4 * j], d[4 * j + 1]); I[j] = pack2(d[4 * j + 2], d[4 * j + 3]);
    } else {
      const uint32_t xr = R[j], xi = I[j];
      R[j] = hfma2(xr, t.r[j & 1], hmul2(xi, t.n[j & 1]));
      I[j] = hfma2(xr, t.i[j & 1], hmul2(xi, t.r[j & 1]));
    }
  }
}
template <int N>
__device__ __forceinline__ void cv_pack(float (&X)[16], uint32_t (&P)[N][2][2], int q) {
#pragma unroll
  for (int k = 0; k < 2; k++)
#pragma unroll
    for (int j = 0; j < 4; j++) P[2 * q + k][j >> 1][j & 1] = pack2(X[4 * j + 2 * k], X[4 * j + 2 * k + 1]);
}
__device__ __forceinline__ void cv_overlap(uint32_t (&P)[8][2][2]) {
#pragma unroll
  for (int k = 3; k > 0; k--)
#pragma unroll
    for (int hh = 0; hh < 2; hh++) {
      P[k][0][hh] = hsub2(P[k][0][hh], P[k - 1][1][hh]);
      P[k][1][hh] = hadd2(P[k][1][hh], P[k - 1][0][hh]);
    }
}
__device__ __forceinline__ void cv_pw(uint32_t (&P)[8][2][2], uint32_t (&Q)[4][2][2]) {
#pragma unroll
  for (int jh = 0; jh < 8; jh++) {
    const int j = jh >> 1, hh = jh & 1;
    uint32_t qr = hmul2(P[4 + j][0][hh], P[0][0][hh]), qi = hmul2(P[4 + j][0][hh], P[0][1][hh]);
    qr = hfma2(hneg2(P[4 + j][1][hh]), P[0][1][hh], qr);
    qi = hfma2(P[4 + j][1][hh], P[0][0][hh], qi);
#pragma unroll
    for (int k = j - 1; k >= 0; k--) {
      qr = hfma2(P[4 + k][0][hh], P[j - k][0][hh], qr);
      qi = hfma2(P[4 + k][0][hh], P[j - k][1][hh], qi);
      qr = hfma2(hneg2(P[4 + k][1][hh]), P[j - k][1][hh], qr);
      qi = hfma2(P[4 + k][1][hh], P[j - k][0][hh], qi);
    }
    Q[j][0][hh] = qr; Q[j][1][hh] = qi;
  }
}
__device__ __forceinline__ void cv_tw2(uint32_t (&Q)[4][2][2], const ConvTw& t, int k) {
#pragma unroll
  for (int hh = 0; hh < 2; hh++) {
    const uint32_t xr = Q[k][0][hh], xi = Q[k][1][hh];
    Q[k][0][hh] = hfma2(xr, t.r[hh], hmul2(xi, t.i[hh]));
    Q[k][1][hh] = hfma2(xr, t.n[hh], hmul2(xi, t.r[hh]));
  }
}
__device__ __forceinline__ void cv_out0(float (&Y)[16], uint32_t T, int w, int lane) {
  reg_fence(Y);
  const uint32_t za = T + w * 2048 + (lane >> 4) * 256 + (lane & 7) * 32 + (((lane >> 3) ^ (lane >> 2)) & 1) * 16;
#pragma unroll
  for (int jj = 0; jj < 2; jj++)
    stsm4t(za + jj * 512, pack2(Y[8 * jj], Y[8 * jj + 1]), pack2(Y[8 * jj + 2], Y[8 * jj + 3]),
           pack2(Y[8 * jj + 4], Y[8 * jj + 5]), pack2(Y[8 * jj + 6], Y[8 * jj + 7]));
}

__device__ __forceinline__ void cv_out1(const uint4& z0, const uint4& z1, const ConvCtx& cc, uint32_t keep, uint32_t tag, int ch, int w, int lane) {
  uint4* zp = g_z + (size_t)cc.chan(ch) * 256 + w * 64 + lane;
#define TG(v) ((v & keep) | (tag & ~keep))
  asm volatile("st.relaxed.gpu.global.v4.u32 [%0], {%1,%2,%3,%4};" ::"l"(zp), "r"(TG(z0.x)), "r"(TG(z0.y)), "r"(TG(z0.z)), "r"(TG(z0.w)) : "memory");
  asm volatile("st.relaxed.gpu.global.v4.u32 [%0], {%1,%2,%3,%4};" ::"l"(zp + 32), "r"(TG(z1.x)), "r"(TG(z1.y)), "r"(TG(z1.z)), "r"(TG(z1.w)) : "memory");
#undef TG
}
template <bool FW, bool BW, int K>
__device__ __forceinline__ void conv_step(uint32_t (&Q)[4][2][2], const ConvTw& t, const ConvCtx& cc, float dl, uint32_t tag, int ch, int w, int lane) {
#define SF(n) if ((SFM >> (n)) & 1) sched_fence_async<K + (n)>()
  float d[64], X[4][16], Z[2][16], Y[16];
  uint32_t R[16], I[16];
  uint4 a[4];
  const int nx = ch + 1;
  const uint32_t T = cc.buf + 16384;
  float dv;
  TIMC(1);
  if (FW) {
    dv = __shfl_sync(~0u, dl, nx);
    mbar_wait(cc.inbar + 8 * (nx & 1), (nx >> 1) & 1);
  }
  TIMC(2);
  WG_FENCE();
  if (BW) {
#pragma unroll
    for (int q = 0; q < 2; q++) {
      wgmma_rs32<0, 1>(Z[q], Q[2 * q][0][0], Q[2 * q + 1][0][0], Q[2 * q][0][1], Q[2 * q + 1][0][1], mkdesc(dlo(S_M2, 128), 512, 0));
      wgmma_rs32<1, 1>(Z[q], Q[2 * q][1][0], Q[2 * q + 1][1][0], Q[2 * q][1][1], Q[2 * q + 1][1][1], mkdesc(dlo(S_M2 + 256, 128), 512, 0));
    }
    WG_COMMIT();
  }
  if (FW) {
    const uint32_t lo = dlo(0, 1024) + (cc.buf >> 4) + (nx & 1) * 512;
    wgmma_ss128<1, 1, 0>(d, mkdesc(dlo(S_M1, 128), 512, 0), mkdesc(lo, 256, 3));
    wgmma_ss128<1, 1, 1>(d, mkdesc(dlo(S_M1 + 256, 128), 512, 0), mkdesc(lo + 32, 256, 3));
    WG_COMMIT();
  }
  TIMC(3);
  if (BW) {
    TIMC(4);
    WG_WAIT(FW ? 1 : 0);
    TIMC(5);
    reg_fence(Z[0]); reg_fence(Z[1]);
    uint32_t V[4][2][2];
    cv_pack(Z[0], V, 0); cv_pack(Z[1], V, 1);
    SF(0);
#pragma unroll
    for (int k = 0; k < 4; k++) cv_tw2(V, t, k);
    bar_sync(cc.nb, 128);
#pragma unroll
    for (int k = 0; k < 4; k++) stsm4(T + w * 512 + lane * 16 + k * 2048, V[k][0][0], V[k][0][1], V[k][1][0], V[k][1][1]);
    SF(1);
    TIMC(6);
  }
  if (FW) {
    WG_WAIT(0);
    reg_fence(d);
    if (nx + 2 < cc.n) bar_arrive(cc.nb + 2 + (nx & 1), 160);
    cv_tw1(d, R, I, t, 0); cv_tw1(d, R, I, t, 1);
    SF(2);
    TIMC(7);
  }
  if (BW) {
    bar_sync(cc.nb, 128);
#pragma unroll
    for (int s = 0; s < 4; s++) a[s] = ldsm4t(T + (4 * w + s) * 512 + lane * 16);
  }
  if (FW) { cv_tw1(d, R, I, t, 2); cv_tw1(d, R, I, t, 3); }
  sched_fence<K + 3>();
  TIMC(8);
  WG_FENCE();
  if (BW) {
    wgmma_rs32<0>(Y, a[0].x, a[0].y, a[0].z, a[0].w, CDESC(S_M1));
#pragma unroll
    for (int i = 1; i < 4; i++) wgmma_rs32<1>(Y, a[i].x, a[i].y, a[i].z, a[i].w, CDESC(S_M1 + 1024 * i));
  }
  if (FW) {
#pragma unroll
    for (int q = 0; q < 4; q++) {
      if (q == 2) WG_COMMIT();
      wgmma_rs32<0>(X[q], R[4 * q], R[4 * q + 2], R[4 * q + 1], R[4 * q + 3], CDESC(S_M2));
      wgmma_rs32<1>(X[q], I[4 * q], I[4 * q + 2], I[4 * q + 1], I[4 * q + 3], CDESC(S_M2 + 1024));
    }
  }
  WG_COMMIT();
  TIMC(9);
  WG_WAIT(FW ? 1 : 0);
  TIMC(10);
  uint4 z0, z1;
  const uint32_t zr = T + w * 2048 + (lane ^ ((lane >> 3) & 1)) * 16;
  if (BW) {
    cv_out0(Y, T, w, lane);
    __syncwarp();
  }
  if (FW) {
    uint32_t P[8][2][2];
    reg_fence(X[0]); reg_fence(X[1]);
    cv_pack(X[0], P, 0); cv_pack(X[1], P, 1);
    cv_overlap(P);
    if (BW) { z0 = lds128(zr); z1 = lds128(zr + 512); }
    sched_fence_async<K + 7>();
    WG_WAIT(0);
    reg_fence(X[2]); reg_fence(X[3]);
    X[2][0] += dv; X[2][1] += dv; X[2][4] += dv; X[2][5] += dv;
    cv_pack(X[2], P, 2); cv_pack(X[3], P, 3);
    SF(4);
    TIMC(11);
    cv_pw(P, Q);
    SF(8);
  } else {
    z0 = lds128(zr); z1 = lds128(zr + 512);
  }
  if (BW) cv_out1(z0, z1, cc, FW && cc.j < 0 && ch < 4 ? ~0u : ~1u, tag, ch, w, lane);
  sched_fence<K + 5>();
  TIMC(13);
#undef SF
}

__device__ __forceinline__ void conv_main(const Ptrs& p, const ConvCtx& cc, int eb, int tid) {
  const int ti = cc.ti, pj = cc.pj;
  const int w = tid >> 5, lane = tid & 31;
  const unsigned ep = ld_relaxed(g_epoch + eb);
  const __nv_bfloat16 dsk = p.ssmd[cc.chan(min(lane, cc.n - 1))];
  if (cc.nb == 12) conv_tables(tid);
  if (cc.j < 0) bar_sync(12, 160); else bar_sync(0, 512);
  ConvTw t;
#pragma unroll
  for (int hh = 0; hh < 2; hh++) {
    const int n2 = 8 * hh + 2 * (lane & 3), m = 4 * (8 * w + (lane >> 2)) + 1;
    cx a = unit(n2 * m, 2048), b = unit((n2 + 1) * m, 2048);
    t.r[hh] = pack2(a.r, b.r); t.i[hh] = pack2(a.i, b.i); t.n[hh] = pack2(-a.i, -b.i);
  }
  const uint32_t tag = (ep + 1) & 3;
  const float dl = 0.125f * __bfloat162float(dsk);
  if (cc.j < 0) prep<1>(p, ti, pj, w, lane);
  {
    uint32_t P[4][2][2];
    mbar_wait_long(cc.inbar, 0);
    TIM(20);
    conv_step<true, false, 10>(P, t, cc, dl, tag, -1, w, lane);
#pragma unroll 1
    for (int ch = 0; ch < cc.n - 1; ch++) {
      conv_step<true, true, 20>(P, t, cc, dl, tag, ch, w, lane);
      if (cc.j < 0 && ch == 3) bar_arrive(0, 160);
      if (ch == 0) TIM(21);
    }
    conv_step<false, true, 30>(P, t, cc, dl, tag, cc.n - 1, w, lane);
  }
  TIM(22);
}

__device__ __forceinline__ cx csel(bool k, cx a, cx b) { return {k ? a.r : b.r, k ? a.i : b.i}; }
__device__ __forceinline__ void ld2cx(uint32_t a, cx& x, cx& y) {
  const uint4 v = lds128(a);
  x = {__uint_as_float(v.x), __uint_as_float(v.y)};
  y = {__uint_as_float(v.z), __uint_as_float(v.w)};
}
__device__ __forceinline__ cx ldcx(uint32_t a) {
  cx x;
  asm volatile("ld.shared.v2.f32 {%0,%1}, [%2];" : "=f"(x.r), "=f"(x.i) : "r"(a) : "memory");
  return x;
}

__device__ __forceinline__ void scan_epilogue(float (&aR)[64], float (&aI)[64], uint32_t last_empty, int ph, int ti, int pj, int tid) {
  const int w = tid >> 5, lane = tid & 31, r = lane >> 2, c = lane & 3;
  const uint32_t par = S_PAR + (ph * 64 + 16 * w + r) * 16;
  uint4* agg = g_agg + (ph * 32 + 16) * 256 + pj * 32 + 8 * w + r;
  const uint32_t tag = (lds32(S_EP) + 1) & 3;
  cx h[2];
  {
    cx lam[2], a[2];
#pragma unroll
    for (int q = 0; q < 2; q++) { lam[q] = ldcx(par + q * 128); h[q] = ldcx(par + 2048 + q * 128); }
    WG_WAIT(0);
    if (elect_one()) mbar_arrive(last_empty);
    asm volatile("setmaxnreg.inc.sync.aligned.u32 168;");
    reg_fence(aR); reg_fence(aI);
    TIM(3 + ph * 2);
#pragma unroll
    for (int q = 0; q < 2; q++) a[q] = {aR[2 * q], aI[2 * q]};
#pragma unroll
    for (int s = 1; s < 32; s++)
#pragma unroll
      for (int q = 0; q < 2; q++) {
        const int i = 4 * (s >> 1) + 2 * q + (s & 1);
        a[q] = cfma(lam[q], a[q], {aR[i], aI[i]});
      }
    sched_fence<1>();
    cx t[2][3];
#pragma unroll
    for (int q = 0; q < 2; q++)
#pragma unroll
      for (int k = 0; k < 3; k++) t[q][k] = {__shfl_up_sync(~0u, a[q].r, k + 1, 4), __shfl_up_sync(~0u, a[q].i, k + 1, 4)};
#pragma unroll
    for (int q = 0; q < 2; q++) {
      const cx z = {0.f, 0.f};
      cx ex = cfma(h[q], csel(c >= 3, t[q][2], z), csel(c >= 2, t[q][1], z));
      ex = cfma(h[q], ex, csel(c >= 1, t[q][0], z));
      a[q] = cfma(h[q], ex, a[q]);
      const cx u = cfma(lam[q], ex, {aR[2 * q], aI[2 * q]});
      aR[2 * q] = u.r; aI[2 * q] = u.i;
    }
    if (c == 3)
      asm volatile("st.relaxed.gpu.global.v4.u32 [%0], {%1,%2,%3,%4};" ::"l"(agg + ti * 256),
                   "r"((__float_as_uint(a[0].r) & ~3u) | tag), "r"((__float_as_uint(a[0].i) & ~3u) | tag),
                   "r"((__float_as_uint(a[1].r) & ~3u) | tag), "r"((__float_as_uint(a[1].i) & ~3u) | tag) : "memory");
    TIM(8 + ph * 4);
  }
  if (ti > 0) {
    const uint2* ap = (const uint2*)(agg + (ti - 1 - (c >> 1)) * 256) + (c & 1);
    const cx one = {1.f, 0.f};
    const cx l128 = ldcx(par + 2048 + 8 + (c & 1) * 128), l256 = csq(l128), fa = csel(c & 2, l128, one);
#pragma unroll
    for (int q = 0; q < 2; q++) h[q] = cmul(csel(c & 1, h[q], one), csel(c & 2, csq(h[q]), one));
    uint2 v[8];
    int n = SPIN_LIMIT;
    bool bad;
    __nanosleep(AGG_NS);
#pragma unroll
    for (int j = 4; j < 8; j++) v[j] = make_uint2(tag, tag);
    do {
      uint32_t x = 0;
#pragma unroll
      for (int j = 0; j < 8; j++)
        if (j < 4 || ti > 8)
          asm volatile("ld.relaxed.gpu.global.v2.u32 {%0,%1}, [%2];" : "=r"(v[j].x), "=r"(v[j].y) : "l"(ap - j * 1024) : "memory");
#pragma unroll
      for (int j = 0; j < 8; j++) x |= (v[j].x ^ tag) | (v[j].y ^ tag);
      bad = __any_sync(~0u, x & 3);
    } while (bad && --n);
    trap_if(n == 0);
#define AG(j) cx{__uint_as_float(v[j].x & ~3u), __uint_as_float(v[j].y & ~3u)}
    const cx l512 = csq(l256);
    cx a = cfma(l512, cfma(l512, cfma(l512, AG(6), AG(4)), AG(2)), AG(0));
    a = cfma(l256, cfma(l512, cfma(l512, cfma(l512, AG(7), AG(5)), AG(3)), AG(1)), a);
#undef AG
    a = cmul(a, fa);
    const cx t1 = {__shfl_xor_sync(~0u, a.r, 1), __shfl_xor_sync(~0u, a.i, 1)};
    const cx t2 = {__shfl_xor_sync(~0u, a.r, 2), __shfl_xor_sync(~0u, a.i, 2)};
    const cx t3 = {__shfl_xor_sync(~0u, a.r, 3), __shfl_xor_sync(~0u, a.i, 3)};
    const cx own = {a.r + t2.r, a.i + t2.i}, oth = {t1.r + t3.r, t1.i + t3.i};
#pragma unroll
    for (int q = 0; q < 2; q++) h[q] = cmul(csel((c & 1) == q, own, oth), h[q]);
  } else {
    h[0] = h[1] = {0.f, 0.f};
  }
  TIM(9 + ph * 4);
  cx lam[2];
  uint32_t cr[2], nci[2];
#pragma unroll
  for (int q = 0; q < 2; q++) {
    const uint4 v = lds128(par + q * 128);
    lam[q] = {__uint_as_float(v.x), __uint_as_float(v.y)};
    cr[q] = v.z; nci[q] = v.w;
  }
  uint4* hg = g_h + (size_t)(ti * 32 + ph * 16 + pj) * 1024 + w * 64 + r * 4 + (c ^ (r >> 1));
  const uint32_t hs = S_STG + w * 1024 + r * 64 + ((c ^ (r >> 1)) << 4);
  uint32_t pr[4][2][4], pi[4][2][4], re[4][2][4];
#pragma unroll
  for (int i = 0; i < 4; i++) {
#pragma unroll
    for (int s2 = 0; s2 < 4; s2++)
#pragma unroll
      for (int q = 0; q < 2; q++) {
        const int k = 4 * (4 * i + s2) + 2 * q;
        cx h0 = cfma(lam[q], h[q], {aR[k], aI[k]});
        h[q] = cfma(lam[q], h0, {aR[k + 1], aI[k + 1]});
        pr[i][q][s2] = pack2(h0.r, h[q].r);
        pi[i][q][s2] = pack2(h0.i, h[q].i);
        re[i][q][s2] = hfma2(pr[i][q][s2], cr[q], hmul2(pi[i][q][s2], nci[q]));
      }
#pragma unroll
    for (int q = 0; q < 2; q++) {
      stg128(hg + i * 256 + q * 32, re[i][q][0], re[i][q][1], re[i][q][2], re[i][q][3]);
    }
    if (i == 0 && (P2F & 1)) sched_fence<7>();
    if (i == 1 && (P2F & 2)) sched_fence<8>();
    if (i == 2 && (P2F & 1)) sched_fence<6>();
  }
  bar_arrive(9, 160);
  sched_fence<9>();
  TIM(10 + ph * 4);
  mbar_wait(B_SFREE + 16 * ph, 0);
  if (ph == 0) mbar_wait(B_SFREE + 8, 0);
#pragma unroll
  for (int q = 0; q < 2; q++) {
    const uint32_t ncr = cr[q] ^ 0x80008000u;
#pragma unroll
    for (int i = 0; i < 4; i++) {
#pragma unroll
      for (int s2 = 0; s2 < 4; s2++) pi[i][q][s2] = hfma2(pi[i][q][s2], ncr, hmul2(pr[i][q][s2], nci[q]));
      sts128(hs + i * 4096 + q * 512, re[i][q][0], re[i][q][1], re[i][q][2], re[i][q][3]);
      sts128(hs + 16384 + i * 4096 + q * 512, pi[i][q][0], pi[i][q][1], pi[i][q][2], pi[i][q][3]);
      if (!IM_LATE) {
        if (IM_NS) __nanosleep(IM_NS);
        stg128(hg + 8192 + i * 256 + q * 32, pi[i][q][0], pi[i][q][1], pi[i][q][2], pi[i][q][3]);
      }
    }
  }
  fence_async_smem();
  __syncwarp();
  if (elect_one()) mbar_arrive(B_LOC + 8 * ph);
  if (IM_LATE) {
#pragma unroll
    for (int i = 0; i < 8; i++) {
      stg128(hg + 8192 + (i >> 1) * 256 + (i & 1) * 32, pi[i >> 1][i & 1][0], pi[i >> 1][i & 1][1], pi[i >> 1][i & 1][2], pi[i >> 1][i & 1][3]);
      if (IM_NS) __nanosleep(IM_NS);
    }
  }
  bar_arrive(10, 160);
  bar_sync(1 + ph, 128);
  asm volatile("setmaxnreg.dec.sync.aligned.u32 160;");
}

__device__ __forceinline__ constexpr uint32_t e_addr(int o, int mh) { return S_STG + (o * 2 + mh) * 2048; }
__device__ __forceinline__ uint32_t z_off(int w, int lane, int mh) {
  return (w & 1) * 2048 + (lane & 15) * 128 + (((4 * (lane >> 4) + 2 * mh + (w >> 1)) ^ (lane & 7)) << 4);
}
constexpr uint32_t S_ZL = sb + (59 % NS) * STAGE;
__device__ __forceinline__ void eterm(const Ptrs& p, int ti, int pj, int tid) {
  const int w = tid >> 5, lane = tid & 31, r = lane >> 2, c = lane & 3;
  const int trow = 64 * (w & 1) + 8 * (w >> 1) + r;
  const int rs = 2 * (r & 3) + (r >> 2);
  uint2 xv[2][8][2], ds[8];
  {
    uint2 gw[8];
#pragma unroll
    for (int jj = 0; jj < 8; jj++) {
      gw[jj] = ldg64(p.gw + pj * 128 + 16 * jj + 4 * c);
      ds[jj] = ldg64(p.dskip + pj * 128 + 16 * jj + 4 * c);
    }
#pragma unroll
    for (int g = 0; g < 2; g++) {
      mbar_wait(B_XT + 8 * g, 0);
#pragma unroll
      for (int i = 0; i < 4; i++)
#pragma unroll
        for (int jj = 4 * g; jj < 4 * g + 4; jj++)
          xv[i >> 1][jj][i & 1] = lds64(sb + ((48 + g) % NS) * STAGE + (trow - r + rs + 16 * (i >> 1) + 32 * (i & 1)) * 128 + (((2 * (jj & 3) + (c >> 1)) ^ rs) << 4) + (c & 1) * 8);
    }
    fence_async_smem();
    __syncwarp();
    if (elect_one()) mbar_arrive(B_XT + 16);
    sched_fence<55>();
    TIM(27);
    float s[4];
#pragma unroll
    for (int i = 0; i < 4; i++) {
      s[i] = 0.f;
#pragma unroll
      for (int jj = 0; jj < 8; jj += 2) {
        const uint2 x = xv[i >> 1][jj][i & 1], y = xv[i >> 1][jj + 1][i & 1];
        const uint32_t q = hfma2(x.x, gw[jj].x, hfma2(x.y, gw[jj].y, hfma2(y.x, gw[jj + 1].x, hmul2(y.y, gw[jj + 1].y))));
        s[i] += bf_lo(q) + bf_hi(q);
      }
    }
    float u0 = (c & 1) ? s[1] : s[0], v0 = (c & 1) ? s[0] : s[1];
    float u1 = (c & 1) ? s[3] : s[2], v1 = (c & 1) ? s[2] : s[3];
    u0 += __shfl_xor_sync(~0u, v0, 1);
    u1 += __shfl_xor_sync(~0u, v1, 1);
    float u = (c & 2) ? u1 : u0;
    u += __shfl_xor_sync(~0u, (c & 2) ? u0 : u1, 2);
    const uint32_t tag = (lds32(S_EP) + 1) & 3;
    asm volatile("st.relaxed.gpu.global.u32 [%0], %1;" ::"l"(g_gate + pj * SEQ + ti * 128 + trow + 16 * (c >> 1) + 32 * (c & 1)),
                 "r"((__float_as_uint(u) & ~3u) | tag) : "memory");
    gate_finish(ti, tid, tag);
  }
  bar_sync(2, 128);
  TIM(31);
  uint32_t g2[2][2], og2[2][2];
#pragma unroll
  for (int mh = 0; mh < 2; mh++)
#pragma unroll
    for (int hf = 0; hf < 2; hf++) {
      uint32_t g;
      asm volatile("ld.shared.u32 %0, [%1];" : "=r"(g) : "r"(S_G + (trow + 16 * mh + 32 * hf) * 4) : "memory");
      g2[mh][hf] = __byte_perm(g, g, 0x3232);
      og2[mh][hf] = hsub2(0x3f803f80u, g2[mh][hf]);
    }
  mbar_wait_long(B_LOC + 16, 0);
#pragma unroll
  for (int o = 4; o < 8; o++) {
    const int jj = jj_of(o);
#pragma unroll
    for (int mh = 0; mh < 2; mh++) sts128(e_addr(o, mh) + tid * 16, xv[mh][jj][0].x, xv[mh][jj][0].y, xv[mh][jj][1].x, xv[mh][jj][1].y);
    if (tid < 4) asm volatile("st.shared.v2.u32 [%0], {%1,%2};" ::"r"(S_PAR + o * 32 + tid * 8), "r"(ds[jj].x), "r"(ds[jj].y) : "memory");
  }
  mbar_wait_long(B_ZT, 0);
#pragma unroll
  for (int mh = 0; mh < 2; mh++)
#pragma unroll
    for (int o = 0; o < 4; o++) {
      const int jj = jj_of(o);
      const uint4 z = ldsm4t(S_STG + o * 4096 + z_off(w, lane, mh));
#pragma unroll
      for (int hf = 0; hf < 2; hf++) {
        uint2& x = xv[mh][jj][hf];
        x.x = hmul2(x.x, hfma2(og2[mh][hf], hf ? z.z : z.x, hmul2(g2[mh][hf], ds[jj].x)));
        x.y = hmul2(x.y, hfma2(og2[mh][hf], hf ? z.w : z.y, hmul2(g2[mh][hf], ds[jj].y)));
      }
    }
  bar_sync(2, 128);
#pragma unroll
  for (int mh = 0; mh < 2; mh++)
#pragma unroll
    for (int o = 0; o < 4; o++) {
      const int jj = jj_of(o);
      sts128(e_addr(o, mh) + tid * 16, xv[mh][jj][0].x, xv[mh][jj][0].y, xv[mh][jj][1].x, xv[mh][jj][1].y);
    }
  bar_arrive(5, 256);
  TIM(1);
  const uint32_t tag = (lds32(S_EP) + 1) & 1;
  const int zn = tid >> 4, ck = tid & 15;
  const uint4* zp = g_z + (size_t)(pj * 128 + 4 * (zn >> 1) + (zn & 1)) * 256 + ti * 16 + ck;
  uint4 v[2][4];
#define ZLOAD(g) _Pragma("unroll") for (int i = 0; i < 4; i++) \
    asm volatile("ld.relaxed.gpu.global.v4.u32 {%0,%1,%2,%3}, [%4];" : "=r"(v[g][i].x), "=r"(v[g][i].y), "=r"(v[g][i].z), "=r"(v[g][i].w) \
                 : "l"(zp + (jj_of(4 + 2 * g + (i >> 1)) * 16 + 2 * (i & 1)) * 256) : "memory")
  mbar_wait_long(B_ZT + 8, 0);
  ZLOAD(0);
  ZLOAD(1);
#pragma unroll
  for (int g = 0; g < 2; g++) {
    int it = SPIN_LIMIT;
    while (true) {
      uint32_t x = 0;
#pragma unroll
      for (int i = 0; i < 4; i++) {
        v[g][i].x ^= tag; v[g][i].y ^= tag; v[g][i].z ^= tag; v[g][i].w ^= tag;
        x |= v[g][i].x | v[g][i].y | v[g][i].z | v[g][i].w;
      }
      if (!__any_sync(~0u, x & 1) || !--it) break;
      __nanosleep(ZL_NS);
      ZLOAD(g);
    }
    trap_if(it == 0);
#pragma unroll
    for (int i = 0; i < 4; i++)
      sts128(S_ZL + (2 * g + (i >> 1)) * 4096 + (ck >> 3) * 2048 + (8 * (i & 1) + zn) * 128 + (((ck & 7) ^ zn) << 4), v[g][i].x, v[g][i].y, v[g][i].z, v[g][i].w);
    bar_arrive(6 + g, 256);
    if (g == 0) TIM(23);
  }
#undef ZLOAD
  TIM(17);
}

__device__ __forceinline__ void store_late(float (&a)[64], float* op, int jj, const uint4& x, const uint4& z, const uint2& ds, float g0, float g1) {
#pragma unroll
  for (int hf = 0; hf < 2; hf++) {
    const float g = hf ? g1 : g0, og = bf_round(1.f - g);
    const uint32_t x0 = hf ? x.z : x.x, x1 = hf ? x.w : x.y, z0 = hf ? z.z : z.x, z1 = hf ? z.w : z.y;
    const int k = 8 * jj + 2 * hf;
    stg128(op + hf * 32 * DM + 16 * jj,
           __float_as_uint(fmaf(g, a[k], bf_lo(x0) * fmaf(og, bf_lo(z0), g * bf_lo(ds.x)))),
           __float_as_uint(fmaf(g, a[k + 1], bf_hi(x0) * fmaf(og, bf_hi(z0), g * bf_hi(ds.x)))),
           __float_as_uint(fmaf(g, a[k + 4], bf_lo(x1) * fmaf(og, bf_lo(z1), g * bf_lo(ds.y)))),
           __float_as_uint(fmaf(g, a[k + 5], bf_hi(x1) * fmaf(og, bf_hi(z1), g * bf_hi(ds.y)))));
  }
}
__device__ __forceinline__ void store_piece(float (&a)[64], float* op, int jj, const uint4& e, float g0, float g1) {
  stg128(op + 16 * jj, __float_as_uint(fmaf(g0, a[8 * jj], bf_lo(e.x))), __float_as_uint(fmaf(g0, a[8 * jj + 1], bf_hi(e.x))),
         __float_as_uint(fmaf(g0, a[8 * jj + 4], bf_lo(e.y))), __float_as_uint(fmaf(g0, a[8 * jj + 5], bf_hi(e.y))));
  stg128(op + 32 * DM + 16 * jj, __float_as_uint(fmaf(g1, a[8 * jj + 2], bf_lo(e.z))), __float_as_uint(fmaf(g1, a[8 * jj + 3], bf_hi(e.z))),
         __float_as_uint(fmaf(g1, a[8 * jj + 6], bf_lo(e.w))), __float_as_uint(fmaf(g1, a[8 * jj + 7], bf_hi(e.w))));
}

__device__ __forceinline__ void issue_g1(const Maps& m, int s, int sl, int ti, int pj) {
  const uint32_t bar = B_FULL + 8 * sl, dst = sb + sl * STAGE;
  const int k0 = (s & 15) * 64, ch = (s >> 4) * 512 + pj * 64;
  mbar_expect(bar, STAGE);
  tma4d(dst + 16384, &m.x, bar, k0, 0, 4 * ti, 0);
  tma3d(dst, &m.b, bar, k0, ch, 0);
}
#define SLOT_WAIT "{.reg .pred p; .reg .u32 n; .reg .b64 z;\n mov.u32 n, 0;\n" \
    "W: mbarrier.try_wait.parity.shared::cta.b64 p, [%0 + %2], %1;\n @p bra.uni G;\n" \
    "add.u32 n, n, 1; setp.lt.u32 p, n, %3; @p bra.uni W;\n mov.b64 z, 0; st.global.u32 [z], n;\n" \
    "G: mbarrier.arrive.expect_tx.shared::cta.b64 _, [%0], 32768;\n"
__device__ __forceinline__ void producer(const Maps& m, int ti, int pj) {
  uint32_t bar = B_FULL, par = 0;
#define NEXT_SLOT() const uint32_t b0 = bar, p0 = par, dst = (bar - B_FULL) * (STAGE / 8) + sb; \
    bar += 8; if (bar == B_FULL + 8 * NS) { bar = B_FULL; par ^= 1; }
#pragma unroll 1
  for (int ph = 0; ph < 2; ph++)
#pragma unroll 1
    for (int k0 = ph ? 0 : NS * 64; k0 < 1024; k0 += 64) {
      NEXT_SLOT();
      asm volatile(SLOT_WAIT
          "cp.async.bulk.tensor.4d.shared::cluster.global.mbarrier::complete_tx::bytes [%4], [%6, {%8, %11, %10, %11}], [%0];\n"
          "cp.async.bulk.tensor.3d.shared::cluster.global.mbarrier::complete_tx::bytes [%5], [%7, {%8, %9, %11}], [%0];}"
          ::"r"(b0), "r"(p0), "n"(8 * NS), "n"(SPIN_LIMIT), "r"(dst + 16384), "r"(dst), "l"(&m.x), "l"(&m.b), "r"(k0),
            "r"(ph * 512 + pj * 64), "r"(4 * ti), "r"(0) : "memory");
    }
#pragma unroll 1
  for (int seg = 0; seg < 8; seg++) {
    const int ph = seg >> 2, part = (seg >> 1) & 1;
    if ((seg & 3) == 0) {
#pragma unroll 1
      for (int u = 0; u < 2; u++) {
        NEXT_SLOT();
        mbar_wait(b0 + 8 * NS, p0);
        mbar_expect(b0, 16384);
        tma5d(dst + 16384, u ? &m.cim : &m.cre, b0, ph * 512 + pj * 64, 0, 0, 0, pj * 8);
        if (ph) {
          mbar_expect(B_XT + 8 * u, 16384);
          tma4d(dst, &m.x2, B_XT + 8 * u, pj * 128 + u * 64, 0, 0, ti * 16);
        }
      }
    }
    const CUtensorMap* cm = part ? &m.cim : &m.cre;
    const uint4* hp = g_h + (size_t)(ti * 4 + (seg >> 1)) * 8192;
    const int s0 = (pj ^ (seg << 2)) & 4;
    mbar_wait(B_FLG + 8 * seg, 0);
    fence_async_global();
    if (seg == 4) TIM(24);
    if (seg == 5) mbar_wait(B_XT + 16, 0);
#pragma unroll 1
    for (int src = s0; src < s0 + 4; src++) {
      if (src == pj) continue;
      NEXT_SLOT();
      asm volatile(SLOT_WAIT
          "cp.async.bulk.shared::cluster.global.mbarrier::complete_tx::bytes [%5], [%7], 16384, [%0];\n"
          "cp.async.bulk.tensor.5d.shared::cluster.global.mbarrier::complete_tx::bytes [%4], [%6, {%8, %10, %10, %10, %9}], [%0];}"
          ::"r"(b0), "r"(p0), "n"(8 * NS), "n"(SPIN_LIMIT), "r"(dst + 16384), "r"(dst), "l"(cm), "l"(hp + src * 1024),
            "r"(ph * 512 + src * 64), "r"(pj * 8), "r"(0) : "memory");
    }
  }
#undef NEXT_SLOT
}

__device__ __forceinline__ void poller(int ti, int pj, int lane, unsigned ep) {
  if (lane < 9) {
    const int f = lane < 8 ? F_H + ((lane >> 1) * 16 + ti) * 2 + ((pj >> 2) ^ (lane & 1)) : F_Z + pj;
    const unsigned need = (ep + 1) * (lane < 8 ? 4 : 16);
    int n = SPIN_LIMIT;
    unsigned todo = 0x1ffu;
    do {
      const unsigned hit = __ballot_sync(0x1ffu, (int)(ld_relaxed(g_flag + f * 32) - need) >= 0) & todo;
      if (hit) {
        asm volatile("fence.acquire.gpu;" ::: "memory");
        if ((hit >> lane) & 1) mbar_arrive(B_FLG + 8 * lane);
        todo ^= hit;
        if (!todo) break;
      }
      if (POLL_NS) __nanosleep(POLL_NS);
    } while (--n);
    trap_if(n == 0);
  }
}
__device__ __forceinline__ void storer(const Maps& m, int ti, int pj) {
#pragma unroll 1
  for (int job = 0; job < 6; job++) {
    bar_sync(job < 2 ? 4 + job : 9 + (job & 1), 160);
    if (elect_one()) flag_release(job < 2 ? F_U + pj * 2 + job : F_H + ((job - 2) * 16 + ti) * 2 + (pj >> 2));
    __syncwarp();
    if (job == 2 || job == 4) TIM(7 + job * 2);
  }
  if (elect_one()) {
    mbar_wait_long(B_LOC + 16, 0);
    mbar_wait_long(B_FLG + 64, 0);
    fence_async_global();
    mbar_expect(B_ZT, 16384);
#pragma unroll 1
    for (int o = 0; o < 4; o++) {
      tma5d(S_STG + o * 4096, &m.z, B_ZT, ti * 128, 0, 0, 0, pj * 8 + jj_of(o));
      tma5d(S_STG + o * 4096 + 2048, &m.z, B_ZT, ti * 128 + 64, 0, 0, 0, pj * 8 + jj_of(o));
    }
  }
}

__device__ __forceinline__ void kv_loader(const Maps& m, int ti, int pj, unsigned t_start) {
  unsigned tt = t_start + KV0_AT;
#pragma unroll 1
  for (int st = 0; st < 4; st++) {
    const int d = pj * 128 + (st >> 1) * 64, tb = ti * 16 + (st & 1) * 8;
    const uint32_t bar = B_PIN + 8 * st;
    if (st >= 2) { bar_sync(st == 2 ? 3 : 11, 160); fence_async_smem(); }
    if (elect_one()) {
      mbar_expect(bar, 16384 + 384);
      if (st == 2) tt = t_start + KV1_AT;
      if ((int)(clock() - tt) > 0) tt = clock();
#pragma unroll 1
      for (int i = 0; i < 4; i++) {
        wait_clock(tt);
        tt += st >= 2 ? KV_GAP1 : KV_GAP0;
        tma3d(S_STG + (st & 1) * 16384 + i * 4096, (i & 2) ? &m.v : &m.k, bar, d, tb, (i & 1) * 4);
        if (i == 0) tma3d(S_T + st * 512, &m.kh, bar, d, tb - 1, 5);
      }
    }
    tt = __shfl_sync(~0u, tt, 0);
  }
}

__device__ __forceinline__ void conv_loader(const Maps& m, const Ptrs& p, const ConvCtx& cc, int eb, int lane, unsigned t_start) {
  const unsigned ep = ld_relaxed(g_epoch + eb);
  wait_clock(t_start + SPF_AT);
#pragma unroll 1
  for (int ch = 0; ch < cc.n; ch++) {
    const int d = cc.chan(ch);
    const uint32_t bar = cc.inbar + 8 * (ch & 1), dst = cc.buf + (ch & 1) * 8192;
    const bool first = ch == 0 || ch == (cc.j < 0 ? 3 : 1);
    if (ch >= 2) bar_sync(cc.nb + 2 + (ch & 1), 160);
    if (elect_one()) {
      mbar_expect(cc.inbar + 16, 4096);
      bulk_load(dst + 4096, p.f + (size_t)d * SEQ, 4096, cc.inbar + 16);
      if (!first) { mbar_expect(bar, 4096); tma3d(dst, &m.u, bar, 0, d & 31, d & ~31); }
      if (ch + 1 < cc.n) l2_prefetch(p.f + (size_t)cc.chan(ch + 1) * SEQ, 4096);
    }
    __syncwarp();
    const uint32_t a = dst + 4096 + 128 + (lane >> 3) * 256 + (lane & 7) * 16;
    mbar_wait(cc.inbar + 16, ch & 1);
#pragma unroll 1
    for (uint32_t i = a; i < a + 4096; i += 2048) {
      const uint4 x = lds128(i), y = lds128(i + 1024);
      __syncwarp();
      sts128(i ^ 16, x.x, x.y, x.z, x.w);
      sts128((i ^ 16) + 1024, y.x, y.y, y.z, y.w);
    }
    fence_async_smem();
    __syncwarp();
    if (elect_one()) {
      mbar_arrive(bar);
      if (first) {
        int n = SPIN_LIMIT;
        while ((int)(ld_relaxed(g_flag + (F_U + (d >> 6)) * 32) - (ep + 1) * 16) < 0 && --n) __nanosleep(POLL_NS);
        trap_if(n == 0);
        asm volatile("fence.acquire.gpu;" ::: "memory");
        fence_async_global();
        mbar_expect(bar, 4096);
        tma3d(dst, &m.u, bar, 0, d & 31, d & ~31);
      }
    }
    __syncwarp();
    if (cc.j < 0 && ch == 6) {
      bar_sync(0, 160);
      if (elect_one()) flag_release(F_Z + cc.pj);
      __syncwarp();
    }
  }
  if (cc.j >= 0 && lane == 0) g_epoch[eb] = ep + 1;
}

struct Ring { uint32_t off, par, rel; };
__device__ __forceinline__ void desc_touch(const uint64_t (&c)[12][NS]) {
  uint32_t x = 0;
#pragma unroll
  for (int i = 0; i < 12 * NS; i += 4) x |= (uint32_t)(&c[0][0])[i];
  trap_if((x | (uint32_t)c[11][NS - 1]) == 0);
}
template <int TA, bool TAB, bool LOC = false>
__device__ __forceinline__ void gemm_steps(float (&a0)[64], float (&a1)[64], Ring& r, int n, const uint64_t (&c)[12][NS], int slot, uint32_t bsw = 0) {
#pragma unroll 1
  do {
    const uint32_t off = r.off, rel = r.rel;
    full_wait(B_FULL + off, r.par, slot++);
    r.rel = off;
    r.off += 8;
    if (r.off == 8 * NS) { r.off = 0; r.par ^= 1; }
    WG_FENCE();
#define DESC(i) (*(const uint64_t*)((const char*)c[i] + off))
#pragma unroll
    for (int k = 0; k < 4; k++) {
      const uint64_t db = TAB ? DESC(3 * k) : mkdesc(off * 256 + dlo(sb + 16384 + 32 * k, 16), 1024, 1);
      if (LOC) {
        const int acc = k || rel != B_DUMMY - B_EMPTY;
        wgmma_ss128p<TA>(a0, mkdesc(dlo(S_STG + 32768 + 1024 * k, 4096) - n * 1024, 512, 2), db, acc);
        wgmma_ss128p<TA>(a1, mkdesc(dlo(S_STG + 32768 + 8192 + 1024 * k, 4096) - n * 1024, 512, 2), db, acc);
      } else {
        wgmma_ss128<TA, 0, 1>(a0, TAB ? DESC(3 * k + 1) : mkdesc(off * 256 + bsw + dlo(sb + 32 * k, 16), 1024, 1), db);
        wgmma_ss128<TA, 0, 1>(a1, TAB ? DESC(3 * k + 2) : mkdesc(off * 256 - bsw + dlo(sb + 8192 + 32 * k, 16), 1024, 1), db);
      }
      if (k == RELK) {
        WG_COMMIT();
        WG_WAIT(1);
        if (elect_one()) mbar_arrive(B_EMPTY + rel);
      }
    }
#undef DESC
    if (RELK < 3) WG_COMMIT();
  } while (--n);
}

template <int I>
__device__ __forceinline__ void tail_steps(float (&a0)[64], float (&a1)[64], const Ptrs& p, float* op, const float (&g)[4], uint4& e, uint4& e0, int tid) {
  constexpr int sl = (64 - WIN + I / 2) % NS, k = 2 * (I & 1), J = I - TOFF;
  if (I == 0) WG_FENCE();
  wgmma_ss128<1, 0, 1>(a1, p.dc2[3 * k + 2][sl], p.dc2[3 * k][sl]);
  wgmma_ss128<1, 0, 1>(a1, p.dc2[3 * k + 5][sl], p.dc2[3 * k + 3][sl]);
  WG_COMMIT();
  if (J == 0) { WG_WAIT(TOFF + 1); reg_fence(a0); }
  if (RES == NS && I == (WIN == NS ? 3 : 0)) { WG_WAIT(WIN == NS ? 2 : 1); if (elect_one()) mbar_arrive(B_ZT + 8); }
  if (J >= 0 && J < 2 * NPB) {
    sched_fence_async<70 + 2 * I>();
    constexpr int o = J >= 0 ? J / 2 : 0, jj = jj_of(o), hf = J & 1;
    if (hf == 0) { e0 = e; e = lds128(e_addr(o + 1 < NPB ? o + 1 : 0, o + 1 == NPB) + tid * 16); }
    const uint32_t ex = hf ? e0.z : e0.x, ey = hf ? e0.w : e0.y;
    stg128(op + hf * 32 * DM + 16 * jj, __float_as_uint(fmaf(g[hf], a0[8 * jj + 2 * hf], bf_lo(ex))), __float_as_uint(fmaf(g[hf], a0[8 * jj + 2 * hf + 1], bf_hi(ex))),
           __float_as_uint(fmaf(g[hf], a0[8 * jj + 2 * hf + 4], bf_lo(ey))), __float_as_uint(fmaf(g[hf], a0[8 * jj + 2 * hf + 5], bf_hi(ey))));
    sched_fence_async<71 + 2 * I>();
  }
  if constexpr (I + 1 < 2 * WIN) tail_steps<I + 1>(a0, a1, p, op, g, e, e0, tid);
}

template <bool BY_SM>
__global__ void __launch_bounds__(512, 1) fused_kernel(const __grid_constant__ Maps m, const __grid_constant__ Ptrs p) {
  extern __shared__ __align__(1024) uint8_t smem_raw[];
  if (threadIdx.x == W0 * 32) {
    asm volatile("prefetch.tensormap [%0];" ::"l"(&m.x) : "memory");
    asm volatile("prefetch.tensormap [%0];" ::"l"(&m.b) : "memory");
  }
  int b = blockIdx.x;
  if (BY_SM) {
    int sm;
    asm("mov.u32 %0, %%smid;" : "=r"(sm));
    const int tp = sm >> 1, q = (tp * 37 - 1184) >> 8;
    const int lo = (tp & 7) * 8 + (tp >> 3), mid = (tp - 31 - 7 * q) * 8 + 4 + q, hi = tp + (tp < 62 ? 4 : -58);
    b = (tp < 32 ? lo : (tp < 60 ? mid : hi)) * 2 + (sm & 1);
  }
  const int spare = b - 128;
  const int ti = ((b >> 5) << 2) | (b & 3), pj = (((b >> 4) & 1) << 2) | ((b >> 2) & 3);
  const int wid = __shfl_sync(~0u, threadIdx.x >> 5, 0), wg = wid >> 2, tid = threadIdx.x & 127, lane = threadIdx.x & 31;
  if (wg == 0) TIM(0);
  const unsigned t_start = clock();
  if (wid == W0) {
    if (elect_one()) {
#pragma unroll
      for (int i = 0; i < NS; i++) mbar_init(B_FULL + 8 * i, (i < 2 && spare >= 0) ? 2 : 1);
    }
    __syncwarp();
    bar_arrive(1, 160);
    if (spare < 0 && elect_one()) {
      unsigned t = clock();
#pragma unroll 1
      for (int s = 0; s < NS; s++) {
        issue_g1(m, s, s, ti, pj);
        t += FILL;
        while ((int)(clock() - t) < 0) {}
      }
    }
  } else if (wid == 13) {
    if (elect_one()) {
      trap_if((uint32_t)__cvta_generic_to_shared(smem_raw) != sb);
#pragma unroll
      for (uint32_t bar = B_EMPTY; bar < S_EP; bar += 8) mbar_init(bar, (bar < B_CINF || (bar >= B_SFREE && bar < B_ZT) || bar == B_ZT + 8 || bar == B_XT + 16) ? 4 :
                           (bar < B_CINF + 16 || ((bar == B_PIN || bar == B_PIN + 8) && spare >= 0)) ? 2 : 1);
    }
  }
  __syncwarp();
  if (wg == 3) {
    asm volatile("setmaxnreg.dec.sync.aligned.u32 %0;" ::"n"(RV == 2 ? 32 : 24));
    bar_sync(1, 160);
    if (spare < 0) {
      if (wid == 13) { bar_arrive(2, 160); bar_arrive(12, 160); }
      bar_arrive(0, 256);
    } else {
      bar_arrive(0, 512);
    }
    if (wid == 13) {
      if (spare < 0) {
        const unsigned ep = ld_relaxed(g_epoch + b);
        kv_loader(m, ti, pj, t_start);
        wait_clock(t_start + POLL_AT);
        poller(ti, pj, lane, ep);
      }
    } else if (wid == 15 || spare >= 0) {
      const ConvCtx cc = conv_ctx(spare, wid == 12 ? 0 : wid - 13, ti, pj);
      conv_loader(m, p, cc, spare < 0 ? b : 128 + cc.j, lane, t_start);
    } else if (wid == 12) {
      if (elect_one()) producer(m, ti, pj);
    } else {
      storer(m, ti, pj);
    }
  } else if (wg == 2 || spare >= 0) {
    asm volatile("setmaxnreg.inc.sync.aligned.u32 160;");
    if (HOLD) wait_clock(t_start + HOLD);
    conv_main(p, conv_ctx(spare, wg, ti, pj), spare < 0 ? b : 128 + spare * 3 + wg, tid);
  } else {
    asm volatile("setmaxnreg.inc.sync.aligned.u32 %0;" ::"n"(RV == 3 ? 168 : 160));
    if (wg == 1) {
      if (HOLD) wait_clock(t_start + HOLD);
      const int ch = (tid >> 6) * 512 + pj * 64 + (tid & 63);
      const unsigned ep = ld_relaxed(g_epoch + b);
      const float lr = __bfloat162float(p.lre[ch]), li = __bfloat162float(p.lim[ch]);
      const float dt = bf_round(expf(__bfloat162float(p.ldt[ch])));
      float sn, cs;
      sincosf(dt * li, &sn, &cs);
      const float ex = expf(dt * lr);
      const float ar = ex * cs, ai = ex * sn;
      const float inv = 2.f / (lr * lr + li * li);
      const float cr = ((ar - 1.f) * lr + ai * li) * inv, ci = (ai * lr - (ar - 1.f) * li) * inv;
      sts128(S_PAR + tid * 16, __float_as_uint(ar), __float_as_uint(ai), pack2(cr, cr), pack2(-ci, -ci));
      const cx l32 = csq(csq(csq(csq(csq({ar, ai}))))), l128 = csq(csq(l32));
      sts128(S_PAR + 2048 + tid * 16, __float_as_uint(l32.r), __float_as_uint(l32.i), __float_as_uint(l128.r), __float_as_uint(l128.i));
      if (tid == 0) asm volatile("st.shared.u32 [%0], %1;" ::"r"(S_EP), "r"(ep) : "memory");
      asm volatile("st.relaxed.gpu.global.v4.u32 [%0], {%1,%1,%1,%1};" ::"l"(g_agg + ((tid >> 5) * 16 + ti) * 256 + pj * 32 + lane),
                   "r"((ep + 1 - ((tid >> 5) & 1)) & 3) : "memory");
      asm volatile("st.relaxed.gpu.global.u32 [%0], %1;" ::"l"(g_gate + pj * SEQ + ti * 128 + tid), "r"(ep & 3) : "memory");
      bar_arrive(6, 256);
      bar_sync(2, 160);
      desc_touch(p.dc1);
      desc_touch(p.dc2);
      prep<0>(p, ti, pj, wid & 3, lane);
    }
    uint32_t bsw = p.bsw;
    asm volatile("" : "+r"(bsw));
    float a0[64], a1[64];
    Ring ring = {8u * wg * (16 % NS), wg * ((16u / NS) & 1), B_DUMMY - B_EMPTY};
    zero(a0); zero(a1);
    reg_fence(a0); reg_fence(a1);
    sched_fence<61>();
    bar_sync(wg * 7, 256);
    TIM(2 + wg * 2);
    if (wg == 0) gemm_steps<0, false>(a0, a1, ring, 15, p.dc1, 0, bsw);
    else gemm_steps<0, true>(a0, a1, ring, 15, p.dc1, 16);
    bar_arrive(7 + wg, 256);
    gemm_steps<0, true>(a0, a1, ring, 1, p.dc1, wg * 16 + 15);
    if (wg == 0) bar_sync(6, 256);
    scan_epilogue(a0, a1, B_EMPTY + ring.rel, wg, ti, pj, tid);
    if (wg == 1) {
      eterm(p, ti, pj, tid);
    } else {
      ring = {8 * (32 % NS), (32 / NS) & 1, B_DUMMY - B_EMPTY};
#pragma unroll
      for (int i = 0; i < 64; i++) asm volatile("" : "=f"(a0[i]), "=f"(a1[i]));
      bar_sync(8, 256);
      TIM(6);
#pragma unroll 1
      for (int o = 0; o < 4; o++) {
        if (!(o & 1)) {
          if (o) TIM(18);
          full_wait(B_LOC + 4 * o, 0, 32 + 8 * o);
          gemm_steps<1, true, true>(a0, a1, ring, 2, p.dc2, 32 + 8 * o);
        }
        gemm_steps<1, true>(a0, a1, ring, (o & 1) ? (o == 1 ? 13 : 13 - RES) : 1, p.dc2, 34 + 16 * (o >> 1) + (o & 1));
        if (!(o & 1) && elect_one()) {
          mbar_arrive(o ? B_LOC + 16 : B_SFREE + 16);
        }
      }
      TIM(28);
      const int w = tid >> 5, trow = 64 * (w & 1) + 8 * (w >> 1) + (lane >> 2);
      float* op = p.out + (size_t)(ti * 128 + trow) * DM + pj * 128 + 4 * (lane & 3);
      float g[4];
      uint4 e;
#pragma unroll
      for (int i = 0; i < RES; i++) {
        const int sl = (64 - RES + i) % NS;
        full_wait(B_FULL + 8 * sl, ((64 - RES + i) / NS) & 1, 64 - RES + i);
        WG_FENCE();
#pragma unroll
        for (int k = 0; k < 4; k++) {
          wgmma_ss128<1, 0, 1>(a0, p.dc2[3 * k + 1][sl], p.dc2[3 * k][sl]);
          if (i == 0 && k == 1) { WG_COMMIT(); WG_WAIT(1); if (elect_one()) mbar_arrive(RES == NS ? B_EMPTY + ring.rel : B_ZT + 8); }
        }
        if (i >= WIN - 1 && i < RES - 1) {
          const int s1 = (64 - RES + i - WIN + 1) % NS;
#pragma unroll
          for (int k = 0; k < 4; k++) wgmma_ss128<1, 0, 1>(a1, p.dc2[3 * k + 2][s1], p.dc2[3 * k][s1]);
        }
        WG_COMMIT();
      }
      TIM(25);
      bar_sync(5, 256);
#pragma unroll
      for (int q = 0; q < 4; q++) g[q] = __uint_as_float(lds32(S_G + (trow + 16 * (q >> 1) + 32 * (q & 1)) * 4));
      e = lds128(e_addr(0, NPB == 0) + tid * 16);
      uint4 e0;
      tail_steps<0>(a0, a1, p, op, g, e, e0, tid);
      TIM(26);
      WG_WAIT(0);
      reg_fence(a1);
      TIM(7);
      uint4 ee[4], x[8], z[8];
      uint2 ds[4];
#pragma unroll
      for (int o = 1; o < 4; o++) ee[o] = lds128(e_addr(o, 1) + tid * 16);
      if (NPB < 4) ee[0] = lds128(e_addr(3, 0) + tid * 16);
      store_piece(a1, op + 16 * DM, jj_of(0), e, g[2], g[3]);
      store_piece(a1, op + 16 * DM, jj_of(1), ee[1], g[2], g[3]);
#define LATE_LOAD(h) { \
        sched_fence<90 + h>(); \
        bar_sync(6 + h, 256); \
        _Pragma("unroll") for (int i = 4 * h; i < 4 * h + 4; i++) { \
          x[i] = lds128(e_addr(4 + (i >> 1), i & 1) + tid * 16); \
          z[i] = ldsm4t(S_ZL + (i >> 1) * 4096 + z_off(w, lane, i & 1)); \
          if (i & 1) ds[i >> 1] = lds64(S_PAR + (4 + (i >> 1)) * 32 + (lane & 3) * 8); \
        } }
#define LATE_STORE(o) { store_late(a0, op, jj_of(4 + o), x[2 * o], z[2 * o], ds[o], g[0], g[1]); \
                        store_late(a1, op + 16 * DM, jj_of(4 + o), x[2 * o + 1], z[2 * o + 1], ds[o], g[2], g[3]); }
      LATE_LOAD(0);
      store_piece(a1, op + 16 * DM, jj_of(2), ee[2], g[2], g[3]);
      store_piece(a1, op + 16 * DM, jj_of(3), ee[3], g[2], g[3]);
      if (NPB < 4) { store_piece(a0, op, jj_of(3), ee[0], g[0], g[1]); }
      LATE_STORE(0);
      LATE_LOAD(1);
      LATE_STORE(1);
      sched_fence<92>();
      LATE_STORE(2);
      LATE_STORE(3);
#undef LATE_LOAD
#undef LATE_STORE
      if (tid == 0) g_epoch[b] = lds32(S_EP) + 1;
      TIM(19);
    }
  }
}

typedef CUresult (*EncFn)(CUtensorMap*, CUtensorMapDataType, cuuint32_t, void*, const cuuint64_t*, const cuuint64_t*,
                          const cuuint32_t*, const cuuint32_t*, CUtensorMapInterleave, CUtensorMapSwizzle,
                          CUtensorMapL2promotion, CUtensorMapFloatOOBfill);

void encode(EncFn enc, CUtensorMap* m, const void* ptr, int rank, const cuuint64_t* dims, const cuuint64_t* strides,
            const cuuint32_t* box, CUtensorMapSwizzle sw) {
  cuuint32_t es[5] = {1, 1, 1, 1, 1};
  enc(m, CU_TENSOR_MAP_DATA_TYPE_BFLOAT16, rank, const_cast<void*>(ptr), dims, strides, box, es, CU_TENSOR_MAP_INTERLEAVE_NONE,
      sw, PROMO, CU_TENSOR_MAP_FLOAT_OOB_FILL_NONE);
}

}

extern "C" void kernel_launch(void* const* d_in, const int* in_sizes, int n_in, void* d_out, int out_size) {
  typedef const __nv_bfloat16* bp;
  Ptrs p;
  p.x = (bp)d_in[0]; p.lre = (bp)d_in[1]; p.lim = (bp)d_in[2]; p.bre = (bp)d_in[3]; p.bim = (bp)d_in[4];
  p.cre = (bp)d_in[5]; p.cim = (bp)d_in[6]; p.ldt = (bp)d_in[7]; p.dskip = (bp)d_in[8];
  p.k = (bp)d_in[10]; p.v = (bp)d_in[11]; p.shift = (bp)d_in[12]; p.f = (bp)d_in[13]; p.ssmd = (bp)d_in[14];
  p.gw = (bp)d_in[15]; p.out = (float*)d_out;

  const uint32_t bsw = p.bim < p.bre;
  p.bsw = bsw * 512;
  for (int sl = 0; sl < NS; sl++)
    for (int k = 0; k < 4; k++) {
      const uint64_t h128 = (uint64_t)(64u | (1u << 30)) << 32, h64 = (uint64_t)(32u | (2u << 30)) << 32;
      const uint32_t st = sb + sl * STAGE;
      p.dc1[3 * k][sl] = p.dc2[3 * k][sl] = h128 | dlo(st + 16384 + 32 * k, 16);
      p.dc1[3 * k + 1][sl] = h128 | dlo(st + bsw * 8192 + 32 * k, 16);
      p.dc1[3 * k + 2][sl] = h128 | dlo(st + (1 - bsw) * 8192 + 32 * k, 16);
      p.dc2[3 * k + 1][sl] = h64 | dlo(st + 1024 * k, 4096);
      p.dc2[3 * k + 2][sl] = h64 | dlo(st + 8192 + 1024 * k, 4096);
    }
  EncFn enc = nullptr;
  cudaDriverEntryPointQueryResult qr;
  cudaGetDriverEntryPoint("cuTensorMapEncodeTiled", (void**)&enc, cudaEnableDefault, &qr);
  void *zptr = nullptr, *uptr = nullptr;
  cudaGetSymbolAddress(&zptr, g_z);
  cudaGetSymbolAddress(&uptr, g_u);

  Maps m;
  {
    cuuint64_t d[4] = {1024, 2, 64, 16}, s[3] = {2048, 65536, 4096};
    cuuint32_t bx[4] = {64, 2, 4, 16};
    encode(enc, &m.x, p.x, 4, d, s, bx, CU_TENSOR_MAP_SWIZZLE_128B);
  }
  {
    cuuint64_t d[3] = {1024, 1024, 2}, s[2] = {2048, (cuuint64_t)(bsw ? p.bre - p.bim : p.bim - p.bre) * 2};
    cuuint32_t bx[3] = {64, 64, 2};
    encode(enc, &m.b, bsw ? p.bim : p.bre, 3, d, s, bx, CU_TENSOR_MAP_SWIZZLE_128B);
  }
  {
    cuuint64_t d[5] = {1024, 2, 4, 2, 64}, s[4] = {2048, 8192, 4096, 32768};
    cuuint32_t bx[5] = {64, 2, 4, 2, 8};
    encode(enc, &m.cre, p.cre, 5, d, s, bx, CU_TENSOR_MAP_SWIZZLE_128B);
    encode(enc, &m.cim, p.cim, 5, d, s, bx, CU_TENSOR_MAP_SWIZZLE_128B);
  }
  {
    cuuint64_t d[3] = {64, 32, 1024}, s[2] = {128, 4096};
    cuuint32_t bx[3] = {64, 1, 32};
    encode(enc, &m.u, uptr, 3, d, s, bx, CU_TENSOR_MAP_SWIZZLE_NONE);
  }
  {
    cuuint64_t d[3] = {1024, 256, 8}, s[2] = {16384, 2048};
    cuuint32_t bx[3] = {64, 8, 4}, bh[3] = {64, 1, 3};
    encode(enc, &m.k, p.k, 3, d, s, bx, CU_TENSOR_MAP_SWIZZLE_128B);
    encode(enc, &m.kh, p.k, 3, d, s, bh, CU_TENSOR_MAP_SWIZZLE_NONE);
    encode(enc, &m.v, p.v, 3, d, s, bx, CU_TENSOR_MAP_SWIZZLE_128B);
  }
  {
    cuuint64_t d[5] = {2048, 2, 4, 2, 64}, s[4] = {4096, 16384, 8192, 65536};
    cuuint32_t bx[5] = {64, 2, 4, 2, 1};
    encode(enc, &m.z, zptr, 5, d, s, bx, CU_TENSOR_MAP_SWIZZLE_128B);
  }
  {
    cuuint64_t d[4] = {1024, 2, 4, 256}, s[3] = {8192, 2048, 16384};
    cuuint32_t bx[4] = {64, 2, 4, 16};
    encode(enc, &m.x2, p.x, 4, d, s, bx, CU_TENSOR_MAP_SWIZZLE_128B);
  }
  int dev = 0, nsm = 0;
  cudaGetDevice(&dev);
  cudaDeviceGetAttribute(&nsm, cudaDevAttrMultiProcessorCount, dev);
  auto kern = nsm == 132 ? fused_kernel<true> : fused_kernel<false>;
  cudaFuncSetAttribute(kern, cudaFuncAttributeMaxDynamicSharedMemorySize, SMEM_BYTES);
  kern<<<132, 512, SMEM_BYTES, cudaStreamPerThread>>>(m, p);
}
```
